```python
import torch

def _softmax(x, axis=-1):
    return torch.softmax(x, dim=axis)
def _gelu(x):
    return torch.nn.functional.gelu(x, approximate="tanh")
def _silu(x):
    return torch.nn.functional.silu(x)
def _sigmoid(x):
    return torch.sigmoid(x)
def _layernorm(x, axis=-1, eps=1e-5):
    m = x.mean(dim=axis, keepdim=True)
    v = x.var(dim=axis, keepdim=True, unbiased=False)
    return (x - m) / torch.sqrt(v + eps)
def _scatter_add(tgt, idx, src, axis=0):
    return tgt.clone().index_add_(axis, idx, src)
def _segment_sum(src, seg, n):
    out = torch.zeros((n,) + src.shape[1:], dtype=src.dtype)
    return out.index_add_(0, seg, src)
def _pad(x, pw):
    flat = tuple(v for pair in reversed(pw) for v in pair)
    return torch.nn.functional.pad(x, flat)

kernel_name = 'recurrent_scan__compressed_kv_cla__moe_arch_mod__prompt'

def setup_inputs():

    _w = (lambda a: (lambda t: t.to(torch.bfloat16) if t.is_floating_point() else t)(torch.as_tensor(a)))
    def _A_setup():
        B, H, Sq, Sk, D, M = 1, 32, 2048, 2048, 128, 1024
        Dc = 4 * D
        return {
            "x": _w((lambda *s: torch.randn(*s, dtype=torch.bfloat16) * 0.05)(B, Sq, M)),
            "c_kv": _w((lambda *s: torch.randn(*s, dtype=torch.bfloat16) * 0.2)(B, Sk, Dc)),
            "w_q": _w((lambda *s: torch.randn(*s, dtype=torch.bfloat16) * 3.2)(M, H, D) * (M ** -0.5)),
            "w_uk": _w((lambda *s: torch.randn(*s, dtype=torch.bfloat16) * 3.2)(Dc, H, D) * (Dc ** -0.5)),
            "w_uv": _w((lambda *s: torch.randn(*s, dtype=torch.bfloat16) * 0.2)(Dc, H, D) * (Dc ** -0.5)),
            "w_o": _w((lambda *s: torch.randn(*s, dtype=torch.bfloat16) * 0.2)(H, D, M) * ((H * D) ** -0.5)),
        }
    _A_in = _A_setup()

    def _B_setup():
        B, S, D, F, C = 1, 2048, 1024, 3584, 2
        return {
            "x": _w((lambda *s: torch.randn(*s, dtype=torch.bfloat16) * 0.05)(B, S, D)),
            "w_r": _w((lambda *s: torch.randn(*s, dtype=torch.bfloat16) * 0.2)(D)),
            "w_gate": _w((lambda *s: torch.randn(*s, dtype=torch.bfloat16) * 0.1)(D, F)),
            "w_up": _w((lambda *s: torch.randn(*s, dtype=torch.bfloat16) * 0.1)(D, F)),
            "w_down": _w((lambda *s: torch.randn(*s, dtype=torch.bfloat16) * 0.1)(F, D)),
        }
    _B_in = _B_setup()

    return {
        "A_x": _A_in["x"],
        "A_c_kv": _A_in["c_kv"],
        "A_w_q": _A_in["w_q"],
        "A_w_uk": _A_in["w_uk"],
        "A_w_uv": _A_in["w_uv"],
        "A_w_o": _A_in["w_o"],
        "B_x": _B_in["x"],
        "B_w_r": _B_in["w_r"],
        "B_w_gate": _B_in["w_gate"],
        "B_w_up": _B_in["w_up"],
        "B_w_down": _B_in["w_down"],
    }

def reference(A_x, A_c_kv, A_w_q, A_w_uk, A_w_uv, A_w_o, B_x, B_w_r, B_w_gate, B_w_up, B_w_down):
    def _A_ref(x, c_kv, w_q, w_uk, w_uv, w_o):
        B, Sq, M = x.shape[0], x.shape[1], x.shape[2]
        Sk = c_kv.shape[1]
        H, D = w_q.shape[1], w_q.shape[2]
        q = torch.einsum("bqm,mhd->bhqd", x, w_q)
        k = torch.einsum("bkc,chd->bhkd", c_kv, w_uk)
        v = torch.einsum("bkc,chd->bhkd", c_kv, w_uv)
        scores = torch.einsum("bhqd,bhkd->bhqk", q, k) * (D ** -0.5)
        off = Sk - Sq
        qi = torch.arange(Sq)[:, None]
        kj = torch.arange(Sk)[None, :]
        cmask = kj <= (qi + off)
        scores = torch.where(cmask[None, None], scores, -1e9)
        p = _softmax(scores, axis=-1)
        ctx = torch.einsum("bhqk,bhkd->bhqd", p, v)
        return torch.einsum("bhqd,hdm->bqm", ctx, w_o)

    def _B_ref(x, w_r, w_gate, w_up, w_down):
        B, S, D = x.shape
        C = 2
        r = x @ w_r
        idx = torch.argsort(-r, axis=-1)[:, :C]
        idx_e = (lambda x, n, axis: torch.repeat_interleave(x, n, dim=axis))(idx.reshape(B, C, 1), D, axis=2)
        x_sel = (lambda x, i, axis: torch.take_along_dim(x, i, dim=axis))(x, idx_e, axis=1)
        g = _silu(x_sel @ w_gate)
        u = x_sel @ w_up
        y = (g * u) @ w_down
        r_sel = _sigmoid((lambda x, i, axis: torch.take_along_dim(x, i, dim=axis))(r, idx, axis=1))
        y = y * r_sel.reshape(B, C, 1)
        b_off = (torch.arange(B) * S).reshape(B, 1)
        flat_idx = (idx + b_off).reshape(B * C)
        zero = (x * 0.0).reshape(B * S, D)
        upd = _scatter_add(zero, flat_idx, y.reshape(B * C, D), axis=0)
        return x + upd.reshape(B, S, D)

    x = A_x
    xn = _layernorm(x, axis=-1)
    s = _A_ref(xn, A_c_kv, A_w_q, A_w_uk, A_w_uv, A_w_o)
    g = _silu(_B_ref(xn, B_w_r, B_w_gate, B_w_up, B_w_down))
    return x + s * g
```

```cpp
#include <cuda_runtime.h>
#include <cuda_bf16.h>
#include <cuda.h>
#include <stdint.h>
#define KTRY 1
#define MASKV 1
#define EREL 1
#define NSUM 2
#define EARLY 2
#define PMINIT 1
#define QSPLIT 1
#define PARK0 1
#define MG 8
#define LQEND 4
#define QKORD 1
#define BALLOT 1
#define AMAP 1
#define EARLYW 2
#define QSCALE 1
#define INPLACE 1

namespace {

constexpr int SEQ = 2048, DM = 1024, NH = 32, DC = 512, FF = 3584;
constexpr int PAGE = 16384;
constexpr int NRING = 12;
constexpr int NCTA = 132, NMAIN = 128;
constexpr uint32_t SM_REGION = NRING * PAGE;
constexpr uint32_t SM_BAR = (NRING + 2) * PAGE;
constexpr uint32_t BAR_FULL = SM_BAR, BAR_EMPTY = SM_BAR + 64;
constexpr uint32_t BAR_DEP = SM_BAR + 128;
constexpr uint32_t BAR_G = SM_BAR + 184;
constexpr uint32_t BAR_DONE = SM_BAR + 200;
constexpr uint32_t BAR_EMPTYL = SM_BAR + 216;
constexpr int NBAR = 35;
constexpr uint32_t SM_PROF = SM_BAR + 320;
constexpr int SMEM_BYTES = SM_PROF + 512;
constexpr uint32_t SPIN_LIMIT = 1u << 16;
constexpr uint32_t POLL_MASK = 7;

struct SyncBlock {
    unsigned done;       unsigned pad0[31];
    unsigned ln;         unsigned pad1[31];
    unsigned router;     unsigned pad4[31];
    unsigned ffn_ticket; unsigned pad2[31];
    unsigned ffn_done;   unsigned pad3[31];
    unsigned kv[NH * 8];
    unsigned kvfree[16 * 8];
    unsigned ctx[32 * NH];
};

__device__ __align__(1024) uint8_t g_xn[8 * 16 * 4 * 8192];
__device__ __align__(4096) uint8_t g_kv[16 * 16 * 65536];
__device__ __align__(4096) uint8_t g_ctx[16 * 64 * 16384];
__device__ __align__(16) uint4 g_routed[2 * 128];
__device__ int g_sel[2];
__device__ __align__(16) float g_r[SEQ];
__device__ __align__(16) float g_ypart[4 * 2 * DM];
__device__ SyncBlock g_sync;

__device__ __forceinline__ uint32_t smem_u32(const void* p) { return (uint32_t)__cvta_generic_to_shared(p); }

__device__ __forceinline__ void mbar_init(uint32_t bar, uint32_t count) {
    asm volatile("mbarrier.init.shared::cta.b64 [%0], %1;" ::"r"(bar), "r"(count) : "memory");
}
#define MBAR_WAIT_ASM(HINT, LIMIT)                                                                  \
    asm volatile("{\n.reg .pred p;\n.reg .u32 n;\nmov.u32 n, 0;\n"                                  \
                 "WAIT_LOOP:\n"                                                                     \
                 "mbarrier.try_wait.parity.shared::cta.b64 p, [%0], %1" HINT ";\n"                  \
                 "@p bra WAIT_DONE;\n"                                                              \
                 "add.u32 n, n, 1;\n"                                                               \
                 "setp.lt.u32 p, n, " LIMIT ";\n"                                                   \
                 "@p bra WAIT_LOOP;\n"                                                              \
                 "WAIT_DONE:\n}\n" ::"r"(bar), "r"(parity) : "memory")
__device__ __forceinline__ void mbar_wait(uint32_t bar, uint32_t parity) { MBAR_WAIT_ASM("", "131072"); }
__device__ __forceinline__ void mbar_sleep(uint32_t bar, uint32_t parity) { MBAR_WAIT_ASM(", 2000", "8192"); }
__device__ __forceinline__ bool mbar_try(uint32_t bar, uint32_t parity) {
    uint32_t ok;
    asm volatile("{\n.reg .pred p;\nmbarrier.try_wait.parity.shared::cta.b64 p, [%1], %2;\nselp.u32 %0, 1, 0, p;\n}\n"
                 : "=r"(ok) : "r"(bar), "r"(parity) : "memory");
    return ok;
}
__device__ __forceinline__ bool mbar_test(uint32_t bar, uint32_t parity) {
    uint32_t ok;
    asm volatile("{\n.reg .pred p;\nmbarrier.test_wait.parity.shared::cta.b64 p, [%1], %2;\nselp.u32 %0, 1, 0, p;\n}\n"
                 : "=r"(ok) : "r"(bar), "r"(parity) : "memory");
    return ok;
}
__device__ __forceinline__ bool elect_one() {
    uint32_t ok;
    asm volatile("{\n.reg .pred p;\nelect.sync _|p, 0xffffffff;\nselp.u32 %0, 1, 0, p;\n}\n" : "=r"(ok));
    return ok;
}
__device__ __forceinline__ void mbar_arrive(uint32_t bar) {
    asm volatile("mbarrier.arrive.shared::cta.b64 _, [%0];" ::"r"(bar) : "memory");
}
__device__ __forceinline__ void mbar_expect_tx(uint32_t bar, uint32_t bytes) {
    asm volatile("mbarrier.arrive.expect_tx.shared::cta.b64 _, [%0], %1;" ::"r"(bar), "r"(bytes) : "memory");
}
__device__ __forceinline__ void mbar_arrive_cluster(uint32_t cluster_addr) {
    asm volatile("mbarrier.arrive.shared::cluster.b64 _, [%0];" ::"r"(cluster_addr) : "memory");
}
__device__ __forceinline__ uint32_t mapa(uint32_t addr, uint32_t rank) {
    uint32_t r;
    asm("mapa.shared::cluster.u32 %0, %1, %2;" : "=r"(r) : "r"(addr), "r"(rank));
    return r;
}
__device__ __forceinline__ void tma_3d(uint32_t dst, const CUtensorMap* m, int c0, int c1, int c2, uint32_t bar) {
    asm volatile("cp.async.bulk.tensor.3d.shared::cluster.global.mbarrier::complete_tx::bytes [%0], [%1, {%3, %4, %5}], [%2];"
                 ::"r"(dst), "l"(m), "r"(bar), "r"(c0), "r"(c1), "r"(c2) : "memory");
}
__device__ __forceinline__ void tma_3d_hint(uint32_t dst, const CUtensorMap* m, int c0, int c1, int c2, uint32_t bar, uint64_t pol) {
    asm volatile("cp.async.bulk.tensor.3d.shared::cluster.global.mbarrier::complete_tx::bytes.L2::cache_hint [%0], [%1, {%3, %4, %5}], [%2], %6;"
                 ::"r"(dst), "l"(m), "r"(bar), "r"(c0), "r"(c1), "r"(c2), "l"(pol) : "memory");
}
__device__ __forceinline__ void tma_3d_mc(uint32_t dst, const CUtensorMap* m, int c0, int c1, int c2, uint32_t bar) {
    asm volatile("cp.async.bulk.tensor.3d.shared::cluster.global.mbarrier::complete_tx::bytes.multicast::cluster [%0], [%1, {%3, %4, %5}], [%2], %6;"
                 ::"r"(dst), "l"(m), "r"(bar), "r"(c0), "r"(c1), "r"(c2), "h"((uint16_t)3) : "memory");
}
__device__ __forceinline__ void bulk_load(uint32_t dst, const void* src, uint32_t bytes, uint32_t bar) {
    asm volatile("cp.async.bulk.shared::cluster.global.mbarrier::complete_tx::bytes [%0], [%1], %2, [%3];"
                 ::"r"(dst), "l"(src), "r"(bytes), "r"(bar) : "memory");
}
__device__ __forceinline__ void cp_async16(uint32_t dst, const void* src) {
    asm volatile("cp.async.cg.shared.global [%0], [%1], 16;" ::"r"(dst), "l"(src) : "memory");
}
__device__ __forceinline__ void bulk_load_mc(uint32_t dst, const void* src, uint32_t bytes, uint32_t bar) {
    asm volatile("cp.async.bulk.shared::cluster.global.mbarrier::complete_tx::bytes.multicast::cluster [%0], [%1], %2, [%3], %4;"
                 ::"r"(dst), "l"(src), "r"(bytes), "r"(bar), "h"((uint16_t)3) : "memory");
}
__device__ __forceinline__ void tma_store_2d(const CUtensorMap* m, int c0, int c1, uint32_t src) {
    asm volatile("cp.async.bulk.tensor.2d.global.shared::cta.bulk_group [%0, {%2, %3}], [%1];"
                 ::"l"(m), "r"(src), "r"(c0), "r"(c1) : "memory");
}
__device__ __forceinline__ void bulk_commit() { asm volatile("cp.async.bulk.commit_group;" ::: "memory"); }
__device__ __forceinline__ void bulk_wait_read() { asm volatile("cp.async.bulk.wait_group.read 0;" ::: "memory"); }
__device__ __forceinline__ void fence_async_smem() { asm volatile("fence.proxy.async.shared::cta;" ::: "memory"); }
__device__ __forceinline__ void prefetch_map(const CUtensorMap* m) {
    asm volatile("prefetch.tensormap [%0];" ::"l"(m) : "memory");
}
__device__ __forceinline__ void red_release(unsigned* p) {
    asm volatile("red.release.gpu.global.add.u32 [%0], 1;" ::"l"(p) : "memory");
}
__device__ __forceinline__ unsigned ld_relaxed(const unsigned* p) {
    unsigned v;
    asm volatile("ld.relaxed.gpu.global.u32 %0, [%1];" : "=r"(v) : "l"(p) : "memory");
    return v;
}
__device__ __forceinline__ void wait_counter(const unsigned* p, unsigned target) {
    for (uint32_t n = 0; (int)(ld_relaxed(p) - target) < 0 && n < SPIN_LIMIT; n++) __nanosleep(100);
    asm volatile("fence.acquire.gpu;" ::: "memory");
    asm volatile("fence.proxy.async.global;" ::: "memory");
}
__device__ __forceinline__ void bar_sync(int id, int n) { asm volatile("bar.sync %0, %1;" ::"r"(id), "r"(n) : "memory"); }
__device__ __forceinline__ void bar_arrive(int id, int n) { asm volatile("bar.arrive %0, %1;" ::"r"(id), "r"(n) : "memory"); }
__device__ __forceinline__ void cluster_sync() {
    asm volatile("barrier.cluster.arrive.relaxed.aligned;\nbarrier.cluster.wait.aligned;" ::: "memory");
}
__device__ __forceinline__ void wg_fence() { asm volatile("wgmma.fence.sync.aligned;" ::: "memory"); }
__device__ __forceinline__ void wg_commit() { asm volatile("wgmma.commit_group.sync.aligned;" ::: "memory"); }
template <int N> __device__ __forceinline__ void wg_wait() { asm volatile("wgmma.wait_group.sync.aligned %0;" ::"n"(N) : "memory"); }
template <int N> __device__ __forceinline__ void reg_fence(float (&a)[N]) {
#pragma unroll
    for (int i = 0; i < N; i++) asm volatile("" : "+f"(a[i])::"memory");
}
template <int N> __device__ __forceinline__ void reg_fence(uint32_t (&a)[N]) {
#pragma unroll
    for (int i = 0; i < N; i++) asm volatile("" : "+r"(a[i])::"memory");
}
__device__ __forceinline__ uint32_t pack_bf16(float lo, float hi) {
    uint32_t r;
    asm("cvt.rn.bf16x2.f32 %0, %1, %2;" : "=r"(r) : "f"(hi), "f"(lo));
    return r;
}
__device__ __forceinline__ float bf_lo(uint32_t v) { return __uint_as_float(v << 16); }
__device__ __forceinline__ float bf_hi(uint32_t v) { return __uint_as_float(v & 0xffff0000u); }
__device__ __forceinline__ float bf_round(float v) { return __bfloat162float(__float2bfloat16_rn(v)); }
__device__ __forceinline__ float ex2(float v) {
    float r;
    asm("ex2.approx.ftz.f32 %0, %1;" : "=f"(r) : "f"(v));
    return r;
}
__device__ __forceinline__ float sqrt_approx(float v) {
    float r;
    asm("sqrt.approx.ftz.f32 %0, %1;" : "=f"(r) : "f"(v));
    return r;
}
__device__ __forceinline__ float rcp_approx(float v) {
    float r;
    asm("rcp.approx.ftz.f32 %0, %1;" : "=f"(r) : "f"(v));
    return r;
}
__device__ __forceinline__ float silu_f(float v) { return v * rcp_approx(1.0f + ex2(v * -1.4426950408889634f)); }
__device__ __forceinline__ void stmatrix_x4(uint32_t addr, uint32_t r0, uint32_t r1, uint32_t r2, uint32_t r3) {
    asm volatile("stmatrix.sync.aligned.m8n8.x4.shared.b16 [%0], {%1, %2, %3, %4};"
                 ::"r"(addr), "r"(r0), "r"(r1), "r"(r2), "r"(r3) : "memory");
}
__device__ __forceinline__ void sts128(uint32_t addr, uint32_t r0, uint32_t r1, uint32_t r2, uint32_t r3) {
    asm volatile("st.shared.v4.b32 [%0], {%1, %2, %3, %4};" ::"r"(addr), "r"(r0), "r"(r1), "r"(r2), "r"(r3) : "memory");
}
__device__ __forceinline__ void lds128(uint32_t addr, uint32_t& r0, uint32_t& r1, uint32_t& r2, uint32_t& r3) {
    asm volatile("ld.shared.v4.b32 {%0, %1, %2, %3}, [%4];" : "=r"(r0), "=r"(r1), "=r"(r2), "=r"(r3) : "r"(addr) : "memory");
}
__device__ __forceinline__ void ldmatrix_x4(uint32_t addr, uint32_t& r0, uint32_t& r1, uint32_t& r2, uint32_t& r3) {
    asm volatile("ldmatrix.sync.aligned.m8n8.x4.shared.b16 {%0, %1, %2, %3}, [%4];"
                 : "=r"(r0), "=r"(r1), "=r"(r2), "=r"(r3) : "r"(addr) : "memory");
}
__device__ __forceinline__ uint32_t bf2_mul(uint32_t a, uint32_t b) {
    uint32_t r;
    asm("mul.rn.bf16x2 %0, %1, %2;" : "=r"(r) : "r"(a), "r"(b));
    return r;
}
__device__ __forceinline__ uint32_t bf2_add(uint32_t a, uint32_t b) {
    uint32_t r;
    asm("add.rn.bf16x2 %0, %1, %2;" : "=r"(r) : "r"(a), "r"(b));
    return r;
}
__device__ __forceinline__ uint64_t policy_evict_first() {
    uint64_t p;
    asm("createpolicy.fractional.L2::evict_first.b64 %0, 1.0;" : "=l"(p));
    return p;
}

__device__ __forceinline__ uint64_t make_desc(uint32_t addr, uint32_t lbo_bytes) {
    return (uint64_t)((addr & 0x3FFFF) >> 4) | ((uint64_t)(lbo_bytes >> 4) << 16) | ((uint64_t)(1024 >> 4) << 32) | (1ull << 62);
}

__device__ __forceinline__ void wgmma_n256_ss(float (&d)[128], uint64_t da, uint64_t db, int acc) {
    asm volatile(
        "{\n.reg .pred p;\nsetp.ne.b32 p, %130, 0;\n"
        "wgmma.mma_async.sync.aligned.m64n256k16.f32.bf16.bf16 {"
        "%0, %1, %2, %3, %4, %5, %6, %7, %8, %9, %10, %11, %12, %13, %14, %15, "
        "%16, %17, %18, %19, %20, %21, %22, %23, %24, %25, %26, %27, %28, %29, %30, %31, "
        "%32, %33, %34, %35, %36, %37, %38, %39, %40, %41, %42, %43, %44, %45, %46, %47, "
        "%48, %49, %50, %51, %52, %53, %54, %55, %56, %57, %58, %59, %60, %61, %62, %63, "
        "%64, %65, %66, %67, %68, %69, %70, %71, %72, %73, %74, %75, %76, %77, %78, %79, "
        "%80, %81, %82, %83, %84, %85, %86, %87, %88, %89, %90, %91, %92, %93, %94, %95, "
        "%96, %97, %98, %99, %100, %101, %102, %103, %104, %105, %106, %107, %108, %109, %110, %111, "
        "%112, %113, %114, %115, %116, %117, %118, %119, %120, %121, %122, %123, %124, %125, %126, %127"
        "}, %128, %129, p, 1, 1, 1, 0;\n}\n"
        :
        "+f"(d[0]), "+f"(d[1]), "+f"(d[2]), "+f"(d[3]), "+f"(d[4]), "+f"(d[5]), "+f"(d[6]), "+f"(d[7]),
        "+f"(d[8]), "+f"(d[9]), "+f"(d[10]), "+f"(d[11]), "+f"(d[12]), "+f"(d[13]), "+f"(d[14]), "+f"(d[15]),
        "+f"(d[16]), "+f"(d[17]), "+f"(d[18]), "+f"(d[19]), "+f"(d[20]), "+f"(d[21]), "+f"(d[22]), "+f"(d[23]),
        "+f"(d[24]), "+f"(d[25]), "+f"(d[26]), "+f"(d[27]), "+f"(d[28]), "+f"(d[29]), "+f"(d[30]), "+f"(d[31]),
        "+f"(d[32]), "+f"(d[33]), "+f"(d[34]), "+f"(d[35]), "+f"(d[36]), "+f"(d[37]), "+f"(d[38]), "+f"(d[39]),
        "+f"(d[40]), "+f"(d[41]), "+f"(d[42]), "+f"(d[43]), "+f"(d[44]), "+f"(d[45]), "+f"(d[46]), "+f"(d[47]),
        "+f"(d[48]), "+f"(d[49]), "+f"(d[50]), "+f"(d[51]), "+f"(d[52]), "+f"(d[53]), "+f"(d[54]), "+f"(d[55]),
        "+f"(d[56]), "+f"(d[57]), "+f"(d[58]), "+f"(d[59]), "+f"(d[60]), "+f"(d[61]), "+f"(d[62]), "+f"(d[63]),
        "+f"(d[64]), "+f"(d[65]), "+f"(d[66]), "+f"(d[67]), "+f"(d[68]), "+f"(d[69]), "+f"(d[70]), "+f"(d[71]),
        "+f"(d[72]), "+f"(d[73]), "+f"(d[74]), "+f"(d[75]), "+f"(d[76]), "+f"(d[77]), "+f"(d[78]), "+f"(d[79]),
        "+f"(d[80]), "+f"(d[81]), "+f"(d[82]), "+f"(d[83]), "+f"(d[84]), "+f"(d[85]), "+f"(d[86]), "+f"(d[87]),
        "+f"(d[88]), "+f"(d[89]), "+f"(d[90]), "+f"(d[91]), "+f"(d[92]), "+f"(d[93]), "+f"(d[94]), "+f"(d[95]),
        "+f"(d[96]), "+f"(d[97]), "+f"(d[98]), "+f"(d[99]), "+f"(d[100]), "+f"(d[101]), "+f"(d[102]), "+f"(d[103]),
        "+f"(d[104]), "+f"(d[105]), "+f"(d[106]), "+f"(d[107]), "+f"(d[108]), "+f"(d[109]), "+f"(d[110]), "+f"(d[111]),
        "+f"(d[112]), "+f"(d[113]), "+f"(d[114]), "+f"(d[115]), "+f"(d[116]), "+f"(d[117]), "+f"(d[118]), "+f"(d[119]),
        "+f"(d[120]), "+f"(d[121]), "+f"(d[122]), "+f"(d[123]), "+f"(d[124]), "+f"(d[125]), "+f"(d[126]), "+f"(d[127])
        : "l"(da), "l"(db), "r"(acc));
}

template <int TB>
__device__ __forceinline__ void wgmma_n128_rs(float (&d)[64], uint32_t a0, uint32_t a1, uint32_t a2, uint32_t a3, uint32_t db, int acc) {
    asm volatile(
        "{\n.reg .pred p;\n.reg .b64 db;\nsetp.ne.b32 p, %69, 0;\nmov.b64 db, {%68, 0x40000040};\n"
        "wgmma.mma_async.sync.aligned.m64n128k16.f32.bf16.bf16 {"
        "%0, %1, %2, %3, %4, %5, %6, %7, %8, %9, %10, %11, %12, %13, %14, %15, "
        "%16, %17, %18, %19, %20, %21, %22, %23, %24, %25, %26, %27, %28, %29, %30, %31, "
        "%32, %33, %34, %35, %36, %37, %38, %39, %40, %41, %42, %43, %44, %45, %46, %47, "
        "%48, %49, %50, %51, %52, %53, %54, %55, %56, %57, %58, %59, %60, %61, %62, %63"
        "}, {%64, %65, %66, %67}, db, p, 1, 1, %70;\n}\n"
        :
        "+f"(d[0]), "+f"(d[1]), "+f"(d[2]), "+f"(d[3]), "+f"(d[4]), "+f"(d[5]), "+f"(d[6]), "+f"(d[7]),
        "+f"(d[8]), "+f"(d[9]), "+f"(d[10]), "+f"(d[11]), "+f"(d[12]), "+f"(d[13]), "+f"(d[14]), "+f"(d[15]),
        "+f"(d[16]), "+f"(d[17]), "+f"(d[18]), "+f"(d[19]), "+f"(d[20]), "+f"(d[21]), "+f"(d[22]), "+f"(d[23]),
        "+f"(d[24]), "+f"(d[25]), "+f"(d[26]), "+f"(d[27]), "+f"(d[28]), "+f"(d[29]), "+f"(d[30]), "+f"(d[31]),
        "+f"(d[32]), "+f"(d[33]), "+f"(d[34]), "+f"(d[35]), "+f"(d[36]), "+f"(d[37]), "+f"(d[38]), "+f"(d[39]),
        "+f"(d[40]), "+f"(d[41]), "+f"(d[42]), "+f"(d[43]), "+f"(d[44]), "+f"(d[45]), "+f"(d[46]), "+f"(d[47]),
        "+f"(d[48]), "+f"(d[49]), "+f"(d[50]), "+f"(d[51]), "+f"(d[52]), "+f"(d[53]), "+f"(d[54]), "+f"(d[55]),
        "+f"(d[56]), "+f"(d[57]), "+f"(d[58]), "+f"(d[59]), "+f"(d[60]), "+f"(d[61]), "+f"(d[62]), "+f"(d[63])
        : "r"(a0), "r"(a1), "r"(a2), "r"(a3), "r"(db), "r"(acc), "n"(TB));
}

__device__ __forceinline__ void wgmma_n128_ss(float* d, uint64_t da, uint64_t db, int acc) {
    asm volatile(
        "{\n.reg .pred p;\nsetp.ne.b32 p, %66, 0;\n"
        "wgmma.mma_async.sync.aligned.m64n128k16.f32.bf16.bf16 {"
        "%0, %1, %2, %3, %4, %5, %6, %7, %8, %9, %10, %11, %12, %13, %14, %15, "
        "%16, %17, %18, %19, %20, %21, %22, %23, %24, %25, %26, %27, %28, %29, %30, %31, "
        "%32, %33, %34, %35, %36, %37, %38, %39, %40, %41, %42, %43, %44, %45, %46, %47, "
        "%48, %49, %50, %51, %52, %53, %54, %55, %56, %57, %58, %59, %60, %61, %62, %63"
        "}, %64, %65, p, 1, 1, 0, 1;\n}\n"
        :
        "+f"(d[0]), "+f"(d[1]), "+f"(d[2]), "+f"(d[3]), "+f"(d[4]), "+f"(d[5]), "+f"(d[6]), "+f"(d[7]),
        "+f"(d[8]), "+f"(d[9]), "+f"(d[10]), "+f"(d[11]), "+f"(d[12]), "+f"(d[13]), "+f"(d[14]), "+f"(d[15]),
        "+f"(d[16]), "+f"(d[17]), "+f"(d[18]), "+f"(d[19]), "+f"(d[20]), "+f"(d[21]), "+f"(d[22]), "+f"(d[23]),
        "+f"(d[24]), "+f"(d[25]), "+f"(d[26]), "+f"(d[27]), "+f"(d[28]), "+f"(d[29]), "+f"(d[30]), "+f"(d[31]),
        "+f"(d[32]), "+f"(d[33]), "+f"(d[34]), "+f"(d[35]), "+f"(d[36]), "+f"(d[37]), "+f"(d[38]), "+f"(d[39]),
        "+f"(d[40]), "+f"(d[41]), "+f"(d[42]), "+f"(d[43]), "+f"(d[44]), "+f"(d[45]), "+f"(d[46]), "+f"(d[47]),
        "+f"(d[48]), "+f"(d[49]), "+f"(d[50]), "+f"(d[51]), "+f"(d[52]), "+f"(d[53]), "+f"(d[54]), "+f"(d[55]),
        "+f"(d[56]), "+f"(d[57]), "+f"(d[58]), "+f"(d[59]), "+f"(d[60]), "+f"(d[61]), "+f"(d[62]), "+f"(d[63])
        : "l"(da), "l"(db), "r"(acc));
}

__device__ __forceinline__ void wgmma_n8_ta(float* d, uint64_t da, uint64_t db) {
    asm volatile("wgmma.mma_async.sync.aligned.m64n8k16.f32.bf16.bf16 {%0, %1, %2, %3}, %4, %5, 1, 1, 1, 1, 0;\n"
                 : "+f"(d[0]), "+f"(d[1]), "+f"(d[2]), "+f"(d[3]) : "l"(da), "l"(db));
}

#define PROF(slot, role)
#undef PROF_GT
#define PROF_GT(slot)

struct Params {
    const __nv_bfloat16* x;
    const __nv_bfloat16* w_r;
    const uint8_t *c_kv, *w_uk, *w_uv;
};
__device__ __forceinline__ void lsu_prefetch(const void* p) { asm volatile("prefetch.global.L2 [%0];" ::"l"(p) : "memory"); }

template <typename T>
__device__ __forceinline__ T* ptr_off(T* base, uint32_t off) {
    uint32_t lo, hi;
    asm("mov.b64 {%0, %1}, %2;" : "=r"(lo), "=r"(hi) : "l"(base));
    asm("add.cc.u32 %0, %0, %2;\naddc.u32 %1, %1, 0;" : "+r"(lo), "+r"(hi) : "r"(off));
    T* r;
    asm("mov.b64 %0, {%1, %2};" : "=l"(r) : "r"(lo), "r"(hi));
    return r;
}
__device__ __forceinline__ int kv_head(int pair) { return AMAP ? (pair & 15) >> 1 : pair >> 3; }
__device__ __forceinline__ int kv_tokens(int pair) { return AMAP ? (pair & 1) * 4 + (pair >> 4) : pair & 7; }
__device__ __forceinline__ int attn_rowblock(int pair, int seg) {
    int j = pair & 3, hl = pair >> 2;
    return ((hl & 1) ^ seg) ? j : 7 - j;
}
__device__ __forceinline__ int outproj_head(int i, int ib) {
    if (i < 16) return i;
    return 16 + 2 * (i & 7) + ((ib < 4) ^ ((i >> 3) & 1));
}

__device__ __forceinline__ void pin_value(uint32_t& v) { asm volatile("" : "+r"(v)); }
__device__ __forceinline__ void pin_value(int& v) { asm volatile("" : "+r"(v)); }
__device__ __forceinline__ void pin_value(const uint8_t*& v) { asm volatile("" : "+l"(v)); }

__device__ __forceinline__ void producer(const Params& P, uint32_t sb, int pair, int c,
                                         const CUtensorMap* m_ckv, const CUtensorMap* m_wu,
                                         const CUtensorMap* m_wq, const CUtensorMap* m_wo, const CUtensorMap* m_x,
                                         const CUtensorMap* m_out) {
    const int hl = pair >> 2;
    const int ibA = attn_rowblock(pair, 0), nA = 2 * ibA + 2;
    const int ib = (pair >> 1) & 7, mi = 2 * ib + c, nb = (pair >> 4) * 4 + (pair & 1) * 2;
    const bool leader = elect_one();
    uint32_t g = 4, tail = 0;
    if (leader) prefetch_map(m_wq);
    auto wait_released = [&](uint32_t need) {
#pragma unroll 1
        for (; tail <= need; tail++) mbar_wait(sb + BAR_EMPTY + (tail & 7) * 8, (tail >> 3) & 1);
    };
    auto wait_released_here = [&](uint32_t need) {
#pragma unroll 1
        for (; tail < need; tail++) mbar_wait(sb + BAR_EMPTY + (tail & 7) * 8, (tail >> 3) & 1);
        if (tail == need) mbar_wait(sb + BAR_EMPTYL + (need & 7) * 8, (need >> 3) & 1);
    };
    auto wait_released_peer = [&](uint32_t need) {
        if (tail == need) {
            uint32_t eb = sb + BAR_EMPTY + (need & 7) * 8, ep = (need >> 3) & 1;
            tail++;
            mbar_wait(eb, ep);
        }
    };
    auto full_bar = [&]() { return sb + BAR_FULL + (g & 7) * 8; };
    auto pin = [](auto&... v) { (pin_value(v), ...); };
#pragma unroll 1
    for (int rnd = 0; rnd < 2; rnd++) {
#pragma unroll 1
        for (int i = rnd ? 0 : 4; i < 16; i++) {
            int kb = i & 7, h2 = (kv_head(pair) + (i & 8) + rnd * 16) * 2, krow = kb * 64;
            uint32_t pg = sb + (i & 3) * (3 * PAGE), pb = pg + (1 + c) * PAGE, bar = full_bar();
            pin(kb, h2, krow, pg, pb, bar);
            const uint32_t need = g - 4 - (i < 2);
            wait_released_here(need);
            if (leader) {
                mbar_expect_tx(bar, 3 * PAGE);
                tma_3d(pg, m_wu, 0, krow, h2, bar);
            }
            wait_released_peer(need);
            if (leader) {
                tma_3d_mc(pb, m_ckv, 0, kv_tokens(pair) * 256 + c * 128, kb, bar);
                if (rnd == 1 && i == 3) asm volatile("red.relaxed.gpu.global.add.u32 [%0], 1;" ::"l"(ptr_off(g_sync.kvfree, hl * 32)) : "memory");
            }
            g++;
        }
        mbar_sleep(sb + BAR_DEP, 0);
        const uint8_t* xa = ptr_off(g_xn, ibA * (16 * 32768) + c * PAGE);
        const uint8_t* xb = ptr_off(g_xn, (7 - ibA) * (16 * 32768) + (1 - c) * PAGE);
#pragma unroll 1
        for (int kb = 0; kb < DM / 64; kb++) {
            uint32_t pg = sb + (kb & 3) * (3 * PAGE), pw = pg + 2 * PAGE + c * 8192, bar = full_bar(), p2 = pg + PAGE;
            int krow = kb * 64;
            pin(pg, pw, p2, bar, krow);
            wait_released_here(g - 4);
            if (leader) {
                mbar_expect_tx(bar, 3 * PAGE);
                bulk_load(pg, xa, PAGE, bar);
            }
            wait_released_peer(g - 4);
            if (leader) {
                tma_3d_mc(pw, m_wq, 0, krow, (rnd * 16 + hl) * 2 + c, bar);
                bulk_load(p2, xb, PAGE, bar);
            }
            g++;
            xa += 32768;
            xb += 32768;
        }
        mbar_sleep(sb + BAR_DEP + 8 + rnd * 16, 0);
        if (rnd == 1 && leader) prefetch_map(m_wo);
        uint32_t pg = sb + c * PAGE;
#pragma unroll 1
        for (int j = 0; j < 36; j++) {
            const bool isk = j == 0 || ((j & 1) && j != 35);
            const int t = isk ? (j + 1) >> 1 : (j - 1) >> 1;
            const uint8_t* src = ptr_off(g_kv, (hl * 16 + (t >= nA ? t - nA : t)) * 65536 + (isk ? 0 : 32768) + c * PAGE);
            uint32_t bar = full_bar(), need = g - 6 + (j < 2) + (j < 5);
            pin(src, bar, need);
            wait_released(need);
            if (leader) {
                mbar_expect_tx(bar, 2 * PAGE);
                bulk_load_mc(pg, src, PAGE, bar);
            }
            g++;
            if (rnd == 0 && j >= 22 && j < 34) {
                const int cta = pair * 2 + c, i = j - 22;
                const uint32_t l = (threadIdx.x & 31) * 128;
                if (i < 8) lsu_prefetch(ptr_off(i & 1 ? P.w_uv : P.w_uk, cta * 32768 + (i >> 1) * 8192 + 4096 + l));
                else lsu_prefetch(ptr_off(P.c_kv, cta * 16384 + (i - 8) * 4096 + l));
            }
            pg = pg >= sb + SM_REGION - 2 * PAGE ? pg - (SM_REGION - 2 * PAGE) : pg + 2 * PAGE;
        }
    }
    uint32_t pg = sb;
#pragma unroll 1
    for (int i = 0; i < 64; i++) {
        if (i == 32 && leader) { prefetch_map(m_x); prefetch_map(m_out); }
        if ((i & 15) == 0 && i != 16) mbar_sleep(sb + BAR_DEP + 32 + (i >> 1) - (i ? 8 : 0), 0);
        const int kb = outproj_head(i >> 1, ib) * 2 + (i & 1);
        const uint8_t* src = ptr_off(g_ctx, (mi * 64 + kb) * PAGE);
        uint32_t bar = full_bar(), pw = pg + PAGE + c * 8192;
        int krow = kb * 64;
        pin(src, bar, pw, krow);
        wait_released_here(g - 6);
        if (leader) {
            mbar_expect_tx(bar, 2 * PAGE);
            bulk_load(pg, src, PAGE, bar);
        }
        wait_released_peer(g - 6);
        if (leader) tma_3d_mc(pw, m_wo, 0, krow, nb + c, bar);
        g++;
        pg = pg == sb + SM_REGION - 2 * PAGE ? sb : pg + 2 * PAGE;
    }
    const uint32_t bar = full_bar();
    wait_released(g - 6);
    if (leader) {
        mbar_expect_tx(bar, 2 * PAGE);
        tma_3d(pg, m_x, 0, mi * 128, nb, bar);
        tma_3d(pg + PAGE, m_x, 0, mi * 128 + 64, nb, bar);
    }
}

__device__ __forceinline__ uint32_t xn_block(int row64, int kb) {
    return (((row64 >> 2) * 16 + kb) * 4 + ((row64 & 1) * 2 + (((row64 >> 1) & 1) ^ 1))) * 8192;
}
__device__ __forceinline__ uint32_t image_offset(int row, int ch) {
    return xn_block(row >> 6, ch >> 3) + (row & 63) * 128 + (((ch & 7) ^ (row & 7)) << 4);
}
__device__ __forceinline__ uint32_t bf2_sub(uint32_t a, uint32_t b) {
    uint32_t r;
    asm("sub.rn.bf16x2 %0, %1, %2;" : "=r"(r) : "r"(a), "r"(b));
    return r;
}
__device__ __forceinline__ uint32_t bf2_fma(uint32_t a, uint32_t b, uint32_t c) {
    uint32_t r;
    asm("fma.rn.bf16x2 %0, %1, %2, %3;" : "=r"(r) : "r"(a), "r"(b), "r"(c));
    return r;
}
template <int N0, int N>
__device__ __forceinline__ void ln_sums(const uint32_t (&u)[N], float& sum, float& sq) {
    float s0 = 0.f, s1 = 0.f, q0 = 0.f, q1 = 0.f;
#pragma unroll
    for (int k = N0; k < N0 + 16; k++) {
        const float a = bf_lo(u[k]), b = bf_hi(u[k]);
        s0 += a; s1 += b;
        q0 = fmaf(a, a, q0); q1 = fmaf(b, b, q1);
    }
    sum = s0 + s1;
    sq = q0 + q1;
}
__device__ __forceinline__ void ln_finish(float sum, float sq, uint32_t& mean2, uint32_t& rhi2, uint32_t& rlo2) {
    const float ms = sum * (1.0f / DM);
    const float var = fmaxf(fmaf(-ms, ms, sq * (1.0f / DM)), 0.f);
    const float rden = rcp_approx(bf_round(sqrt_approx(bf_round(bf_round(var) + 1e-5f))));
    const float rhi = bf_round(rden);
    mean2 = pack_bf16(ms, ms);
    rhi2 = pack_bf16(rhi, rhi);
    rlo2 = pack_bf16(rden - rhi, rden - rhi);
}
template <int N0, int N>
__device__ __forceinline__ void ln_apply(uint32_t (&u)[N], uint32_t mean2, uint32_t rhi2, uint32_t rlo2, uint8_t* dst) {
#pragma unroll
    for (int i = 0; i < 4; i++) {
        uint32_t o[4];
#pragma unroll
        for (int k = 0; k < 4; k++) {
            const uint32_t d = bf2_sub(u[N0 + 4 * i + k], mean2);
            o[k] = bf2_fma(d, rhi2, bf2_mul(d, rlo2));
        }
#pragma unroll
        for (int k = 0; k < 4; k++) u[N0 + 4 * i + k] = o[k];
        __stcg(reinterpret_cast<uint4*>(dst + i * 131072), make_uint4(o[0], o[1], o[2], o[3]));
    }
}
__device__ __forceinline__ int query_rowblock(int pair, int c, int w, int seg) {
    const int qA = (w ? 0 : 2) + c;
    return 4 * attn_rowblock(pair, seg) + (seg ? 3 - qA : qA);
}

__device__ __forceinline__ void fetch_helper(const Params& P, uint32_t sb, int w, int lane, int pair, int c) {
    const uint32_t page = sb + SM_REGION + w * PAGE + lane * 16;
    mbar_sleep(sb + BAR_FULL + 5 * 8, 0);
#pragma unroll 1
    for (int i = 0; i < 2; i++) {
        lsu_prefetch(ptr_off(w ? P.w_uv : P.w_uk, ((pair * 2 + c) * 4 + i * 2 + (lane >> 4)) * 8192 + 2048 + (lane & 15) * 128));
        __nanosleep(300);
    }
    const unsigned e1 = __ldcg(&g_sync.done) / NCTA + 1;
#pragma unroll 1
    for (int e = 1; e <= 7; e += 2) mbar_sleep(sb + BAR_DONE + 8, (e >> 1) & 1);
    const int rb = ((pair >> 1) & 7) * 4 + c * 2 + w, kb0 = (pair >> 4) * 4 + (pair & 1) * 2;
    const uint8_t* src = ptr_off(g_xn, xn_block(rb, kb0) + lane * 16);
#pragma unroll 1
    for (int i = 0; i < 32; i += 4) {
#pragma unroll
        for (int k = 0; k < 4; k++) cp_async16(page + (i + k) * 512, src + (i + k) * 512 + (i >> 4) * (32768 - 8192));
        __nanosleep(200);
    }
    wait_counter(&g_sync.ffn_done, e1);
    const int r = __ldcg(ptr_off(g_sel, (lane >> 4) * 4)) - rb * 64, ch = lane & 15;
    const uint4 t = __ldcg(ptr_off(g_routed, ((lane >> 4) * 128 + kb0 * 8 + ch) * 16));
    asm volatile("cp.async.wait_all;" ::: "memory");
    __syncwarp();
    if (r >= 0 && r < 64)
        sts128(sb + SM_REGION + w * PAGE + (ch >> 3) * 8192 + r * 128 + (((ch & 7) ^ (r & 7)) << 4), t.x, t.y, t.z, t.w);
    __syncwarp();
    if (lane == 0) mbar_arrive(sb + BAR_G + w * 8);
    PROF(20, 2);
}

__device__ __noinline__ void sync_helper(uint32_t sb, int lane, int pair, int c) {
    const unsigned e1 = __ldcg(&g_sync.done) / NCTA + 1;
    const int ib = (pair >> 1) & 7;
    int e = 0, b = 0;
#pragma unroll 1
    for (uint32_t n = 0; (e < 9 || b < 7) && n < SPIN_LIMIT; n++) {
        if (e < 9 && __all_sync(~0u, mbar_test(sb + BAR_DONE + (e & 1) * 8, (e >> 1) & 1))) {
            const int rnd = e > 4, ev = (e - 1) & 3;
            unsigned* flag = e == 0 ? &g_sync.ln
                           : ev < 2 ? ptr_off(g_sync.kv, (rnd * 16 + kv_head(pair) + 8 * ev) * 32)
                                    : ptr_off(g_sync.ctx, (query_rowblock(pair, c, lane & 1, ev & 1) * NH + rnd * 16 + (pair >> 2)) * 4);
            asm volatile("fence.proxy.async.global;\nfence.release.gpu;" ::: "memory");
            if (lane < ((e == 0 || ev < 2) ? 1 : 2)) asm volatile("red.relaxed.gpu.global.add.u32 [%0], 1;" ::"l"(flag) : "memory");
            PROF(10 + e, 2);
            e++;
        }
        if (b < 7 && e > 0 && (b < 4 || (n & POLL_MASK) == 0)) {
            const int i = b == 4 ? lane >> 1 : 8 * b - 24 + ((lane >> 1) & 7);
            const unsigned* cnt = b == 0 ? &g_sync.ln
                                : b == 2 ? ptr_off(g_sync.kvfree, (kv_head(pair) + 8 * (lane & 1)) * 32)
                                : b < 4 ? ptr_off(g_sync.kv, ((b >> 1) * 16 + (pair >> 2)) * 32)
                                        : ptr_off(g_sync.ctx, ((4 * ib + 2 * c + (lane & 1)) * NH + outproj_head(i & 31, ib)) * 4);
            if (__all_sync(~0u, (int)(ld_relaxed(cnt) - e1 * (b == 0 ? NMAIN : b == 2 ? 8 : b < 4 ? 16 : 1)) >= 0)) {
                asm volatile("fence.acquire.gpu;\nfence.proxy.async.global;" ::: "memory");
                __syncwarp();
                if (lane == 0) mbar_arrive(sb + BAR_DEP + b * 8);
                PROF(1 + b, 2);
                b++;
            }
        }
        __nanosleep(150);
    }
}

__device__ __forceinline__ unsigned long long block_max_key(unsigned long long k, unsigned long long* red, int tid) {
#pragma unroll
    for (int o = 16; o; o >>= 1) {
        unsigned long long t = __shfl_xor_sync(~0u, k, o);
        k = t > k ? t : k;
    }
    bar_sync(1, 256);
    if ((tid & 31) == 0) red[tid >> 5] = k;
    bar_sync(1, 256);
    k = red[0];
#pragma unroll
    for (int i = 1; i < 8; i++) k = red[i] > k ? red[i] : k;
    return k;
}

constexpr int FS = FF / 4;
constexpr int FSTAGE = 32768, FNST = 6;
constexpr int FN1 = 2 * (DM / 16), FN2 = FS / 16;

__device__ __forceinline__ void ffn_producer(uint32_t sb, int s, const CUtensorMap* m_gate, const CUtensorMap* m_up,
                                             const CUtensorMap* m_down) {
    const uint64_t pol = policy_evict_first();
    int slot = 0, ph = 1;
#pragma unroll 1
    for (int st = 0; st < FN1 + FN2; st++) {
        mbar_sleep(sb + BAR_EMPTY + slot * 8, ph);
        const uint32_t bar = sb + BAR_FULL + slot * 8;
        const bool up = st < FN1;
        mbar_expect_tx(bar, up ? FS * 32 : DM * 32);
        tma_3d_hint(sb + slot * FSTAGE, up ? ((st & 1) ? m_up : m_gate) : m_down, 0,
                    up ? (st >> 1) * 16 : s * FS + (st - FN1) * 16, up ? s * (FS / 64) : 0, bar, pol);
        if (++slot == FNST) { slot = 0; ph ^= 1; }
    }
}

__device__ __forceinline__ void ffn_cta(uint8_t* smem, uint32_t sb, int s, unsigned epoch, const __nv_bfloat16* w_r) {
    const int tid = threadIdx.x, lane = tid & 31;
    const int warp = __shfl_sync(~0u, tid >> 5, 0), w = warp >> 2;
    constexpr uint32_t XB = FNST * FSTAGE, HB = XB + 16384, AUX = HB + 14336;
    unsigned long long* red = reinterpret_cast<unsigned long long*>(smem + AUX);
    unsigned* flag = reinterpret_cast<unsigned*>(smem + AUX + 128);
    const unsigned e1 = epoch + 1;
    for (int i = tid; i < (16384 + 14336) / 16; i += 256) reinterpret_cast<uint4*>(smem + XB)[i] = make_uint4(0, 0, 0, 0);
    {
        float wf[32];
#pragma unroll
        for (int i = 0; i < 4; i++) {
            const uint4 t = __ldg(reinterpret_cast<const uint4*>(w_r) + lane + 32 * i);
            const uint32_t tu[4] = {t.x, t.y, t.z, t.w};
#pragma unroll
            for (int k = 0; k < 4; k++) { wf[8 * i + 2 * k] = bf_lo(tu[k]); wf[8 * i + 2 * k + 1] = bf_hi(tu[k]); }
        }
        if (tid == 0) wait_counter(&g_sync.ln, e1 * NMAIN);
        bar_sync(1, 256);
#pragma unroll 1
        for (int r0 = s * (SEQ / 4) + warp * (SEQ / 32); r0 < s * (SEQ / 4) + (warp + 1) * (SEQ / 32); r0 += 4) {
            uint4 t[4][4];
#pragma unroll
            for (int r = 0; r < 4; r++)
#pragma unroll
                for (int i = 0; i < 4; i++) t[r][i] = __ldcg(reinterpret_cast<const uint4*>(g_xn + image_offset(r0 + r, lane) + i * 131072));
            float acc[4];
#pragma unroll
            for (int r = 0; r < 4; r++) {
                float a = 0.f, b = 0.f;
#pragma unroll
                for (int i = 0; i < 4; i++) {
                    const uint32_t tu[4] = {t[r][i].x, t[r][i].y, t[r][i].z, t[r][i].w};
#pragma unroll
                    for (int k = 0; k < 4; k++) {
                        a = fmaf(bf_lo(tu[k]), wf[8 * i + 2 * k], a);
                        b = fmaf(bf_hi(tu[k]), wf[8 * i + 2 * k + 1], b);
                    }
                }
                acc[r] = a + b;
            }
#pragma unroll
            for (int o = 16; o; o >>= 1)
#pragma unroll
                for (int r = 0; r < 4; r++) acc[r] += __shfl_xor_sync(~0u, acc[r], o);
            if (lane < 4) __stcg(&g_r[r0 + lane], bf_round(lane == 0 ? acc[0] : lane == 1 ? acc[1] : lane == 2 ? acc[2] : acc[3]));
        }
        __threadfence();
        bar_sync(1, 256);
        if (tid == 0) {
            red_release(&g_sync.router);
            wait_counter(&g_sync.router, e1 * 4);
        }
        bar_sync(1, 256);
    }
    unsigned long long keys[8];
    unsigned long long best = 0;
#pragma unroll
    for (int i = 0; i < 8; i++) {
        int idx = tid + 256 * i;
        uint32_t b = __float_as_uint(__ldcg(&g_r[idx]) + 0.0f);
        b = (b & 0x80000000u) ? ~b : (b | 0x80000000u);
        keys[i] = ((unsigned long long)b << 32) | (unsigned)(SEQ - 1 - idx);
        best = keys[i] > best ? keys[i] : best;
    }
    const unsigned long long k0 = block_max_key(best, red, tid);
    best = 0;
#pragma unroll
    for (int i = 0; i < 8; i++) best = (keys[i] != k0 && keys[i] > best) ? keys[i] : best;
    const unsigned long long k1 = block_max_key(best, red, tid);
    const int row = SEQ - 1 - (int)((w ? k1 : k0) & 0xffffffffu);
    const int ch = tid & 127;
    const uint4 xrow = __ldcg(reinterpret_cast<const uint4*>(g_xn + image_offset(row, ch)));
    *reinterpret_cast<uint4*>(smem + XB + (ch >> 3) * 1024 + w * 128 + (((ch & 7) ^ w) << 4)) = xrow;
    fence_async_smem();
    bar_sync(1, 256);
    PROF(20, tid >> 7);
    int slot = 0, ph = 0, prev = 0;
    auto next_stage = [&](bool has_prev) {
        wg_commit();
        wg_wait<1>();
        if (has_prev && lane < 2) mbar_arrive(sb + BAR_EMPTY + prev * 8);
        prev = slot;
        if (++slot == FNST) { slot = 0; ph ^= 1; }
    };
    {
        float ag[28], au[28];
#pragma unroll
        for (int i = 0; i < 28; i++) ag[i] = au[i] = 0.f;
#pragma unroll 1
        for (int ks = 0; ks < DM / 16; ks++) {
            const uint64_t db = make_desc(sb + XB + (ks >> 2) * 1024 + (ks & 3) * 32, 16);
            mbar_wait(sb + BAR_FULL + slot * 8, ph);
            uint64_t da = make_desc(sb + slot * FSTAGE + w * (7 * 2048), 16);
            wg_fence();
#pragma unroll
            for (int b = 0; b < 7; b++) wgmma_n8_ta(ag + 4 * b, da + b * 128, db);
            next_stage(ks > 0);
            mbar_wait(sb + BAR_FULL + slot * 8, ph);
            da = make_desc(sb + slot * FSTAGE + w * (7 * 2048), 16);
            wg_fence();
#pragma unroll
            for (int b = 0; b < 7; b++) wgmma_n8_ta(au + 4 * b, da + b * 128, db);
            next_stage(true);
        }
        wg_wait<0>();
        reg_fence(ag);
        reg_fence(au);
        if ((lane & 3) == 0) {
#pragma unroll
            for (int i = 0; i < 28; i++) {
                const int f = (warp & 3) * 16 + (lane >> 2) + (i & 2) * 4, tok = i & 1;
                const float h = bf_round(silu_f(bf_round(ag[i]))) * bf_round(au[i]);
                *reinterpret_cast<__nv_bfloat16*>(smem + HB + (w * 7 + (i >> 2)) * 1024 + tok * 128 + (((f >> 3) ^ tok) << 4) + (f & 7) * 2) =
                    __float2bfloat16_rn(h);
            }
        }
    }
    fence_async_smem();
    bar_sync(1, 256);
    PROF(21, tid >> 7);
    {
        float ay[32];
#pragma unroll
        for (int i = 0; i < 32; i++) ay[i] = 0.f;
#pragma unroll 1
        for (int ks = 0; ks < FN2; ks++) {
            const uint64_t db = make_desc(sb + HB + (ks >> 2) * 1024 + (ks & 3) * 32, 16);
            mbar_wait(sb + BAR_FULL + slot * 8, ph);
            const uint64_t da = make_desc(sb + slot * FSTAGE + w * (8 * 2048), 16);
            wg_fence();
#pragma unroll
            for (int b = 0; b < 8; b++) wgmma_n8_ta(ay + 4 * b, da + b * 128, db);
            next_stage(true);
        }
        wg_wait<0>();
        reg_fence(ay);
        if ((lane & 3) == 0) {
#pragma unroll
            for (int i = 0; i < 32; i++)
                g_ypart[(s * 2 + (i & 1)) * DM + (w * 8 + (i >> 2)) * 64 + (warp & 3) * 16 + (lane >> 2) + (i & 2) * 4] = ay[i];
        }
    }
    PROF(23, tid >> 7);
    __threadfence();
    bar_sync(1, 256);
    if (tid == 0) {
        *flag = atomicAdd(&g_sync.ffn_ticket, 1u) == epoch * 4 + 3;
        __threadfence();
    }
    bar_sync(1, 256);
    if (*flag) {
        const float sg = bf_round(__fdividef(1.0f, 1.0f + __expf(-__ldcg(&g_r[row]))));
        const uint32_t xu[4] = {xrow.x, xrow.y, xrow.z, xrow.w};
        uint32_t o[4];
#pragma unroll
        for (int k = 0; k < 4; k++) {
            float y0 = 0.f, y1 = 0.f;
#pragma unroll
            for (int q = 0; q < 4; q++) {
                const float2 y = __ldcg(reinterpret_cast<const float2*>(&g_ypart[(q * 2 + w) * DM + ch * 8 + 2 * k]));
                y0 += y.x; y1 += y.y;
            }
            o[k] = pack_bf16(bf_lo(xu[k]) + bf_round(bf_round(y0) * sg), bf_hi(xu[k]) + bf_round(bf_round(y1) * sg));
        }
        g_routed[w * 128 + ch] = make_uint4(o[0], o[1], o[2], o[3]);
        if (ch == 0) g_sel[w] = row;
        bar_sync(1, 256);
        if (tid == 0) red_release(&g_sync.ffn_done);
    }
}

__device__ __forceinline__ uint32_t slab_addr(uint32_t stg, int lane, int s) {
    const int row = ((lane >> 3) & 1) * 8 + (lane & 7);
    const int chunk = 2 * (s & 3) + (lane >> 4);
    return stg + row * 128 + (s >> 2) * 8192 + ((chunk ^ (lane & 7)) << 4);
}

constexpr float SM_SCALE = 0.08838834764831845f * 1.4426950408889634f;
constexpr float SUM_HI = 1048576.f, SUM_LO = 1.0f / 1048576.f;

template <int I0, int I1, int J0>
__device__ __forceinline__ void mask_range(float (&S)[64], float limf) {
#pragma unroll
    for (int i = I0; i < I1; i++) {
        const int j = i >> 2;
        float t;
        asm("add.sat.f32 %0, %1, %2;" : "=f"(t) : "f"((float)(32 * (j >> 2) + 2 * (j & 3) + (i & 1) - (i & 2) * 4)), "f"(-limf));
        S[4 * J0 + i] = fmaf(t, -1e30f, S[4 * J0 + i]);
    }
}
template <int J0>
__device__ __forceinline__ void mask_half(float (&S)[64], float limf, int v) {
    asm volatile("" : "+f"(limf));
    if (v < 2) {
        mask_range<0, 16, J0>(S, limf);
#pragma unroll
        for (int i = 16; i < 32; i++) S[4 * J0 + i] = -1e30f;
    } else {
        mask_range<16, 32, J0>(S, limf);
    }
}
__device__ __forceinline__ void issue_qk(float (&S)[64], const uint32_t (&Q)[32], uint32_t d0) {
#pragma unroll
    for (int s = 0; s < 8; s++)
        wgmma_n128_rs<1>(S, Q[4 * s], Q[4 * s + 1], Q[4 * s + 2], Q[4 * s + 3], d0 + s * 128, s > 0);
}
template <int H>
__device__ __forceinline__ void issue_pv(float (&O)[64], const uint32_t (&Pm)[32], uint32_t d0, int acc) {
#pragma unroll
    for (int s = 4 * H; s < 4 * H + 4; s++)
        wgmma_n128_rs<0>(O, Pm[4 * s], Pm[4 * s + 1], Pm[4 * s + 2], Pm[4 * s + 3], d0 + H * (PAGE >> 4) + (s & 3) * 2, s > 0 ? 1 : acc);
}
template <int J0, int J1>
__device__ __forceinline__ void exp_groups(const float (&S)[64], uint32_t (&Pm)[32], float (&sum)[NSUM]) {
#pragma unroll
    for (int i = 2 * J0; i < 2 * J1; i++) asm volatile("" : "+r"(Pm[i])::"memory");
#pragma unroll
    for (int j = J0; j < J1; j++) {
        const float e0 = ex2(S[4 * j]), e1 = ex2(S[4 * j + 1]), e2 = ex2(S[4 * j + 2]), e3 = ex2(S[4 * j + 3]);
        if (NSUM == 4) {
            sum[0] = j ? sum[0] + e0 : e0; sum[2] = j ? sum[2] + e1 : e1; sum[1] = j ? sum[1] + e2 : e2; sum[3] = j ? sum[3] + e3 : e3;
        } else {
            sum[0] = (j ? sum[0] + e0 : e0) + e1; sum[1] = (j ? sum[1] + e2 : e2) + e3;
        }
        Pm[2 * j] = pack_bf16(e0, e1);
        Pm[2 * j + 1] = pack_bf16(e2, e3);
    }
}
__device__ __forceinline__ void shift_rows(float (&S)[64], float d0, float d1) {
#pragma unroll
    for (int j = 0; j < 16; j++) {
        S[4 * j] -= d0; S[4 * j + 1] -= d0; S[4 * j + 2] -= d1; S[4 * j + 3] -= d1;
    }
}
__device__ constexpr int chunk_src(int i) { return 4 * (4 * (i >> 3) + (i & 3)) + 2 * ((i >> 2) & 1); }
enum : uint32_t { CTL_FIRST = 1, CTL_SWITCH = 2, CTL_LAST = 4, CTL_HALF = 128, CTL_MASKHI = 256, CTL_LOADQ = 512, CTL_PVHALF = 1024, CTL_PVACC = 16384,
                  CTL_SHIFT = 32768 };
__device__ __forceinline__ float quad_sum(float v) {
    v += __shfl_xor_sync(~0u, v, 1);
    return v + __shfl_xor_sync(~0u, v, 2);
}

__device__ __forceinline__ void store_part(uint8_t* base, uint32_t row_bits, int p, const uint32_t (&pk)[64]) {
    asm volatile("{\n.reg .b64 d0, d1;\nxor.b64 d0, %0, %1;\nxor.b64 d1, d0, 64;\n"
                 "TS: .branchtargets P0, P1, P2, P3, P4, P5, P6, P7;\n"
                 "brx.idx.uni %2, TS;\n"
                 "P0:\n st.global.cg.v4.u32 [d0 + 0], {%3, %4, %5, %6};\n st.global.cg.v4.u32 [d1 + 0], {%11, %12, %13, %14};\n bra.uni DONE;\n"
                 "P1:\n st.global.cg.v4.u32 [d0 + 0], {%7, %8, %9, %10};\n st.global.cg.v4.u32 [d1 + 0], {%15, %16, %17, %18};\n bra.uni DONE;\n"
                 "P2:\n st.global.cg.v4.u32 [d0 + 16384], {%19, %20, %21, %22};\n st.global.cg.v4.u32 [d1 + 16384], {%27, %28, %29, %30};\n bra.uni DONE;\n"
                 "P3:\n st.global.cg.v4.u32 [d0 + 16384], {%23, %24, %25, %26};\n st.global.cg.v4.u32 [d1 + 16384], {%31, %32, %33, %34};\n bra.uni DONE;\n"
                 "P4:\n st.global.cg.v4.u32 [d0 + 65536], {%35, %36, %37, %38};\n st.global.cg.v4.u32 [d1 + 65536], {%43, %44, %45, %46};\n bra.uni DONE;\n"
                 "P5:\n st.global.cg.v4.u32 [d0 + 65536], {%39, %40, %41, %42};\n st.global.cg.v4.u32 [d1 + 65536], {%47, %48, %49, %50};\n bra.uni DONE;\n"
                 "P6:\n st.global.cg.v4.u32 [d0 + 81920], {%51, %52, %53, %54};\n st.global.cg.v4.u32 [d1 + 81920], {%59, %60, %61, %62};\n bra.uni DONE;\n"
                 "P7:\n st.global.cg.v4.u32 [d0 + 81920], {%55, %56, %57, %58};\n st.global.cg.v4.u32 [d1 + 81920], {%63, %64, %65, %66};\n bra.uni DONE;\n"
                 "DONE:\n}\n"
                 ::"l"(base), "l"((uint64_t)((p & 1) ? row_bits : 0)), "r"(p), "r"(pk[0]), "r"(pk[1]), "r"(pk[2]), "r"(pk[3]), "r"(pk[4]), "r"(pk[5]), "r"(pk[6]), "r"(pk[7]), "r"(pk[8]), "r"(pk[9]), "r"(pk[10]), "r"(pk[11]), "r"(pk[12]), "r"(pk[13]), "r"(pk[14]), "r"(pk[15]), "r"(pk[16]), "r"(pk[17]), "r"(pk[18]), "r"(pk[19]), "r"(pk[20]), "r"(pk[21]), "r"(pk[22]), "r"(pk[23]), "r"(pk[24]), "r"(pk[25]), "r"(pk[26]), "r"(pk[27]), "r"(pk[28]), "r"(pk[29]), "r"(pk[30]), "r"(pk[31]), "r"(pk[32]), "r"(pk[33]), "r"(pk[34]), "r"(pk[35]), "r"(pk[36]), "r"(pk[37]), "r"(pk[38]), "r"(pk[39]), "r"(pk[40]), "r"(pk[41]), "r"(pk[42]), "r"(pk[43]), "r"(pk[44]), "r"(pk[45]), "r"(pk[46]), "r"(pk[47]), "r"(pk[48]), "r"(pk[49]), "r"(pk[50]), "r"(pk[51]), "r"(pk[52]), "r"(pk[53]), "r"(pk[54]), "r"(pk[55]), "r"(pk[56]), "r"(pk[57]), "r"(pk[58]), "r"(pk[59]), "r"(pk[60]), "r"(pk[61]), "r"(pk[62]), "r"(pk[63])
                 : "memory");
}

__device__ __forceinline__ void consumer(uint32_t sb, int pair, int c, const CUtensorMap* m_out, const uint8_t* x) {
    const int tid = threadIdx.x;
    const int warp = __shfl_sync(~0u, tid >> 5, 0);
    const int w = warp >> 2, v = warp & 3, lane = tid & 31;

    const uint32_t empty_rel = lane == 2 ? mapa(sb + BAR_EMPTYL, c) : mapa(sb + BAR_EMPTY, lane & 1);
    auto release = [&](uint32_t grp) {
        if (lane < 3) mbar_arrive_cluster(empty_rel + (grp & 7) * 8);
    };
    auto wait_full = [&](uint32_t grp) { mbar_wait(sb + BAR_FULL + (grp & 7) * 8, (grp >> 3) & 1); };

    uint32_t g = 0;
    const uint32_t stg = sb + SM_REGION + w * PAGE + v * 2048;
    const uint32_t chunk0 = (lane >> 2) * 128 + (((lane & 3) ^ (lane >> 2)) << 4);
    uint32_t ndone = 0;
    auto mark_done = [&]() {
        __syncwarp();
        if (lane == 0) mbar_arrive(sb + BAR_DONE + (ndone & 1) * 8);
        ndone++;
    };
    auto ctx_dst = [&](int rnd, int seg) {
        const int rb = query_rowblock(pair, c, w, seg);
        return ptr_off(g_ctx, ((rb >> 1) * 64 + (rnd * 16 + (pair >> 2)) * 2) * PAGE + (rb & 1) * 8192 + v * 2048);
    };

    uint32_t ctl_tab;
    {
        const int t = lane, firstB = 2 * attn_rowblock(pair, 0) + 2 - w;
        auto is_half = [&](int u) { return (u == firstB - 1 || u == 16) && c == (u >= firstB); };
        auto block = [&](int u) { return u + (w == 1 && u >= firstB); };
        auto place = [](int j) { return ((j & 15) << 3) | ((j - (j * 43 >> 8) * 6) << 11); };
        const int jv = min(2 * block(t - 1) + 2, 35), jk = t == 17 ? jv : max(2 * block(t) - 1, 0);
        const bool diag = t == firstB - 1 || t == 16;
        ctl_tab = ((t == 0 || t == firstB) ? CTL_FIRST : 0) | (t == firstB ? CTL_SWITCH : 0) | (t == 17 ? CTL_LAST : 0) |
                  (diag ? (is_half(t) ? CTL_HALF : CTL_MASKHI) : 0) | (t == firstB - 1 ? CTL_LOADQ : 0) |
                  (is_half(t - 1) ? CTL_PVHALF : 0) | ((t == 1 || t == firstB + 1) ? 0 : CTL_PVACC) |
                  place(jk) | ((place(jv) | (t ? 3 : 0)) << 16);
    }

    uint32_t pk[64];
#pragma unroll
    for (int i = 0; i < 64; i++) pk[i] = 0;
    uint8_t* pend = nullptr;
    uint32_t prow = 0x400;
    auto write_part = [&](int p) { store_part(pend, prow, p, pk); };
    if (w == 1) bar_arrive(2, 256);

    for (int item = 0; item < 6; item++) {
        if (item != 2 && item != 5) {
            constexpr int nk = DC / 64;
            float acc[128];
            auto issue_kblock = [&](int first_acc) {
                wait_full(g);
                const uint32_t pg = sb + (g & 3) * (3 * PAGE);
                const uint64_t da = make_desc(pg + w * 8192, 16), db = make_desc(pg + PAGE, 16);
                wg_fence();
                wgmma_n256_ss(acc, da, db, first_acc);
                wgmma_n256_ss(acc, da + 128, db + 2, 1);
                wgmma_n256_ss(acc, da + 256, db + 4, 1);
                wgmma_n256_ss(acc, da + 384, db + 6, 1);
                wg_commit();
                g++;
            };
            if (item == 0) PROF(17, w);
            issue_kblock(0);
            if (item == 0) PROF(1, w);
            if (item == 0 && w == 0) PROF_GT(1);
            const int nparts = item == 0 ? 0 : (item == 3 ? 4 : 8);
            const int ln_row = (pair * 2 + c) * 16 + warp * 2;
            if (item == 0) {
                const uint8_t* src = ptr_off(x, ln_row * (DM * 2) + lane * 16);
#pragma unroll
                for (int i = 0; i < 8; i++) {
                    const uint4 t = __ldcg(reinterpret_cast<const uint4*>(src + i * 512));
                    pk[4 * i] = t.x; pk[4 * i + 1] = t.y; pk[4 * i + 2] = t.z; pk[4 * i + 3] = t.w;
                }
            }
#pragma unroll 1
            for (int kb = 1; kb < nk; kb++) {
                if (kb == nk - 1 && w == 1) bar_sync(4, 256);
                issue_kblock(1);
                if (kb == nk - 1 && w == 0) bar_arrive(4, 256);
                wg_wait<1>();
                release(g - 2);
                if (kb <= nparts) {
                    if (item == 4 && kb == 1) mbar_wait(sb + BAR_DEP + 16, 0);
                    write_part(kb - 1);
                    if (kb == nk - 1) write_part(nk - 1);
                    if (kb == nparts || kb == nk - 1) mark_done();
                }
                if (g >= 4 && g <= 8) {
                    float s[2], q[2];
                    if (g == 4) {
                        ln_sums<0>(pk, s[0], q[0]);
                        pk[32] = __float_as_uint(s[0]); pk[33] = __float_as_uint(q[0]);
                    }
                    if (g == 5) {
                        ln_sums<16>(pk, s[1], q[1]);
                        pk[34] = __float_as_uint(s[1]); pk[35] = __float_as_uint(q[1]);
                    }
                    if (g == 6) {
#pragma unroll
                        for (int r = 0; r < 2; r++) { s[r] = __uint_as_float(pk[32 + 2 * r]); q[r] = __uint_as_float(pk[33 + 2 * r]); }
                        const bool hi = lane & 16, od = lane & 8;
                        float a = hi ? s[1] : s[0], b = hi ? q[1] : q[0];
                        a += __shfl_xor_sync(~0u, hi ? s[0] : s[1], 16);
                        b += __shfl_xor_sync(~0u, hi ? q[0] : q[1], 16);
                        float t = od ? b : a;
                        t += __shfl_xor_sync(~0u, od ? a : b, 8);
#pragma unroll
                        for (int o = 4; o; o >>= 1) t += __shfl_xor_sync(~0u, t, o);
#pragma unroll
                        for (int r = 0; r < 2; r++) {
                            s[r] = __shfl_sync(~0u, t, 16 * r);
                            q[r] = __shfl_sync(~0u, t, 16 * r + 8);
                        }
                        ln_finish(s[0], q[0], pk[36], pk[37], pk[38]);
                        ln_finish(s[1], q[1], pk[39], pk[40], pk[41]);
                    }
                    if (g == 7) ln_apply<0>(pk, pk[36], pk[37], pk[38], ptr_off(g_xn, image_offset(ln_row, lane)));
                    if (g == 8) {
                        ln_apply<16>(pk, pk[39], pk[40], pk[41], ptr_off(g_xn, image_offset(ln_row + 1, lane)));
                        mark_done();
                    }
                }
            }
            wg_wait<0>();
            reg_fence(acc);
            release(g - 1);
            PROF(2 + 2 * item, w);
            if (w == 0) PROF_GT(2 + 2 * item);
            const float ksc = (QSCALE || c) ? 1.0f : SM_SCALE;
#pragma unroll
            for (int i = 0; i < 64; i++) pk[i] = pack_bf16(acc[chunk_src(i)] * ksc, acc[chunk_src(i) + 1] * ksc);
            const uint32_t vrow = (v >> 1) * 32 + (lane >> 3) * 8 + (v & 1) * 4 + ((lane >> 2) & 1);
            pend = ptr_off(g_kv, ((kv_head(pair) + (item == 1 || item == 4 ? 8 : 0)) * 16 + kv_tokens(pair) * 2) * 65536 + w * 8192 +
                                     (c ? 32768 + vrow * 128 + (((lane & 3) ^ (vrow & 7)) << 4) : v * 2048 + chunk0));
            prow = c ? 0x120 : 0x400;
            PROF(3 + 2 * item, w);
            continue;
        }

        float O[64], S[64];
        auto issue_q = [&](int first_acc) {
            wait_full(g);
            const uint32_t pg = sb + (g & 3) * (3 * PAGE);
            const uint64_t da = make_desc(pg + w * 8192, 16), db = make_desc(pg + 2 * PAGE, 8192);
            const uint64_t dab = make_desc(pg + PAGE + (1 - w) * 8192, 16);
            wg_fence();
#pragma unroll
            for (int q = 0; q < 4; q++) wgmma_n128_ss(S, da + 2 * q, db + 128 * q, q ? 1 : first_acc);
            wg_commit();
#pragma unroll
            for (int q = 0; q < 4; q++) wgmma_n128_ss(O, dab + 2 * q, db + 128 * q, q ? 1 : first_acc);
            wg_commit();
            g++;
        };
        issue_q(0);
#pragma unroll 1
        for (int kb = 1; kb < DM / 64; kb++) {
            if (kb == DM / 64 - 2 && w == 1) bar_sync(4, 256);
            issue_q(1);
            if (kb == DM / 64 - 1 && w == 0) bar_arrive(4, 256);
            wg_wait<QSPLIT ? 2 : 1>();
            release(g - 2);
            if (kb <= 8) {
                write_part(kb - 1);
                if (kb == 8) mark_done();
            }
        }
        uint32_t Q[32], Pm[32];
#pragma unroll
        for (int i = 0; i < 32; i++) Pm[i] = PMINIT ? pk[i] : 0;
        float lim = (float)(v * 16 + (lane >> 2) - 8 * (lane & 3));
        float mc[2] = {0.f, 0.f}, l[2] = {0.f, 0.f}, sum[NSUM];
        uint32_t ctl = __shfl_sync(~0u, ctl_tab, 0), nxt = __shfl_sync(~0u, ctl_tab, 1);
        int t = 1;
        asm volatile("" : "+f"(lim), "+f"(mc[0]), "+f"(mc[1]), "+f"(l[0]), "+f"(l[1]), "+r"(ctl), "+r"(nxt), "+r"(t));
        constexpr float qsc = QSCALE ? SM_SCALE : 1.0f;
        wg_wait<QSPLIT ? 1 : 0>();
        reg_fence(S);
#pragma unroll
        for (int i = 0; i < 32; i++) Q[i] = pack_bf16(S[2 * i] * qsc, S[2 * i + 1] * qsc);
        reg_fence(Q);
        wait_full(g);
        wg_wait<0>();
        reg_fence(O);
        release(g - 1);
        PROF(2 + 2 * item, w);
        if (w == 0) PROF_GT(2 + 2 * item);

        auto put_queries = [&](const float (&A)[64]) {
#pragma unroll
            for (int i = 0; i < 8; i++)
                sts128(stg + lane * 16 + (i >> 2) * 8192 + (i & 3) * 512, pack_bf16(A[8 * i] * qsc, A[8 * i + 1] * qsc), pack_bf16(A[8 * i + 2] * qsc, A[8 * i + 3] * qsc),
                       pack_bf16(A[8 * i + 4] * qsc, A[8 * i + 5] * qsc), pack_bf16(A[8 * i + 6] * qsc, A[8 * i + 7] * qsc));
        };
        auto get_queries = [&](int i0, int i1) {
#pragma unroll
            for (int i = i0; i < i1; i++) lds128(stg + lane * 16 + (i >> 2) * 8192 + (i & 3) * 512, Q[4 * i], Q[4 * i + 1], Q[4 * i + 2], Q[4 * i + 3]);
        };
        const uint32_t kdesc0 = (uint32_t)make_desc(sb, PAGE), vdesc0 = (uint32_t)make_desc(sb, 16);
        auto wait_block = [&](uint32_t word) { mbar_wait(sb + BAR_FULL + (word & 56), (word >> 6) & 1); };
        put_queries(O);
        bar_sync(2 + w, 256);
        wg_fence();
        issue_qk(S, Q, kdesc0);
        wg_commit();
        wg_fence();
        wg_commit();
        wg_commit();
        bar_arrive(3 - w, 256);
        for (;;) {
            const bool kready = KTRY ? mbar_try(sb + BAR_FULL + (nxt & 56), (nxt >> 6) & 1) : true;
            if (!KTRY) wait_block(nxt);
            wg_wait<2>();
            reg_fence(S);
            if (ctl & (CTL_HALF | CTL_MASKHI | CTL_SHIFT)) {
                if (ctl & CTL_LOADQ) {
                    get_queries(0, 8);
                    if (EREL && w == 1) release((nxt >> 3) - 2);
                }
                if (ctl & CTL_HALF) mask_half<0>(S, lim, v);
                if (ctl & CTL_MASKHI) mask_half<8>(S, lim, v);
                if (ctl & CTL_SHIFT) shift_rows(S, mc[0], mc[1]);
            }
            float early[4 * EARLY + 1];
#pragma unroll
            for (int j = 0; j < EARLY; j++) {
#pragma unroll
                for (int i = 4 * j; i < 4 * j + 4; i++) early[i] = ex2(S[i]);
                sum[0] = (j ? sum[0] + early[4 * j] : early[4 * j]) + early[4 * j + 1];
                sum[1] = (j ? sum[1] + early[4 * j + 2] : early[4 * j + 2]) + early[4 * j + 3];
            }
            const uint32_t tie = EARLY ? __float_as_uint(sum[0]) & __float_as_uint(sum[1]) & (ctl & 0x80000000u) : 0;
            if (lane < 3) mbar_arrive_cluster(empty_rel + tie + (ctl & 56));
            wg_wait<1>();
#pragma unroll
            for (int j = 0; j < EARLY; j++) {
                asm volatile("" : "+r"(Pm[2 * j]), "+r"(Pm[2 * j + 1])::"memory");
                Pm[2 * j] = pack_bf16(early[4 * j], early[4 * j + 1]);
                Pm[2 * j + 1] = pack_bf16(early[4 * j + 2], early[4 * j + 3]);
            }
            exp_groups<EARLY, 8>(S, Pm, sum);
            const bool half = ctl & CTL_HALF;
            if (!half) {
                wg_wait<0>();
                reg_fence(O);
                if (lane < ((ctl >> 16) & 3)) mbar_arrive_cluster(empty_rel + ((ctl >> 16) & 56));
                exp_groups<8, 16>(S, Pm, sum);
            } else {
                asm volatile("wgmma.wait_group.sync.aligned 0;\n" ::: "memory");
                reg_fence(O);
                if (lane < ((ctl >> 16) & 3)) asm volatile("mbarrier.arrive.shared::cluster.b64 _, [%0];\n" ::"r"(empty_rel + ((ctl >> 16) & 56)) : "memory");
            }
            if (NSUM == 4) { sum[0] += sum[2]; sum[1] += sum[3]; }
            const bool over = !(sum[0] + sum[1] <= SUM_HI);
            if (__any_sync(~0u, over || !kready) || (((ctl & CTL_FIRST) | (nxt & (CTL_SWITCH | CTL_LAST))) != 0)) {
                bool bad = __any_sync(~0u, over);
                if (KTRY && !kready) wait_block(nxt);
                const bool first = ctl & CTL_FIRST;
                if (first) {
                    uint32_t b0 = __ballot_sync(~0u, sum[0] >= SUM_LO), b1 = __ballot_sync(~0u, sum[1] >= SUM_LO);
                    b0 |= b0 >> 1; b1 |= b1 >> 1;
                    b0 |= b0 >> 2; b1 |= b1 >> 2;
                    bad |= (b0 & b1 & 0x11111111u) != 0x11111111u;
                }
                if (bad) {
                    if (half) {
#pragma unroll
                        for (int i = 32; i < 64; i++) S[i] = -INFINITY;
                    }
                    float d0 = fmaxf(S[0], S[1]), d1 = fmaxf(S[2], S[3]);
#pragma unroll
                    for (int j = 1; j < 16; j++) {
                        d0 = fmaxf(d0, fmaxf(S[4 * j], S[4 * j + 1]));
                        d1 = fmaxf(d1, fmaxf(S[4 * j + 2], S[4 * j + 3]));
                    }
                    d0 = fmaxf(d0, __shfl_xor_sync(~0u, d0, 1));
                    d1 = fmaxf(d1, __shfl_xor_sync(~0u, d1, 1));
                    d0 = fmaxf(d0, __shfl_xor_sync(~0u, d0, 2));
                    d1 = fmaxf(d1, __shfl_xor_sync(~0u, d1, 2));
                    if (!first) {
                        d0 = fmaxf(d0, 0.f);
                        d1 = fmaxf(d1, 0.f);
                        const float a0 = ex2(-d0), a1 = ex2(-d1);
#pragma unroll
                        for (int j = 0; j < 16; j++) {
                            O[4 * j] *= a0; O[4 * j + 1] *= a0; O[4 * j + 2] *= a1; O[4 * j + 3] *= a1;
                        }
                        l[0] *= a0; l[1] *= a1;
                    }
                    mc[0] += d0; mc[1] += d1;
                    ctl_tab |= CTL_SHIFT;
                    nxt |= CTL_SHIFT;
                    shift_rows(S, d0, d1);
                    exp_groups<0, 16>(S, Pm, sum);
                    if (NSUM == 4) { sum[0] += sum[2]; sum[1] += sum[3]; }
                }
                if (nxt & CTL_LAST) break;
                if (nxt & CTL_SWITCH) {
                    ctl = nxt & ~CTL_SHIFT;
                    ctl_tab &= ~CTL_SHIFT;
                    const uint32_t vdesc = vdesc0 + ((ctl >> 16) & 0x3800);
                    wait_block(ctl >> 16);
                    bar_sync(2 + w, 256);
                    if (ctl & CTL_PVHALF) {
                        wg_fence();
                        issue_pv<0>(O, Pm, vdesc, ctl & CTL_PVACC);
                        wg_commit();
                    } else {
                        wg_fence();
                        issue_pv<0>(O, Pm, vdesc, ctl & CTL_PVACC);
                        issue_pv<1>(O, Pm, vdesc, 1);
                        wg_commit();
                    }
                    nxt = __shfl_sync(~0u, ctl_tab, ++t);
                    const float scale[2] = {rcp_approx(quad_sum(l[0] + sum[0])), rcp_approx(quad_sum(l[1] + sum[1]))};
                    l[0] = l[1] = mc[0] = mc[1] = 0.f;
                    if (w == 1) { if (!EREL) release((ctl >> 3) - 2); release((ctl >> 3) + 1); }
                    uint8_t* dst = ctx_dst(item == 5, 0);
                    uint8_t* d[2] = {ptr_off(dst, chunk0), ptr_off(dst, chunk0 ^ 64)};
                    wg_fence();
                    issue_qk(S, Q, kdesc0 + (ctl & 0x3800));
                    wg_commit();
                    bar_arrive(3 - w, 256);
                    wg_wait<1>();
                    reg_fence(O);
#pragma unroll
                    for (int i = 0; i < 8; i++) {
                        const float sc = scale[i & 1];
#pragma unroll
                        for (int k = 0; k < 4; k++) Pm[4 * i + k] = pack_bf16(O[chunk_src(4 * i + k)] * sc, O[chunk_src(4 * i + k) + 1] * sc);
                        __stcg(reinterpret_cast<uint4*>(d[(i >> 1) & 1] + (i >> 2) * PAGE + (i & 1) * 1024),
                               make_uint4(Pm[4 * i], Pm[4 * i + 1], Pm[4 * i + 2], Pm[4 * i + 3]));
                    }
                    mark_done();
                    wg_fence();
                    wg_commit();
                    wg_commit();
                    continue;
                }
            }
            ctl = nxt;
            bar_sync(2 + w, 256);
            wg_fence();
            issue_qk(S, Q, kdesc0 + (ctl & 0x3800));
            wg_commit();
            l[0] += sum[0]; l[1] += sum[1];
            nxt = __shfl_sync(~0u, ctl_tab, ++t);
            wait_block(ctl >> 16);
            const uint32_t vdesc = vdesc0 + ((ctl >> 16) & 0x3800);
            wg_fence();
            issue_pv<0>(O, Pm, vdesc, ctl & CTL_PVACC);
            wg_commit();
            issue_pv<1>(O, Pm, vdesc, 1);
            wg_commit();
            bar_arrive(3 - w, 256);
        }
        g += 36;
        if (w == 0) release(g - 3);
        const uint32_t vdesc = vdesc0 + (nxt & 0x3800);
        if (nxt & CTL_PVHALF) {
            wg_fence();
            issue_pv<0>(O, Pm, vdesc, nxt & CTL_PVACC);
            wg_commit();
        } else {
            wg_fence();
            issue_pv<0>(O, Pm, vdesc, nxt & CTL_PVACC);
            issue_pv<1>(O, Pm, vdesc, 1);
            wg_commit();
        }
        ctl_tab = (ctl_tab & ~(0x00780078u | CTL_SHIFT)) | ((ctl_tab + 0x00200020u) & 0x00780078u);
        l[0] += sum[0]; l[1] += sum[1];
        const float i0 = rcp_approx(quad_sum(l[0])), i1 = rcp_approx(quad_sum(l[1]));
        wg_wait<0>();
        reg_fence(O);
        if (w == 0) release(g - 2);
        release(g - 1);
#pragma unroll
        for (int i = 0; i < 32; i++) {
            const float sc = (i & 4) ? i1 : i0;
            pk[i] = pack_bf16(O[chunk_src(i)] * sc, O[chunk_src(i) + 1] * sc);
        }
        pend = ptr_off(ctx_dst(item == 5, 1), chunk0);
        prow = 0x400;
#pragma unroll
        for (int i = 32; i < 64; i++) pk[i] = 0;
        PROF(3 + 2 * item, w);
        if (w == 0) PROF_GT(3 + 2 * item);
    }

    float acc[64];
    uint32_t slot = 0;
    auto issue_out = [&](int first_acc) {
        wait_full(g);
        const uint64_t da = make_desc(sb + slot + w * 8192, 16), db = make_desc(sb + slot + PAGE, 8192);
        wg_fence();
#pragma unroll
        for (int q = 0; q < 4; q++) wgmma_n128_ss(acc, da + 2 * q, db + 128 * q, q ? 1 : first_acc);
        wg_commit();
        g++;
        slot = slot == SM_REGION - 2 * PAGE ? 0 : slot + 2 * PAGE;
    };
    issue_out(0);
#pragma unroll 1
    for (int kb = 1; kb < 64; kb++) {
        issue_out(1);
        wg_wait<1>();
        release(g - 2);
        if (kb <= 8 && !(kb & 1)) {
            write_part((kb >> 1) - 1);
            if (kb == 8) mark_done();
        }
        if (kb >= 32 && (kb & 3) == 2 * w) {
            uint32_t u0, u1, u2, u3;
            const uint32_t a = stg + (kb & 16) * 512 + (kb & 12) * 128 + lane * 16;
            mbar_wait(sb + BAR_G + w * 8, 0);
            lds128(a, u0, u1, u2, u3);
            sts128(a, pack_bf16(silu_f(bf_lo(u0)), silu_f(bf_hi(u0))), pack_bf16(silu_f(bf_lo(u1)), silu_f(bf_hi(u1))),
                   pack_bf16(silu_f(bf_lo(u2)), silu_f(bf_hi(u2))), pack_bf16(silu_f(bf_lo(u3)), silu_f(bf_hi(u3))));
        }
    }
    wait_full(g);
    __syncwarp();
    const uint32_t xs = sb + slot + w * PAGE + v * 2048;
    uint32_t xr[32], gr[32];
#pragma unroll
    for (int s = 0; s < 8; s++) {
        ldmatrix_x4(slab_addr(xs, lane, s), xr[4 * s], xr[4 * s + 1], xr[4 * s + 2], xr[4 * s + 3]);
        ldmatrix_x4(slab_addr(stg, lane, s), gr[4 * s], gr[4 * s + 1], gr[4 * s + 2], gr[4 * s + 3]);
    }
    wg_wait<0>();
    reg_fence(acc);
    PROF(14, w);
    if (w == 0) PROF_GT(14);
#pragma unroll
    for (int s = 0; s < 8; s++) {
        uint32_t o[4];
#pragma unroll
        for (int k = 0; k < 4; k++)
            o[k] = bf2_add(xr[4 * s + k], bf2_mul(pack_bf16(acc[8 * s + 2 * k], acc[8 * s + 2 * k + 1]), gr[4 * s + k]));
        stmatrix_x4(slab_addr(stg, lane, s), o[0], o[1], o[2], o[3]);
    }
    fence_async_smem();
    __syncwarp();
    PROF(28, w);
    if (lane == 0) {
        const int orow = ((pair >> 1) & 7) * 256 + c * 128 + w * 64 + v * 16, ocol = (pair >> 4) * 256 + (pair & 1) * 128;
        tma_store_2d(m_out, ocol, orow, stg);
        tma_store_2d(m_out, ocol + 64, orow, stg + 8192);
        bulk_commit();
        bulk_wait_read();
    }
    __syncwarp();
}

__global__ void __cluster_dims__(2, 1, 1) __launch_bounds__(384, 1)
fused_kernel(const __grid_constant__ CUtensorMap m_ckv, const __grid_constant__ CUtensorMap m_wuk,
             const __grid_constant__ CUtensorMap m_wuv, const __grid_constant__ CUtensorMap m_wq,
             const __grid_constant__ CUtensorMap m_wo, const __grid_constant__ CUtensorMap m_x,
             const __grid_constant__ CUtensorMap m_out, const __grid_constant__ CUtensorMap m_gate,
             const __grid_constant__ CUtensorMap m_up, const __grid_constant__ CUtensorMap m_down, const Params P) {
    extern __shared__ __align__(1024) uint8_t smem[];
    const uint32_t sb = __shfl_sync(~0u, smem_u32(smem), 0);
    const int tid = threadIdx.x;
    const int cl = blockIdx.x >> 1, c = blockIdx.x & 1;
    const int pair = cl >= 64 ? cl : cl < 4 ? cl * 16 + 15 : cl < 36 ? ((cl - 4) >> 3) * 16 + ((cl - 4) & 7)
                                                                    : ((cl - 36) / 7) * 16 + 8 + (cl - 36) % 7;
    const bool starter = tid == 256 && pair < NMAIN / 2;
    if (tid == 256) {
#pragma unroll
        for (int i = 0; i < NBAR; i++) mbar_init(sb + SM_BAR + i * 8, (i >> 3) == 1 ? 16 : i >= 25 ? 8 : 1);
        asm volatile("fence.mbarrier_init.release.cluster;" ::: "memory");
    }
    const CUtensorMap* m_wu = c ? &m_wuv : &m_wuk;
    if (starter) {
        prefetch_map(&m_ckv);
#pragma unroll 1
        for (int kb = 0; kb < 4; kb++) {
            mbar_expect_tx(sb + BAR_FULL + kb * 8, 3 * PAGE);
            if (kb < EARLYW) tma_3d(sb + kb * (3 * PAGE), m_wu, 0, kb * 64, kv_head(pair) * 2, sb + BAR_FULL + kb * 8);
        }
    }
    PROF(18, (tid >> 7) & 1);
    __syncthreads();
    cluster_sync();
    PROF(22, (tid >> 7) & 1);
    if (starter) {
#pragma unroll 1
        for (int kb = 0; kb < 4; kb++) {
            if (kb >= EARLYW) tma_3d(sb + kb * (3 * PAGE), m_wu, 0, kb * 64, kv_head(pair) * 2, sb + BAR_FULL + kb * 8);
            tma_3d_mc(sb + kb * (3 * PAGE) + (1 + c) * PAGE, &m_ckv, 0, kv_tokens(pair) * 256 + c * 128, kb, sb + BAR_FULL + kb * 8);
        }
    }
    PROF(19, (tid >> 7) & 1);
    const int warp = __shfl_sync(~0u, tid >> 5, 0), lane = tid & 31;
    auto finish = [&]() {
        PROF(29, tid >> 7);
        cluster_sync();
        if (tid == 0) atomicAdd(&g_sync.done, 1u);
    };
    if (pair >= NMAIN / 2) {
        if (warp < 8) ffn_cta(smem, sb, blockIdx.x - NMAIN, __ldcg(&g_sync.done) / NCTA, P.w_r);
        else if (tid == 256) ffn_producer(sb, blockIdx.x - NMAIN, &m_gate, &m_up, &m_down);
        __syncwarp();
        finish();
    } else if (warp < 8) {
        asm volatile("setmaxnreg.inc.sync.aligned.u32 232;");
        consumer(sb, pair, c, &m_out, (const uint8_t*)P.x);
        finish();
    } else {
        asm volatile("setmaxnreg.dec.sync.aligned.u32 40;");
        if (warp == 10) {
            sync_helper(sb, lane, pair, c);
        } else if (warp & 1) {
            fetch_helper(P, sb, (warp >> 1) & 1, lane, pair, c);
        } else {
            producer(P, sb, pair, c, &m_ckv, m_wu, &m_wq, &m_wo, &m_x, &m_out);
        }
        cluster_sync();
    }
}

typedef CUresult (*EncodeFn)(CUtensorMap*, CUtensorMapDataType, cuuint32_t, void*, const cuuint64_t*, const cuuint64_t*,
                             const cuuint32_t*, const cuuint32_t*, CUtensorMapInterleave, CUtensorMapSwizzle,
                             CUtensorMapL2promotion, CUtensorMapFloatOOBfill);

void make_map_2d(EncodeFn fn, CUtensorMap* m, const void* ptr, int rows, int cols, int box_rows) {
    cuuint64_t dims[2] = {(cuuint64_t)cols, (cuuint64_t)rows};
    cuuint64_t strides[1] = {(cuuint64_t)cols * 2};
    cuuint32_t box[2] = {64, (cuuint32_t)box_rows};
    cuuint32_t es[2] = {1, 1};
    fn(m, CU_TENSOR_MAP_DATA_TYPE_BFLOAT16, 2, const_cast<void*>(ptr), dims, strides, box, es, CU_TENSOR_MAP_INTERLEAVE_NONE,
       CU_TENSOR_MAP_SWIZZLE_128B, CU_TENSOR_MAP_L2_PROMOTION_L2_256B, CU_TENSOR_MAP_FLOAT_OOB_FILL_NONE);
}
void make_map_w(EncodeFn fn, CUtensorMap* m, const void* ptr, int rows, int cols, int blocks, int box_rows = 32) {
    cuuint64_t dims[3] = {64, (cuuint64_t)rows, (cuuint64_t)cols / 64};
    cuuint64_t strides[2] = {(cuuint64_t)cols * 2, 128};
    cuuint32_t box[3] = {64, (cuuint32_t)box_rows, (cuuint32_t)blocks};
    cuuint32_t es[3] = {1, 1, 1};
    fn(m, CU_TENSOR_MAP_DATA_TYPE_BFLOAT16, 3, const_cast<void*>(ptr), dims, strides, box, es, CU_TENSOR_MAP_INTERLEAVE_NONE,
       CU_TENSOR_MAP_SWIZZLE_128B, CU_TENSOR_MAP_L2_PROMOTION_L2_256B, CU_TENSOR_MAP_FLOAT_OOB_FILL_NONE);
}

}

extern "C" void kernel_launch(void* const* d_in, const int* in_sizes, int n_in, void* d_out, int out_size) {
    static EncodeFn fn = nullptr;
    if (!fn) {
        void* f = nullptr;
        cudaDriverEntryPointQueryResult qr;
        cudaGetDriverEntryPoint("cuTensorMapEncodeTiled", &f, cudaEnableDefault, &qr);
        fn = (EncodeFn)f;
        cudaFuncSetAttribute(fused_kernel, cudaFuncAttributeMaxDynamicSharedMemorySize, SMEM_BYTES);
    }
    CUtensorMap m_ckv, m_wuk, m_wuv, m_wq, m_wo, m_x, m_out, m_gate, m_up, m_down;
    make_map_w(fn, &m_gate, d_in[8], DM, FF, FS / 64, 16);
    make_map_w(fn, &m_up, d_in[9], DM, FF, FS / 64, 16);
    make_map_w(fn, &m_down, d_in[10], FF, DM, DM / 64, 16);
    make_map_w(fn, &m_ckv, d_in[1], SEQ, DC, 1, 128);
    make_map_w(fn, &m_wq, d_in[2], DM, NH * 128, 1, 64);
    make_map_w(fn, &m_wuk, d_in[3], DC, NH * 128, 2, 64);
    make_map_w(fn, &m_wuv, d_in[4], DC, NH * 128, 2, 64);
    make_map_w(fn, &m_wo, d_in[5], NH * 128, DM, 1, 64);
    make_map_w(fn, &m_x, d_in[0], SEQ, DM, 2, 64);
    make_map_2d(fn, &m_out, d_out, SEQ, DM, 16);
    Params P;
    P.x = (const __nv_bfloat16*)d_in[0];
    P.w_r = (const __nv_bfloat16*)d_in[7];
    P.c_kv = (const uint8_t*)d_in[1];
    P.w_uk = (const uint8_t*)d_in[3];
    P.w_uv = (const uint8_t*)d_in[4];
    fused_kernel<<<NCTA, 384, SMEM_BYTES>>>(m_ckv, m_wuk, m_wuv, m_wq, m_wo, m_x, m_out, m_gate, m_up, m_down, P);
}
```

```cpp
#include <cuda_runtime.h>
#include <cuda_bf16.h>
#include <cuda.h>
#include <stdint.h>
#include <type_traits>
#define WN 4
#define WINP 1
#define LQN 8
#define LQPOS 1
#define QOPQ 0
#define NTIE 1
#define KTRY 1
#define MASKV 1
#define EREL 0
#define NSUM 2
#define EARLY 2
#define PMINIT 1
#define QSPLIT 1
#define PARK0 1
#define MG 8
#define LQEND 4
#define QKORD 1
#define BALLOT 1
#define AMAP 1
#define EARLYW 2
#define QSCALE 1
#define INPLACE 1

namespace {

constexpr int SEQ = 2048, DM = 1024, NH = 32, DC = 512, FF = 3584;
constexpr int PAGE = 16384;
constexpr int NRING = 12;
constexpr int NCTA = 132, NMAIN = 128;
constexpr uint32_t SM_REGION = NRING * PAGE;
constexpr uint32_t SM_BAR = (NRING + 2) * PAGE;
constexpr uint32_t BAR_FULL = SM_BAR, BAR_EMPTY = SM_BAR + 64;
constexpr uint32_t BAR_DEP = SM_BAR + 128;
constexpr uint32_t BAR_G = SM_BAR + 184;
constexpr uint32_t BAR_DONE = SM_BAR + 200;
constexpr uint32_t BAR_EMPTYL = SM_BAR + 216;
constexpr int NBAR = 35;
constexpr uint32_t SM_PROF = SM_BAR + 320;
constexpr int SMEM_BYTES = SM_PROF + 512;
constexpr uint32_t SPIN_LIMIT = 1u << 16;
constexpr uint32_t POLL_MASK = 7;

struct SyncBlock {
    unsigned done;       unsigned pad0[31];
    unsigned ln;         unsigned pad1[31];
    unsigned router;     unsigned pad4[31];
    unsigned ffn_ticket; unsigned pad2[31];
    unsigned ffn_done;   unsigned pad3[31];
    unsigned kv[NH * 8];
    unsigned kvfree[16 * 8];
    unsigned ctx[32 * NH];
};

__device__ __align__(1024) uint8_t g_xn[8 * 16 * 4 * 8192];
__device__ __align__(4096) uint8_t g_kv[16 * 16 * 65536];
__device__ __align__(4096) uint8_t g_ctx[16 * 64 * 16384];
__device__ __align__(16) uint4 g_routed[2 * 128];
__device__ int g_sel[2];
__device__ __align__(16) float g_r[SEQ];
__device__ __align__(16) float g_ypart[4 * 2 * DM];
__device__ SyncBlock g_sync;

__device__ __forceinline__ uint32_t smem_u32(const void* p) { return (uint32_t)__cvta_generic_to_shared(p); }

__device__ __forceinline__ void mbar_init(uint32_t bar, uint32_t count) {
    asm volatile("mbarrier.init.shared::cta.b64 [%0], %1;" ::"r"(bar), "r"(count) : "memory");
}
#define MBAR_WAIT_ASM(HINT, LIMIT)                                                                  \
    asm volatile("{\n.reg .pred p;\n.reg .u32 n;\nmov.u32 n, 0;\n"                                  \
                 "WAIT_LOOP:\n"                                                                     \
                 "mbarrier.try_wait.parity.shared::cta.b64 p, [%0], %1" HINT ";\n"                  \
                 "@p bra WAIT_DONE;\n"                                                              \
                 "add.u32 n, n, 1;\n"                                                               \
                 "setp.lt.u32 p, n, " LIMIT ";\n"                                                   \
                 "@p bra WAIT_LOOP;\n"                                                              \
                 "WAIT_DONE:\n}\n" ::"r"(bar), "r"(parity) : "memory")
__device__ __forceinline__ void mbar_wait(uint32_t bar, uint32_t parity) { MBAR_WAIT_ASM("", "131072"); }
__device__ __forceinline__ void mbar_sleep(uint32_t bar, uint32_t parity) { MBAR_WAIT_ASM(", 2000", "8192"); }
__device__ __forceinline__ bool mbar_try(uint32_t bar, uint32_t parity) {
    uint32_t ok;
    asm volatile("{\n.reg .pred p;\nmbarrier.try_wait.parity.shared::cta.b64 p, [%1], %2;\nselp.u32 %0, 1, 0, p;\n}\n"
                 : "=r"(ok) : "r"(bar), "r"(parity) : "memory");
    return ok;
}
__device__ __forceinline__ bool mbar_test(uint32_t bar, uint32_t parity) {
    uint32_t ok;
    asm volatile("{\n.reg .pred p;\nmbarrier.test_wait.parity.shared::cta.b64 p, [%1], %2;\nselp.u32 %0, 1, 0, p;\n}\n"
                 : "=r"(ok) : "r"(bar), "r"(parity) : "memory");
    return ok;
}
__device__ __forceinline__ bool elect_one() {
    uint32_t ok;
    asm volatile("{\n.reg .pred p;\nelect.sync _|p, 0xffffffff;\nselp.u32 %0, 1, 0, p;\n}\n" : "=r"(ok));
    return ok;
}
__device__ __forceinline__ void mbar_arrive(uint32_t bar) {
    asm volatile("mbarrier.arrive.shared::cta.b64 _, [%0];" ::"r"(bar) : "memory");
}
__device__ __forceinline__ void mbar_expect_tx(uint32_t bar, uint32_t bytes) {
    asm volatile("mbarrier.arrive.expect_tx.shared::cta.b64 _, [%0], %1;" ::"r"(bar), "r"(bytes) : "memory");
}
__device__ __forceinline__ void mbar_arrive_cluster(uint32_t cluster_addr) {
    asm volatile("mbarrier.arrive.shared::cluster.b64 _, [%0];" ::"r"(cluster_addr) : "memory");
}
__device__ __forceinline__ uint32_t mapa(uint32_t addr, uint32_t rank) {
    uint32_t r;
    asm("mapa.shared::cluster.u32 %0, %1, %2;" : "=r"(r) : "r"(addr), "r"(rank));
    return r;
}
__device__ __forceinline__ void tma_3d(uint32_t dst, const CUtensorMap* m, int c0, int c1, int c2, uint32_t bar) {
    asm volatile("cp.async.bulk.tensor.3d.shared::cluster.global.mbarrier::complete_tx::bytes [%0], [%1, {%3, %4, %5}], [%2];"
                 ::"r"(dst), "l"(m), "r"(bar), "r"(c0), "r"(c1), "r"(c2) : "memory");
}
__device__ __forceinline__ void tma_3d_hint(uint32_t dst, const CUtensorMap* m, int c0, int c1, int c2, uint32_t bar, uint64_t pol) {
    asm volatile("cp.async.bulk.tensor.3d.shared::cluster.global.mbarrier::complete_tx::bytes.L2::cache_hint [%0], [%1, {%3, %4, %5}], [%2], %6;"
                 ::"r"(dst), "l"(m), "r"(bar), "r"(c0), "r"(c1), "r"(c2), "l"(pol) : "memory");
}
__device__ __forceinline__ void tma_3d_mc(uint32_t dst, const CUtensorMap* m, int c0, int c1, int c2, uint32_t bar) {
    asm volatile("cp.async.bulk.tensor.3d.shared::cluster.global.mbarrier::complete_tx::bytes.multicast::cluster [%0], [%1, {%3, %4, %5}], [%2], %6;"
                 ::"r"(dst), "l"(m), "r"(bar), "r"(c0), "r"(c1), "r"(c2), "h"((uint16_t)3) : "memory");
}
__device__ __forceinline__ void bulk_load(uint32_t dst, const void* src, uint32_t bytes, uint32_t bar) {
    asm volatile("cp.async.bulk.shared::cluster.global.mbarrier::complete_tx::bytes [%0], [%1], %2, [%3];"
                 ::"r"(dst), "l"(src), "r"(bytes), "r"(bar) : "memory");
}
__device__ __forceinline__ void cp_async16(uint32_t dst, const void* src) {
    asm volatile("cp.async.cg.shared.global [%0], [%1], 16;" ::"r"(dst), "l"(src) : "memory");
}
__device__ __forceinline__ void bulk_load_mc(uint32_t dst, const void* src, uint32_t bytes, uint32_t bar) {
    asm volatile("cp.async.bulk.shared::cluster.global.mbarrier::complete_tx::bytes.multicast::cluster [%0], [%1], %2, [%3], %4;"
                 ::"r"(dst), "l"(src), "r"(bytes), "r"(bar), "h"((uint16_t)3) : "memory");
}
__device__ __forceinline__ void tma_store_2d(const CUtensorMap* m, int c0, int c1, uint32_t src) {
    asm volatile("cp.async.bulk.tensor.2d.global.shared::cta.bulk_group [%0, {%2, %3}], [%1];"
                 ::"l"(m), "r"(src), "r"(c0), "r"(c1) : "memory");
}
__device__ __forceinline__ void bulk_commit() { asm volatile("cp.async.bulk.commit_group;" ::: "memory"); }
__device__ __forceinline__ void bulk_wait_read() { asm volatile("cp.async.bulk.wait_group.read 0;" ::: "memory"); }
__device__ __forceinline__ void fence_async_smem() { asm volatile("fence.proxy.async.shared::cta;" ::: "memory"); }
__device__ __forceinline__ void prefetch_map(const CUtensorMap* m) {
    asm volatile("prefetch.tensormap [%0];" ::"l"(m) : "memory");
}
__device__ __forceinline__ void red_release(unsigned* p) {
    asm volatile("red.release.gpu.global.add.u32 [%0], 1;" ::"l"(p) : "memory");
}
__device__ __forceinline__ unsigned ld_relaxed(const unsigned* p) {
    unsigned v;
    asm volatile("ld.relaxed.gpu.global.u32 %0, [%1];" : "=r"(v) : "l"(p) : "memory");
    return v;
}
__device__ __forceinline__ void wait_counter(const unsigned* p, unsigned target) {
    for (uint32_t n = 0; (int)(ld_relaxed(p) - target) < 0 && n < SPIN_LIMIT; n++) __nanosleep(100);
    asm volatile("fence.acquire.gpu;" ::: "memory");
    asm volatile("fence.proxy.async.global;" ::: "memory");
}
__device__ __forceinline__ void bar_sync(int id, int n) { asm volatile("bar.sync %0, %1;" ::"r"(id), "r"(n) : "memory"); }
__device__ __forceinline__ void bar_arrive(int id, int n) { asm volatile("bar.arrive %0, %1;" ::"r"(id), "r"(n) : "memory"); }
__device__ __forceinline__ void cluster_sync() {
    asm volatile("barrier.cluster.arrive.relaxed.aligned;\nbarrier.cluster.wait.aligned;" ::: "memory");
}
__device__ __forceinline__ void wg_fence() { asm volatile("wgmma.fence.sync.aligned;" ::: "memory"); }
__device__ __forceinline__ void wg_commit() { asm volatile("wgmma.commit_group.sync.aligned;" ::: "memory"); }
template <int N> __device__ __forceinline__ void wg_wait() { asm volatile("wgmma.wait_group.sync.aligned %0;" ::"n"(N) : "memory"); }
template <int N> __device__ __forceinline__ void reg_fence(float (&a)[N]) {
#pragma unroll
    for (int i = 0; i < N; i++) asm volatile("" : "+f"(a[i])::"memory");
}
template <int N> __device__ __forceinline__ void reg_fence(uint32_t (&a)[N]) {
#pragma unroll
    for (int i = 0; i < N; i++) asm volatile("" : "+r"(a[i])::"memory");
}
__device__ __forceinline__ uint32_t pack_bf16(float lo, float hi) {
    uint32_t r;
    asm("cvt.rn.bf16x2.f32 %0, %1, %2;" : "=r"(r) : "f"(hi), "f"(lo));
    return r;
}
__device__ __forceinline__ float bf_lo(uint32_t v) { return __uint_as_float(v << 16); }
__device__ __forceinline__ float bf_hi(uint32_t v) { return __uint_as_float(v & 0xffff0000u); }
__device__ __forceinline__ float bf_round(float v) { return __bfloat162float(__float2bfloat16_rn(v)); }
__device__ __forceinline__ float ex2(float v) {
    float r;
    asm("ex2.approx.ftz.f32 %0, %1;" : "=f"(r) : "f"(v));
    return r;
}
__device__ __forceinline__ float sqrt_approx(float v) {
    float r;
    asm("sqrt.approx.ftz.f32 %0, %1;" : "=f"(r) : "f"(v));
    return r;
}
__device__ __forceinline__ float rcp_approx(float v) {
    float r;
    asm("rcp.approx.ftz.f32 %0, %1;" : "=f"(r) : "f"(v));
    return r;
}
__device__ __forceinline__ float silu_f(float v) { return v * rcp_approx(1.0f + ex2(v * -1.4426950408889634f)); }
__device__ __forceinline__ void stmatrix_x4(uint32_t addr, uint32_t r0, uint32_t r1, uint32_t r2, uint32_t r3) {
    asm volatile("stmatrix.sync.aligned.m8n8.x4.shared.b16 [%0], {%1, %2, %3, %4};"
                 ::"r"(addr), "r"(r0), "r"(r1), "r"(r2), "r"(r3) : "memory");
}
__device__ __forceinline__ void sts128(uint32_t addr, uint32_t r0, uint32_t r1, uint32_t r2, uint32_t r3) {
    asm volatile("st.shared.v4.b32 [%0], {%1, %2, %3, %4};" ::"r"(addr), "r"(r0), "r"(r1), "r"(r2), "r"(r3) : "memory");
}
__device__ __forceinline__ void lds128(uint32_t addr, uint32_t& r0, uint32_t& r1, uint32_t& r2, uint32_t& r3) {
    asm volatile("ld.shared.v4.b32 {%0, %1, %2, %3}, [%4];" : "=r"(r0), "=r"(r1), "=r"(r2), "=r"(r3) : "r"(addr) : "memory");
}
__device__ __forceinline__ void ldmatrix_x4(uint32_t addr, uint32_t& r0, uint32_t& r1, uint32_t& r2, uint32_t& r3) {
    asm volatile("ldmatrix.sync.aligned.m8n8.x4.shared.b16 {%0, %1, %2, %3}, [%4];"
                 : "=r"(r0), "=r"(r1), "=r"(r2), "=r"(r3) : "r"(addr) : "memory");
}
__device__ __forceinline__ uint32_t bf2_mul(uint32_t a, uint32_t b) {
    uint32_t r;
    asm("mul.rn.bf16x2 %0, %1, %2;" : "=r"(r) : "r"(a), "r"(b));
    return r;
}
__device__ __forceinline__ uint32_t bf2_add(uint32_t a, uint32_t b) {
    uint32_t r;
    asm("add.rn.bf16x2 %0, %1, %2;" : "=r"(r) : "r"(a), "r"(b));
    return r;
}
__device__ __forceinline__ uint64_t policy_evict_first() {
    uint64_t p;
    asm("createpolicy.fractional.L2::evict_first.b64 %0, 1.0;" : "=l"(p));
    return p;
}

__device__ __forceinline__ uint64_t make_desc(uint32_t addr, uint32_t lbo_bytes) {
    return (uint64_t)((addr & 0x3FFFF) >> 4) | ((uint64_t)(lbo_bytes >> 4) << 16) | ((uint64_t)(1024 >> 4) << 32) | (1ull << 62);
}

__device__ __forceinline__ void wgmma_n256_ss(float (&d)[128], uint64_t da, uint64_t db, int acc) {
    asm volatile(
        "{\n.reg .pred p;\nsetp.ne.b32 p, %130, 0;\n"
        "wgmma.mma_async.sync.aligned.m64n256k16.f32.bf16.bf16 {"
        "%0, %1, %2, %3, %4, %5, %6, %7, %8, %9, %10, %11, %12, %13, %14, %15, "
        "%16, %17, %18, %19, %20, %21, %22, %23, %24, %25, %26, %27, %28, %29, %30, %31, "
        "%32, %33, %34, %35, %36, %37, %38, %39, %40, %41, %42, %43, %44, %45, %46, %47, "
        "%48, %49, %50, %51, %52, %53, %54, %55, %56, %57, %58, %59, %60, %61, %62, %63, "
        "%64, %65, %66, %67, %68, %69, %70, %71, %72, %73, %74, %75, %76, %77, %78, %79, "
        "%80, %81, %82, %83, %84, %85, %86, %87, %88, %89, %90, %91, %92, %93, %94, %95, "
        "%96, %97, %98, %99, %100, %101, %102, %103, %104, %105, %106, %107, %108, %109, %110, %111, "
        "%112, %113, %114, %115, %116, %117, %118, %119, %120, %121, %122, %123, %124, %125, %126, %127"
        "}, %128, %129, p, 1, 1, 1, 0;\n}\n"
        :
        "+f"(d[0]), "+f"(d[1]), "+f"(d[2]), "+f"(d[3]), "+f"(d[4]), "+f"(d[5]), "+f"(d[6]), "+f"(d[7]),
        "+f"(d[8]), "+f"(d[9]), "+f"(d[10]), "+f"(d[11]), "+f"(d[12]), "+f"(d[13]), "+f"(d[14]), "+f"(d[15]),
        "+f"(d[16]), "+f"(d[17]), "+f"(d[18]), "+f"(d[19]), "+f"(d[20]), "+f"(d[21]), "+f"(d[22]), "+f"(d[23]),
        "+f"(d[24]), "+f"(d[25]), "+f"(d[26]), "+f"(d[27]), "+f"(d[28]), "+f"(d[29]), "+f"(d[30]), "+f"(d[31]),
        "+f"(d[32]), "+f"(d[33]), "+f"(d[34]), "+f"(d[35]), "+f"(d[36]), "+f"(d[37]), "+f"(d[38]), "+f"(d[39]),
        "+f"(d[40]), "+f"(d[41]), "+f"(d[42]), "+f"(d[43]), "+f"(d[44]), "+f"(d[45]), "+f"(d[46]), "+f"(d[47]),
        "+f"(d[48]), "+f"(d[49]), "+f"(d[50]), "+f"(d[51]), "+f"(d[52]), "+f"(d[53]), "+f"(d[54]), "+f"(d[55]),
        "+f"(d[56]), "+f"(d[57]), "+f"(d[58]), "+f"(d[59]), "+f"(d[60]), "+f"(d[61]), "+f"(d[62]), "+f"(d[63]),
        "+f"(d[64]), "+f"(d[65]), "+f"(d[66]), "+f"(d[67]), "+f"(d[68]), "+f"(d[69]), "+f"(d[70]), "+f"(d[71]),
        "+f"(d[72]), "+f"(d[73]), "+f"(d[74]), "+f"(d[75]), "+f"(d[76]), "+f"(d[77]), "+f"(d[78]), "+f"(d[79]),
        "+f"(d[80]), "+f"(d[81]), "+f"(d[82]), "+f"(d[83]), "+f"(d[84]), "+f"(d[85]), "+f"(d[86]), "+f"(d[87]),
        "+f"(d[88]), "+f"(d[89]), "+f"(d[90]), "+f"(d[91]), "+f"(d[92]), "+f"(d[93]), "+f"(d[94]), "+f"(d[95]),
        "+f"(d[96]), "+f"(d[97]), "+f"(d[98]), "+f"(d[99]), "+f"(d[100]), "+f"(d[101]), "+f"(d[102]), "+f"(d[103]),
        "+f"(d[104]), "+f"(d[105]), "+f"(d[106]), "+f"(d[107]), "+f"(d[108]), "+f"(d[109]), "+f"(d[110]), "+f"(d[111]),
        "+f"(d[112]), "+f"(d[113]), "+f"(d[114]), "+f"(d[115]), "+f"(d[116]), "+f"(d[117]), "+f"(d[118]), "+f"(d[119]),
        "+f"(d[120]), "+f"(d[121]), "+f"(d[122]), "+f"(d[123]), "+f"(d[124]), "+f"(d[125]), "+f"(d[126]), "+f"(d[127])
        : "l"(da), "l"(db), "r"(acc));
}

template <int TB>
__device__ __forceinline__ void wgmma_n128_rs(float (&d)[64], uint32_t a0, uint32_t a1, uint32_t a2, uint32_t a3, uint32_t db, int acc) {
    asm volatile(
        "{\n.reg .pred p;\n.reg .b64 db;\nsetp.ne.b32 p, %69, 0;\nmov.b64 db, {%68, 0x40000040};\n"
        "wgmma.mma_async.sync.aligned.m64n128k16.f32.bf16.bf16 {"
        "%0, %1, %2, %3, %4, %5, %6, %7, %8, %9, %10, %11, %12, %13, %14, %15, "
        "%16, %17, %18, %19, %20, %21, %22, %23, %24, %25, %26, %27, %28, %29, %30, %31, "
        "%32, %33, %34, %35, %36, %37, %38, %39, %40, %41, %42, %43, %44, %45, %46, %47, "
        "%48, %49, %50, %51, %52, %53, %54, %55, %56, %57, %58, %59, %60, %61, %62, %63"
        "}, {%64, %65, %66, %67}, db, p, 1, 1, %70;\n}\n"
        :
        "+f"(d[0]), "+f"(d[1]), "+f"(d[2]), "+f"(d[3]), "+f"(d[4]), "+f"(d[5]), "+f"(d[6]), "+f"(d[7]),
        "+f"(d[8]), "+f"(d[9]), "+f"(d[10]), "+f"(d[11]), "+f"(d[12]), "+f"(d[13]), "+f"(d[14]), "+f"(d[15]),
        "+f"(d[16]), "+f"(d[17]), "+f"(d[18]), "+f"(d[19]), "+f"(d[20]), "+f"(d[21]), "+f"(d[22]), "+f"(d[23]),
        "+f"(d[24]), "+f"(d[25]), "+f"(d[26]), "+f"(d[27]), "+f"(d[28]), "+f"(d[29]), "+f"(d[30]), "+f"(d[31]),
        "+f"(d[32]), "+f"(d[33]), "+f"(d[34]), "+f"(d[35]), "+f"(d[36]), "+f"(d[37]), "+f"(d[38]), "+f"(d[39]),
        "+f"(d[40]), "+f"(d[41]), "+f"(d[42]), "+f"(d[43]), "+f"(d[44]), "+f"(d[45]), "+f"(d[46]), "+f"(d[47]),
        "+f"(d[48]), "+f"(d[49]), "+f"(d[50]), "+f"(d[51]), "+f"(d[52]), "+f"(d[53]), "+f"(d[54]), "+f"(d[55]),
        "+f"(d[56]), "+f"(d[57]), "+f"(d[58]), "+f"(d[59]), "+f"(d[60]), "+f"(d[61]), "+f"(d[62]), "+f"(d[63])
        : "r"(a0), "r"(a1), "r"(a2), "r"(a3), "r"(db), "r"(acc), "n"(TB));
}

__device__ __forceinline__ void wgmma_n128_ss(float* d, uint64_t da, uint64_t db, int acc) {
    asm volatile(
        "{\n.reg .pred p;\nsetp.ne.b32 p, %66, 0;\n"
        "wgmma.mma_async.sync.aligned.m64n128k16.f32.bf16.bf16 {"
        "%0, %1, %2, %3, %4, %5, %6, %7, %8, %9, %10, %11, %12, %13, %14, %15, "
        "%16, %17, %18, %19, %20, %21, %22, %23, %24, %25, %26, %27, %28, %29, %30, %31, "
        "%32, %33, %34, %35, %36, %37, %38, %39, %40, %41, %42, %43, %44, %45, %46, %47, "
        "%48, %49, %50, %51, %52, %53, %54, %55, %56, %57, %58, %59, %60, %61, %62, %63"
        "}, %64, %65, p, 1, 1, 0, 1;\n}\n"
        :
        "+f"(d[0]), "+f"(d[1]), "+f"(d[2]), "+f"(d[3]), "+f"(d[4]), "+f"(d[5]), "+f"(d[6]), "+f"(d[7]),
        "+f"(d[8]), "+f"(d[9]), "+f"(d[10]), "+f"(d[11]), "+f"(d[12]), "+f"(d[13]), "+f"(d[14]), "+f"(d[15]),
        "+f"(d[16]), "+f"(d[17]), "+f"(d[18]), "+f"(d[19]), "+f"(d[20]), "+f"(d[21]), "+f"(d[22]), "+f"(d[23]),
        "+f"(d[24]), "+f"(d[25]), "+f"(d[26]), "+f"(d[27]), "+f"(d[28]), "+f"(d[29]), "+f"(d[30]), "+f"(d[31]),
        "+f"(d[32]), "+f"(d[33]), "+f"(d[34]), "+f"(d[35]), "+f"(d[36]), "+f"(d[37]), "+f"(d[38]), "+f"(d[39]),
        "+f"(d[40]), "+f"(d[41]), "+f"(d[42]), "+f"(d[43]), "+f"(d[44]), "+f"(d[45]), "+f"(d[46]), "+f"(d[47]),
        "+f"(d[48]), "+f"(d[49]), "+f"(d[50]), "+f"(d[51]), "+f"(d[52]), "+f"(d[53]), "+f"(d[54]), "+f"(d[55]),
        "+f"(d[56]), "+f"(d[57]), "+f"(d[58]), "+f"(d[59]), "+f"(d[60]), "+f"(d[61]), "+f"(d[62]), "+f"(d[63])
        : "l"(da), "l"(db), "r"(acc));
}

__device__ __forceinline__ void wgmma_n8_ta(float* d, uint64_t da, uint64_t db) {
    asm volatile("wgmma.mma_async.sync.aligned.m64n8k16.f32.bf16.bf16 {%0, %1, %2, %3}, %4, %5, 1, 1, 1, 1, 0;\n"
                 : "+f"(d[0]), "+f"(d[1]), "+f"(d[2]), "+f"(d[3]) : "l"(da), "l"(db));
}

#define PROF(slot, role)
#undef PROF_GT
#define PROF_GT(slot)

struct Params {
    const __nv_bfloat16* x;
    const __nv_bfloat16* w_r;
    const uint8_t *c_kv, *w_uk, *w_uv;
};
__device__ __forceinline__ void lsu_prefetch(const void* p) { asm volatile("prefetch.global.L2 [%0];" ::"l"(p) : "memory"); }

template <typename T>
__device__ __forceinline__ T* ptr_off(T* base, uint32_t off) {
    uint32_t lo, hi;
    asm("mov.b64 {%0, %1}, %2;" : "=r"(lo), "=r"(hi) : "l"(base));
    asm("add.cc.u32 %0, %0, %2;\naddc.u32 %1, %1, 0;" : "+r"(lo), "+r"(hi) : "r"(off));
    T* r;
    asm("mov.b64 %0, {%1, %2};" : "=l"(r) : "r"(lo), "r"(hi));
    return r;
}
__device__ __forceinline__ int kv_head(int pair) { return AMAP ? (pair & 15) >> 1 : pair >> 3; }
__device__ __forceinline__ int kv_tokens(int pair) { return AMAP ? (pair & 1) * 4 + (pair >> 4) : pair & 7; }
__device__ __forceinline__ int attn_rowblock(int pair, int seg) {
    int j = pair & 3, hl = pair >> 2;
    return ((hl & 1) ^ seg) ? j : 7 - j;
}
__device__ __forceinline__ int outproj_head(int i, int ib) {
    if (i < 16) return i;
    return 16 + 2 * (i & 7) + ((ib < 4) ^ ((i >> 3) & 1));
}

__device__ __forceinline__ void pin_value(uint32_t& v) { asm volatile("" : "+r"(v)); }
__device__ __forceinline__ void pin_value(int& v) { asm volatile("" : "+r"(v)); }
__device__ __forceinline__ void pin_value(const uint8_t*& v) { asm volatile("" : "+l"(v)); }

__device__ __forceinline__ void producer(const Params& P, uint32_t sb, int pair, int c,
                                         const CUtensorMap* m_ckv, const CUtensorMap* m_wu,
                                         const CUtensorMap* m_wq, const CUtensorMap* m_wo, const CUtensorMap* m_x,
                                         const CUtensorMap* m_out) {
    const int hl = pair >> 2;
    const int ibA = attn_rowblock(pair, 0), nA = 2 * ibA + 2;
    const int ib = (pair >> 1) & 7, mi = 2 * ib + c, nb = (pair >> 4) * 4 + (pair & 1) * 2;
    const bool leader = elect_one();
    uint32_t g = 4, tail = 0;
    if (leader) prefetch_map(m_wq);
    auto wait_released = [&](uint32_t need) {
#pragma unroll 1
        for (; tail <= need; tail++) mbar_wait(sb + BAR_EMPTY + (tail & 7) * 8, (tail >> 3) & 1);
    };
    auto wait_released_here = [&](uint32_t need) {
#pragma unroll 1
        for (; tail < need; tail++) mbar_wait(sb + BAR_EMPTY + (tail & 7) * 8, (tail >> 3) & 1);
        if (tail == need) mbar_wait(sb + BAR_EMPTYL + (need & 7) * 8, (need >> 3) & 1);
    };
    auto wait_released_peer = [&](uint32_t need) {
        if (tail == need) {
            uint32_t eb = sb + BAR_EMPTY + (need & 7) * 8, ep = (need >> 3) & 1;
            tail++;
            mbar_wait(eb, ep);
        }
    };
    auto full_bar = [&]() { return sb + BAR_FULL + (g & 7) * 8; };
    auto pin = [](auto&... v) { (pin_value(v), ...); };
#pragma unroll 1
    for (int rnd = 0; rnd < 2; rnd++) {
#pragma unroll 1
        for (int i = rnd ? 0 : 4; i < 16; i++) {
            int kb = i & 7, h2 = (kv_head(pair) + (i & 8) + rnd * 16) * 2, krow = kb * 64;
            uint32_t pg = sb + (i & 3) * (3 * PAGE), pb = pg + (1 + c) * PAGE, bar = full_bar();
            pin(kb, h2, krow, pg, pb, bar);
            const uint32_t need = g - 4 - (i < 2);
            wait_released_here(need);
            if (leader) {
                mbar_expect_tx(bar, 3 * PAGE);
                tma_3d(pg, m_wu, 0, krow, h2, bar);
            }
            wait_released_peer(need);
            if (leader) {
                tma_3d_mc(pb, m_ckv, 0, kv_tokens(pair) * 256 + c * 128, kb, bar);
                if (rnd == 1 && i == 3) asm volatile("red.relaxed.gpu.global.add.u32 [%0], 1;" ::"l"(ptr_off(g_sync.kvfree, hl * 32)) : "memory");
            }
            g++;
        }
        mbar_sleep(sb + BAR_DEP, 0);
        const uint8_t* xa = ptr_off(g_xn, ibA * (16 * 32768) + c * PAGE);
        const uint8_t* xb = ptr_off(g_xn, (7 - ibA) * (16 * 32768) + (1 - c) * PAGE);
#pragma unroll 1
        for (int kb = 0; kb < DM / 64; kb++) {
            uint32_t pg = sb + (kb & 3) * (3 * PAGE), pw = pg + 2 * PAGE + c * 8192, bar = full_bar(), p2 = pg + PAGE;
            int krow = kb * 64;
            pin(pg, pw, p2, bar, krow);
            wait_released_here(g - 4);
            if (leader) {
                mbar_expect_tx(bar, 3 * PAGE);
                bulk_load(pg, xa, PAGE, bar);
            }
            wait_released_peer(g - 4);
            if (leader) {
                tma_3d_mc(pw, m_wq, 0, krow, (rnd * 16 + hl) * 2 + c, bar);
                bulk_load(p2, xb, PAGE, bar);
            }
            g++;
            xa += 32768;
            xb += 32768;
        }
        mbar_sleep(sb + BAR_DEP + 8 + rnd * 16, 0);
        if (rnd == 1 && leader) prefetch_map(m_wo);
        uint32_t pg = sb + c * PAGE;
#pragma unroll 1
        for (int j = 0; j < 36; j++) {
            const bool isk = j == 0 || ((j & 1) && j != 35);
            const int t = isk ? (j + 1) >> 1 : (j - 1) >> 1;
            const uint8_t* src = ptr_off(g_kv, (hl * 16 + (t >= nA ? t - nA : t)) * 65536 + (isk ? 0 : 32768) + c * PAGE);
            uint32_t bar = full_bar(), need = g - 6 + (j < 2) + (j < 5);
            pin(src, bar, need);
            wait_released(need);
            if (leader) {
                mbar_expect_tx(bar, 2 * PAGE);
                bulk_load_mc(pg, src, PAGE, bar);
            }
            g++;
            if (rnd == 0 && j >= 22 && j < 34) {
                const int cta = pair * 2 + c, i = j - 22;
                const uint32_t l = (threadIdx.x & 31) * 128;
                if (i < 8) lsu_prefetch(ptr_off(i & 1 ? P.w_uv : P.w_uk, cta * 32768 + (i >> 1) * 8192 + 4096 + l));
                else lsu_prefetch(ptr_off(P.c_kv, cta * 16384 + (i - 8) * 4096 + l));
            }
            pg = pg >= sb + SM_REGION - 2 * PAGE ? pg - (SM_REGION - 2 * PAGE) : pg + 2 * PAGE;
        }
    }
    uint32_t pg = sb;
#pragma unroll 1
    for (int i = 0; i < 64; i++) {
        if (i == 32 && leader) { prefetch_map(m_x); prefetch_map(m_out); }
        if ((i & 15) == 0 && i != 16) mbar_sleep(sb + BAR_DEP + 32 + (i >> 1) - (i ? 8 : 0), 0);
        const int kb = outproj_head(i >> 1, ib) * 2 + (i & 1);
        const uint8_t* src = ptr_off(g_ctx, (mi * 64 + kb) * PAGE);
        uint32_t bar = full_bar(), pw = pg + PAGE + c * 8192;
        int krow = kb * 64;
        pin(src, bar, pw, krow);
        wait_released_here(g - 6);
        if (leader) {
            mbar_expect_tx(bar, 2 * PAGE);
            bulk_load(pg, src, PAGE, bar);
        }
        wait_released_peer(g - 6);
        if (leader) tma_3d_mc(pw, m_wo, 0, krow, nb + c, bar);
        g++;
        pg = pg == sb + SM_REGION - 2 * PAGE ? sb : pg + 2 * PAGE;
    }
    const uint32_t bar = full_bar();
    wait_released(g - 6);
    if (leader) {
        mbar_expect_tx(bar, 2 * PAGE);
        tma_3d(pg, m_x, 0, mi * 128, nb, bar);
        tma_3d(pg + PAGE, m_x, 0, mi * 128 + 64, nb, bar);
    }
}

__device__ __forceinline__ uint32_t xn_block(int row64, int kb) {
    return (((row64 >> 2) * 16 + kb) * 4 + ((row64 & 1) * 2 + (((row64 >> 1) & 1) ^ 1))) * 8192;
}
__device__ __forceinline__ uint32_t image_offset(int row, int ch) {
    return xn_block(row >> 6, ch >> 3) + (row & 63) * 128 + (((ch & 7) ^ (row & 7)) << 4);
}
__device__ __forceinline__ uint32_t bf2_sub(uint32_t a, uint32_t b) {
    uint32_t r;
    asm("sub.rn.bf16x2 %0, %1, %2;" : "=r"(r) : "r"(a), "r"(b));
    return r;
}
__device__ __forceinline__ uint32_t bf2_fma(uint32_t a, uint32_t b, uint32_t c) {
    uint32_t r;
    asm("fma.rn.bf16x2 %0, %1, %2, %3;" : "=r"(r) : "r"(a), "r"(b), "r"(c));
    return r;
}
template <int N0, int N>
__device__ __forceinline__ void ln_sums(const uint32_t (&u)[N], float& sum, float& sq) {
    float s0 = 0.f, s1 = 0.f, q0 = 0.f, q1 = 0.f;
#pragma unroll
    for (int k = N0; k < N0 + 16; k++) {
        const float a = bf_lo(u[k]), b = bf_hi(u[k]);
        s0 += a; s1 += b;
        q0 = fmaf(a, a, q0); q1 = fmaf(b, b, q1);
    }
    sum = s0 + s1;
    sq = q0 + q1;
}
__device__ __forceinline__ void ln_finish(float sum, float sq, uint32_t& mean2, uint32_t& rhi2, uint32_t& rlo2) {
    const float ms = sum * (1.0f / DM);
    const float var = fmaxf(fmaf(-ms, ms, sq * (1.0f / DM)), 0.f);
    const float rden = rcp_approx(bf_round(sqrt_approx(bf_round(bf_round(var) + 1e-5f))));
    const float rhi = bf_round(rden);
    mean2 = pack_bf16(ms, ms);
    rhi2 = pack_bf16(rhi, rhi);
    rlo2 = pack_bf16(rden - rhi, rden - rhi);
}
template <int N0, int N>
__device__ __forceinline__ void ln_apply(uint32_t (&u)[N], uint32_t mean2, uint32_t rhi2, uint32_t rlo2, uint8_t* dst) {
#pragma unroll
    for (int i = 0; i < 4; i++) {
        uint32_t o[4];
#pragma unroll
        for (int k = 0; k < 4; k++) {
            const uint32_t d = bf2_sub(u[N0 + 4 * i + k], mean2);
            o[k] = bf2_fma(d, rhi2, bf2_mul(d, rlo2));
        }
#pragma unroll
        for (int k = 0; k < 4; k++) u[N0 + 4 * i + k] = o[k];
        __stcg(reinterpret_cast<uint4*>(dst + i * 131072), make_uint4(o[0], o[1], o[2], o[3]));
    }
}
__device__ __forceinline__ int query_rowblock(int pair, int c, int w, int seg) {
    const int qA = (w ? 0 : 2) + c;
    return 4 * attn_rowblock(pair, seg) + (seg ? 3 - qA : qA);
}

__device__ __forceinline__ void fetch_helper(const Params& P, uint32_t sb, int w, int lane, int pair, int c) {
    const uint32_t page = sb + SM_REGION + w * PAGE + lane * 16;
    mbar_sleep(sb + BAR_FULL + 5 * 8, 0);
#pragma unroll 1
    for (int i = 0; i < 2; i++) {
        lsu_prefetch(ptr_off(w ? P.w_uv : P.w_uk, ((pair * 2 + c) * 4 + i * 2 + (lane >> 4)) * 8192 + 2048 + (lane & 15) * 128));
        __nanosleep(300);
    }
    const unsigned e1 = __ldcg(&g_sync.done) / NCTA + 1;
#pragma unroll 1
    for (int e = 1; e <= 7; e += 2) mbar_sleep(sb + BAR_DONE + 8, (e >> 1) & 1);
    const int rb = ((pair >> 1) & 7) * 4 + c * 2 + w, kb0 = (pair >> 4) * 4 + (pair & 1) * 2;
    const uint8_t* src = ptr_off(g_xn, xn_block(rb, kb0) + lane * 16);
#pragma unroll 1
    for (int i = 0; i < 32; i += 4) {
#pragma unroll
        for (int k = 0; k < 4; k++) cp_async16(page + (i + k) * 512, src + (i + k) * 512 + (i >> 4) * (32768 - 8192));
        __nanosleep(200);
    }
    wait_counter(&g_sync.ffn_done, e1);
    const int r = __ldcg(ptr_off(g_sel, (lane >> 4) * 4)) - rb * 64, ch = lane & 15;
    const uint4 t = __ldcg(ptr_off(g_routed, ((lane >> 4) * 128 + kb0 * 8 + ch) * 16));
    asm volatile("cp.async.wait_all;" ::: "memory");
    __syncwarp();
    if (r >= 0 && r < 64)
        sts128(sb + SM_REGION + w * PAGE + (ch >> 3) * 8192 + r * 128 + (((ch & 7) ^ (r & 7)) << 4), t.x, t.y, t.z, t.w);
    __syncwarp();
    if (lane == 0) mbar_arrive(sb + BAR_G + w * 8);
    PROF(20, 2);
}

__device__ __noinline__ void sync_helper(uint32_t sb, int lane, int pair, int c) {
    const unsigned e1 = __ldcg(&g_sync.done) / NCTA + 1;
    const int ib = (pair >> 1) & 7;
    int e = 0, b = 0;
#pragma unroll 1
    for (uint32_t n = 0; (e < 9 || b < 7) && n < SPIN_LIMIT; n++) {
        if (e < 9 && __all_sync(~0u, mbar_test(sb + BAR_DONE + (e & 1) * 8, (e >> 1) & 1))) {
            const int rnd = e > 4, ev = (e - 1) & 3;
            unsigned* flag = e == 0 ? &g_sync.ln
                           : ev < 2 ? ptr_off(g_sync.kv, (rnd * 16 + kv_head(pair) + 8 * ev) * 32)
                                    : ptr_off(g_sync.ctx, (query_rowblock(pair, c, lane & 1, ev & 1) * NH + rnd * 16 + (pair >> 2)) * 4);
            asm volatile("fence.proxy.async.global;\nfence.release.gpu;" ::: "memory");
            if (lane < ((e == 0 || ev < 2) ? 1 : 2)) asm volatile("red.relaxed.gpu.global.add.u32 [%0], 1;" ::"l"(flag) : "memory");
            PROF(10 + e, 2);
            e++;
        }
        if (b < 7 && e > 0 && (b < 4 || (n & POLL_MASK) == 0)) {
            const int i = b == 4 ? lane >> 1 : 8 * b - 24 + ((lane >> 1) & 7);
            const unsigned* cnt = b == 0 ? &g_sync.ln
                                : b == 2 ? ptr_off(g_sync.kvfree, (kv_head(pair) + 8 * (lane & 1)) * 32)
                                : b < 4 ? ptr_off(g_sync.kv, ((b >> 1) * 16 + (pair >> 2)) * 32)
                                        : ptr_off(g_sync.ctx, ((4 * ib + 2 * c + (lane & 1)) * NH + outproj_head(i & 31, ib)) * 4);
            if (__all_sync(~0u, (int)(ld_relaxed(cnt) - e1 * (b == 0 ? NMAIN : b == 2 ? 8 : b < 4 ? 16 : 1)) >= 0)) {
                asm volatile("fence.acquire.gpu;\nfence.proxy.async.global;" ::: "memory");
                __syncwarp();
                if (lane == 0) mbar_arrive(sb + BAR_DEP + b * 8);
                PROF(1 + b, 2);
                b++;
            }
        }
        __nanosleep(150);
    }
}

__device__ __forceinline__ unsigned long long block_max_key(unsigned long long k, unsigned long long* red, int tid) {
#pragma unroll
    for (int o = 16; o; o >>= 1) {
        unsigned long long t = __shfl_xor_sync(~0u, k, o);
        k = t > k ? t : k;
    }
    bar_sync(1, 256);
    if ((tid & 31) == 0) red[tid >> 5] = k;
    bar_sync(1, 256);
    k = red[0];
#pragma unroll
    for (int i = 1; i < 8; i++) k = red[i] > k ? red[i] : k;
    return k;
}

constexpr int FS = FF / 4;
constexpr int FSTAGE = 32768, FNST = 6;
constexpr int FN1 = 2 * (DM / 16), FN2 = FS / 16;

__device__ __forceinline__ void ffn_producer(uint32_t sb, int s, const CUtensorMap* m_gate, const CUtensorMap* m_up,
                                             const CUtensorMap* m_down) {
    const uint64_t pol = policy_evict_first();
    int slot = 0, ph = 1;
#pragma unroll 1
    for (int st = 0; st < FN1 + FN2; st++) {
        mbar_sleep(sb + BAR_EMPTY + slot * 8, ph);
        const uint32_t bar = sb + BAR_FULL + slot * 8;
        const bool up = st < FN1;
        mbar_expect_tx(bar, up ? FS * 32 : DM * 32);
        tma_3d_hint(sb + slot * FSTAGE, up ? ((st & 1) ? m_up : m_gate) : m_down, 0,
                    up ? (st >> 1) * 16 : s * FS + (st - FN1) * 16, up ? s * (FS / 64) : 0, bar, pol);
        if (++slot == FNST) { slot = 0; ph ^= 1; }
    }
}

__device__ __forceinline__ void ffn_cta(uint8_t* smem, uint32_t sb, int s, unsigned epoch, const __nv_bfloat16* w_r) {
    const int tid = threadIdx.x, lane = tid & 31;
    const int warp = __shfl_sync(~0u, tid >> 5, 0), w = warp >> 2;
    constexpr uint32_t XB = FNST * FSTAGE, HB = XB + 16384, AUX = HB + 14336;
    unsigned long long* red = reinterpret_cast<unsigned long long*>(smem + AUX);
    unsigned* flag = reinterpret_cast<unsigned*>(smem + AUX + 128);
    const unsigned e1 = epoch + 1;
    for (int i = tid; i < (16384 + 14336) / 16; i += 256) reinterpret_cast<uint4*>(smem + XB)[i] = make_uint4(0, 0, 0, 0);
    {
        float wf[32];
#pragma unroll
        for (int i = 0; i < 4; i++) {
            const uint4 t = __ldg(reinterpret_cast<const uint4*>(w_r) + lane + 32 * i);
            const uint32_t tu[4] = {t.x, t.y, t.z, t.w};
#pragma unroll
            for (int k = 0; k < 4; k++) { wf[8 * i + 2 * k] = bf_lo(tu[k]); wf[8 * i + 2 * k + 1] = bf_hi(tu[k]); }
        }
        if (tid == 0) wait_counter(&g_sync.ln, e1 * NMAIN);
        bar_sync(1, 256);
#pragma unroll 1
        for (int r0 = s * (SEQ / 4) + warp * (SEQ / 32); r0 < s * (SEQ / 4) + (warp + 1) * (SEQ / 32); r0 += 4) {
            uint4 t[4][4];
#pragma unroll
            for (int r = 0; r < 4; r++)
#pragma unroll
                for (int i = 0; i < 4; i++) t[r][i] = __ldcg(reinterpret_cast<const uint4*>(g_xn + image_offset(r0 + r, lane) + i * 131072));
            float acc[4];
#pragma unroll
            for (int r = 0; r < 4; r++) {
                float a = 0.f, b = 0.f;
#pragma unroll
                for (int i = 0; i < 4; i++) {
                    const uint32_t tu[4] = {t[r][i].x, t[r][i].y, t[r][i].z, t[r][i].w};
#pragma unroll
                    for (int k = 0; k < 4; k++) {
                        a = fmaf(bf_lo(tu[k]), wf[8 * i + 2 * k], a);
                        b = fmaf(bf_hi(tu[k]), wf[8 * i + 2 * k + 1], b);
                    }
                }
                acc[r] = a + b;
            }
#pragma unroll
            for (int o = 16; o; o >>= 1)
#pragma unroll
                for (int r = 0; r < 4; r++) acc[r] += __shfl_xor_sync(~0u, acc[r], o);
            if (lane < 4) __stcg(&g_r[r0 + lane], bf_round(lane == 0 ? acc[0] : lane == 1 ? acc[1] : lane == 2 ? acc[2] : acc[3]));
        }
        __threadfence();
        bar_sync(1, 256);
        if (tid == 0) {
            red_release(&g_sync.router);
            wait_counter(&g_sync.router, e1 * 4);
        }
        bar_sync(1, 256);
    }
    unsigned long long keys[8];
    unsigned long long best = 0;
#pragma unroll
    for (int i = 0; i < 8; i++) {
        int idx = tid + 256 * i;
        uint32_t b = __float_as_uint(__ldcg(&g_r[idx]) + 0.0f);
        b = (b & 0x80000000u) ? ~b : (b | 0x80000000u);
        keys[i] = ((unsigned long long)b << 32) | (unsigned)(SEQ - 1 - idx);
        best = keys[i] > best ? keys[i] : best;
    }
    const unsigned long long k0 = block_max_key(best, red, tid);
    best = 0;
#pragma unroll
    for (int i = 0; i < 8; i++) best = (keys[i] != k0 && keys[i] > best) ? keys[i] : best;
    const unsigned long long k1 = block_max_key(best, red, tid);
    const int row = SEQ - 1 - (int)((w ? k1 : k0) & 0xffffffffu);
    const int ch = tid & 127;
    const uint4 xrow = __ldcg(reinterpret_cast<const uint4*>(g_xn + image_offset(row, ch)));
    *reinterpret_cast<uint4*>(smem + XB + (ch >> 3) * 1024 + w * 128 + (((ch & 7) ^ w) << 4)) = xrow;
    fence_async_smem();
    bar_sync(1, 256);
    PROF(20, tid >> 7);
    int slot = 0, ph = 0, prev = 0;
    auto next_stage = [&](bool has_prev) {
        wg_commit();
        wg_wait<1>();
        if (has_prev && lane < 2) mbar_arrive(sb + BAR_EMPTY + prev * 8);
        prev = slot;
        if (++slot == FNST) { slot = 0; ph ^= 1; }
    };
    {
        float ag[28], au[28];
#pragma unroll
        for (int i = 0; i < 28; i++) ag[i] = au[i] = 0.f;
#pragma unroll 1
        for (int ks = 0; ks < DM / 16; ks++) {
            const uint64_t db = make_desc(sb + XB + (ks >> 2) * 1024 + (ks & 3) * 32, 16);
            mbar_wait(sb + BAR_FULL + slot * 8, ph);
            uint64_t da = make_desc(sb + slot * FSTAGE + w * (7 * 2048), 16);
            wg_fence();
#pragma unroll
            for (int b = 0; b < 7; b++) wgmma_n8_ta(ag + 4 * b, da + b * 128, db);
            next_stage(ks > 0);
            mbar_wait(sb + BAR_FULL + slot * 8, ph);
            da = make_desc(sb + slot * FSTAGE + w * (7 * 2048), 16);
            wg_fence();
#pragma unroll
            for (int b = 0; b < 7; b++) wgmma_n8_ta(au + 4 * b, da + b * 128, db);
            next_stage(true);
        }
        wg_wait<0>();
        reg_fence(ag);
        reg_fence(au);
        if ((lane & 3) == 0) {
#pragma unroll
            for (int i = 0; i < 28; i++) {
                const int f = (warp & 3) * 16 + (lane >> 2) + (i & 2) * 4, tok = i & 1;
                const float h = bf_round(silu_f(bf_round(ag[i]))) * bf_round(au[i]);
                *reinterpret_cast<__nv_bfloat16*>(smem + HB + (w * 7 + (i >> 2)) * 1024 + tok * 128 + (((f >> 3) ^ tok) << 4) + (f & 7) * 2) =
                    __float2bfloat16_rn(h);
            }
        }
    }
    fence_async_smem();
    bar_sync(1, 256);
    PROF(21, tid >> 7);
    {
        float ay[32];
#pragma unroll
        for (int i = 0; i < 32; i++) ay[i] = 0.f;
#pragma unroll 1
        for (int ks = 0; ks < FN2; ks++) {
            const uint64_t db = make_desc(sb + HB + (ks >> 2) * 1024 + (ks & 3) * 32, 16);
            mbar_wait(sb + BAR_FULL + slot * 8, ph);
            const uint64_t da = make_desc(sb + slot * FSTAGE + w * (8 * 2048), 16);
            wg_fence();
#pragma unroll
            for (int b = 0; b < 8; b++) wgmma_n8_ta(ay + 4 * b, da + b * 128, db);
            next_stage(true);
        }
        wg_wait<0>();
        reg_fence(ay);
        if ((lane & 3) == 0) {
#pragma unroll
            for (int i = 0; i < 32; i++)
                g_ypart[(s * 2 + (i & 1)) * DM + (w * 8 + (i >> 2)) * 64 + (warp & 3) * 16 + (lane >> 2) + (i & 2) * 4] = ay[i];
        }
    }
    PROF(23, tid >> 7);
    __threadfence();
    bar_sync(1, 256);
    if (tid == 0) {
        *flag = atomicAdd(&g_sync.ffn_ticket, 1u) == epoch * 4 + 3;
        __threadfence();
    }
    bar_sync(1, 256);
    if (*flag) {
        const float sg = bf_round(__fdividef(1.0f, 1.0f + __expf(-__ldcg(&g_r[row]))));
        const uint32_t xu[4] = {xrow.x, xrow.y, xrow.z, xrow.w};
        uint32_t o[4];
#pragma unroll
        for (int k = 0; k < 4; k++) {
            float y0 = 0.f, y1 = 0.f;
#pragma unroll
            for (int q = 0; q < 4; q++) {
                const float2 y = __ldcg(reinterpret_cast<const float2*>(&g_ypart[(q * 2 + w) * DM + ch * 8 + 2 * k]));
                y0 += y.x; y1 += y.y;
            }
            o[k] = pack_bf16(bf_lo(xu[k]) + bf_round(bf_round(y0) * sg), bf_hi(xu[k]) + bf_round(bf_round(y1) * sg));
        }
        g_routed[w * 128 + ch] = make_uint4(o[0], o[1], o[2], o[3]);
        if (ch == 0) g_sel[w] = row;
        bar_sync(1, 256);
        if (tid == 0) red_release(&g_sync.ffn_done);
    }
}

__device__ __forceinline__ uint32_t slab_addr(uint32_t stg, int lane, int s) {
    const int row = ((lane >> 3) & 1) * 8 + (lane & 7);
    const int chunk = 2 * (s & 3) + (lane >> 4);
    return stg + row * 128 + (s >> 2) * 8192 + ((chunk ^ (lane & 7)) << 4);
}

constexpr float SM_SCALE = 0.08838834764831845f * 1.4426950408889634f;
constexpr float SUM_HI = 1048576.f, SUM_LO = 1.0f / 1048576.f;

template <int I0, int I1, int J0>
__device__ __forceinline__ void mask_range(float (&S)[64], float limf) {
#pragma unroll
    for (int i = I0; i < I1; i++) {
        const int j = i >> 2;
        float t;
        asm("add.sat.f32 %0, %1, %2;" : "=f"(t) : "f"((float)(32 * (j >> 2) + 2 * (j & 3) + (i & 1) - (i & 2) * 4)), "f"(-limf));
        S[4 * J0 + i] = fmaf(t, -1e30f, S[4 * J0 + i]);
    }
}
template <int J0>
__device__ __forceinline__ void mask_half(float (&S)[64], float limf, int v) {
    asm volatile("" : "+f"(limf));
    if (v < 2) {
        mask_range<0, 16, J0>(S, limf);
#pragma unroll
        for (int i = 16; i < 32; i++) S[4 * J0 + i] = -1e30f;
    } else {
        mask_range<16, 32, J0>(S, limf);
    }
}
__device__ __forceinline__ void issue_qk(float (&S)[64], const uint32_t (&Q)[32], uint32_t d0) {
#pragma unroll
    for (int s = 0; s < 8; s++)
        wgmma_n128_rs<1>(S, Q[4 * s], Q[4 * s + 1], Q[4 * s + 2], Q[4 * s + 3], d0 + s * 128, s > 0);
}
template <int H>
__device__ __forceinline__ void issue_pv(float (&O)[64], const uint32_t (&Pm)[32], uint32_t d0, int acc) {
#pragma unroll
    for (int s = 4 * H; s < 4 * H + 4; s++)
        wgmma_n128_rs<0>(O, Pm[4 * s], Pm[4 * s + 1], Pm[4 * s + 2], Pm[4 * s + 3], d0 + H * (PAGE >> 4) + (s & 3) * 2, s > 0 ? 1 : acc);
}
template <int J0, int J1>
__device__ __forceinline__ void exp_groups(const float (&S)[64], uint32_t (&Pm)[32], float (&sum)[NSUM]) {
#pragma unroll
    for (int i = 2 * J0; i < 2 * J1; i++) asm volatile("" : "+r"(Pm[i])::"memory");
#pragma unroll
    for (int j = J0; j < J1; j++) {
        const float e0 = ex2(S[4 * j]), e1 = ex2(S[4 * j + 1]), e2 = ex2(S[4 * j + 2]), e3 = ex2(S[4 * j + 3]);
        if (NSUM == 4) {
            sum[0] = j ? sum[0] + e0 : e0; sum[2] = j ? sum[2] + e1 : e1; sum[1] = j ? sum[1] + e2 : e2; sum[3] = j ? sum[3] + e3 : e3;
        } else {
            sum[0] = (j ? sum[0] + e0 : e0) + e1; sum[1] = (j ? sum[1] + e2 : e2) + e3;
        }
        Pm[2 * j] = pack_bf16(e0, e1);
        Pm[2 * j + 1] = pack_bf16(e2, e3);
    }
}
__device__ __forceinline__ void shift_rows(float (&S)[64], float d0, float d1) {
#pragma unroll
    for (int j = 0; j < 16; j++) {
        S[4 * j] -= d0; S[4 * j + 1] -= d0; S[4 * j + 2] -= d1; S[4 * j + 3] -= d1;
    }
}
__device__ constexpr int chunk_src(int i) { return 4 * (4 * (i >> 3) + (i & 3)) + 2 * ((i >> 2) & 1); }
enum : uint32_t { CTL_FIRST = 1, CTL_SWITCH = 2, CTL_LAST = 4, CTL_HALF = 128, CTL_MASKHI = 256, CTL_WOUT = 512, CTL_PVHALF = 1024, CTL_PVACC = 16384,
                  CTL_SHIFT = 32768 };
__device__ __forceinline__ float quad_sum(float v) {
    v += __shfl_xor_sync(~0u, v, 1);
    return v + __shfl_xor_sync(~0u, v, 2);
}

__device__ __forceinline__ void store_part(uint8_t* base, uint32_t row_bits, int p, const uint32_t (&pk)[64]) {
    asm volatile("{\n.reg .b64 d0, d1;\nxor.b64 d0, %0, %1;\nxor.b64 d1, d0, 64;\n"
                 "TS: .branchtargets P0, P1, P2, P3, P4, P5, P6, P7;\n"
                 "brx.idx.uni %2, TS;\n"
                 "P0:\n st.global.cg.v4.u32 [d0 + 0], {%3, %4, %5, %6};\n st.global.cg.v4.u32 [d1 + 0], {%11, %12, %13, %14};\n bra.uni DONE;\n"
                 "P1:\n st.global.cg.v4.u32 [d0 + 0], {%7, %8, %9, %10};\n st.global.cg.v4.u32 [d1 + 0], {%15, %16, %17, %18};\n bra.uni DONE;\n"
                 "P2:\n st.global.cg.v4.u32 [d0 + 16384], {%19, %20, %21, %22};\n st.global.cg.v4.u32 [d1 + 16384], {%27, %28, %29, %30};\n bra.uni DONE;\n"
                 "P3:\n st.global.cg.v4.u32 [d0 + 16384], {%23, %24, %25, %26};\n st.global.cg.v4.u32 [d1 + 16384], {%31, %32, %33, %34};\n bra.uni DONE;\n"
                 "P4:\n st.global.cg.v4.u32 [d0 + 65536], {%35, %36, %37, %38};\n st.global.cg.v4.u32 [d1 + 65536], {%43, %44, %45, %46};\n bra.uni DONE;\n"
                 "P5:\n st.global.cg.v4.u32 [d0 + 65536], {%39, %40, %41, %42};\n st.global.cg.v4.u32 [d1 + 65536], {%47, %48, %49, %50};\n bra.uni DONE;\n"
                 "P6:\n st.global.cg.v4.u32 [d0 + 81920], {%51, %52, %53, %54};\n st.global.cg.v4.u32 [d1 + 81920], {%59, %60, %61, %62};\n bra.uni DONE;\n"
                 "P7:\n st.global.cg.v4.u32 [d0 + 81920], {%55, %56, %57, %58};\n st.global.cg.v4.u32 [d1 + 81920], {%63, %64, %65, %66};\n bra.uni DONE;\n"
                 "DONE:\n}\n"
                 ::"l"(base), "l"((uint64_t)((p & 1) ? row_bits : 0)), "r"(p), "r"(pk[0]), "r"(pk[1]), "r"(pk[2]), "r"(pk[3]), "r"(pk[4]), "r"(pk[5]), "r"(pk[6]), "r"(pk[7]), "r"(pk[8]), "r"(pk[9]), "r"(pk[10]), "r"(pk[11]), "r"(pk[12]), "r"(pk[13]), "r"(pk[14]), "r"(pk[15]), "r"(pk[16]), "r"(pk[17]), "r"(pk[18]), "r"(pk[19]), "r"(pk[20]), "r"(pk[21]), "r"(pk[22]), "r"(pk[23]), "r"(pk[24]), "r"(pk[25]), "r"(pk[26]), "r"(pk[27]), "r"(pk[28]), "r"(pk[29]), "r"(pk[30]), "r"(pk[31]), "r"(pk[32]), "r"(pk[33]), "r"(pk[34]), "r"(pk[35]), "r"(pk[36]), "r"(pk[37]), "r"(pk[38]), "r"(pk[39]), "r"(pk[40]), "r"(pk[41]), "r"(pk[42]), "r"(pk[43]), "r"(pk[44]), "r"(pk[45]), "r"(pk[46]), "r"(pk[47]), "r"(pk[48]), "r"(pk[49]), "r"(pk[50]), "r"(pk[51]), "r"(pk[52]), "r"(pk[53]), "r"(pk[54]), "r"(pk[55]), "r"(pk[56]), "r"(pk[57]), "r"(pk[58]), "r"(pk[59]), "r"(pk[60]), "r"(pk[61]), "r"(pk[62]), "r"(pk[63])
                 : "memory");
}

__device__ __forceinline__ void consumer(uint32_t sb, int pair, int c, const CUtensorMap* m_out, const uint8_t* x) {
    const int tid = threadIdx.x;
    const int warp = __shfl_sync(~0u, tid >> 5, 0);
    const int w = warp >> 2, v = warp & 3, lane = tid & 31;

    const uint32_t empty_rel = lane == 2 ? mapa(sb + BAR_EMPTYL, c) : mapa(sb + BAR_EMPTY, lane & 1);
    auto release = [&](uint32_t grp) {
        if (lane < 3) mbar_arrive_cluster(empty_rel + (grp & 7) * 8);
    };
    auto wait_full = [&](uint32_t grp) { mbar_wait(sb + BAR_FULL + (grp & 7) * 8, (grp >> 3) & 1); };

    uint32_t g = 0;
    const uint32_t stg = sb + SM_REGION + w * PAGE + v * 2048;
    const uint32_t chunk0 = (lane >> 2) * 128 + (((lane & 3) ^ (lane >> 2)) << 4);
    uint32_t ndone = 0;
    auto mark_done = [&]() {
        __syncwarp();
        if (lane == 0) mbar_arrive(sb + BAR_DONE + (ndone & 1) * 8);
        ndone++;
    };
    auto ctx_dst = [&](int rnd, int seg) {
        const int rb = query_rowblock(pair, c, w, seg);
        return ptr_off(g_ctx, ((rb >> 1) * 64 + (rnd * 16 + (pair >> 2)) * 2) * PAGE + (rb & 1) * 8192 + v * 2048);
    };

    uint32_t ctl_tab;
    {
        const int t = lane, firstB = 2 * attn_rowblock(pair, 0) + 2 - w;
        auto is_half = [&](int u) { return (u == firstB - 1 || u == 16) && c == (u >= firstB); };
        auto block = [&](int u) { return u + (w == 1 && u >= firstB); };
        auto place = [](int j) { return ((j & 15) << 3) | ((j - (j * 43 >> 8) * 6) << 11); };
        const int jv = min(2 * block(t - 1) + 2, 35), jk = t == 17 ? jv : max(2 * block(t) - 1, 0);
        const bool diag = t == firstB - 1 || t == 16;
        ctl_tab = ((t == 0 || t == firstB) ? CTL_FIRST : 0) | (t == firstB ? CTL_SWITCH : 0) | (t == 17 ? CTL_LAST : 0) |
                  (diag ? (is_half(t) ? CTL_HALF : CTL_MASKHI) : 0) | (t == firstB + 1 ? CTL_WOUT : 0) |
                  (is_half(t - 1) ? CTL_PVHALF : 0) | ((t == 1 || t == firstB + 1) ? 0 : CTL_PVACC) |
                  place(jk) | ((place(jv) | (t ? 3 : 0)) << 16);
    }

    uint32_t pk[64];
#pragma unroll
    for (int i = 0; i < 64; i++) pk[i] = 0;
    uint8_t* pend = nullptr;
    uint32_t prow = 0x400;
    auto write_part = [&](int p) { store_part(pend, prow, p, pk); };
    if (w == 1) bar_arrive(2, 256);

    for (int item = 0; item < 6; item++) {
        if (item != 2 && item != 5) {
            constexpr int nk = DC / 64;
            float acc[128];
            auto issue_kblock = [&](int first_acc) {
                wait_full(g);
                const uint32_t pg = sb + (g & 3) * (3 * PAGE);
                const uint64_t da = make_desc(pg + w * 8192, 16), db = make_desc(pg + PAGE, 16);
                wg_fence();
                wgmma_n256_ss(acc, da, db, first_acc);
                wgmma_n256_ss(acc, da + 128, db + 2, 1);
                wgmma_n256_ss(acc, da + 256, db + 4, 1);
                wgmma_n256_ss(acc, da + 384, db + 6, 1);
                wg_commit();
                g++;
            };
            if (item == 0) PROF(17, w);
            issue_kblock(0);
            if (item == 0) PROF(1, w);
            if (item == 0 && w == 0) PROF_GT(1);
            const int nparts = item == 0 ? 0 : (item == 3 ? 4 : 8);
            const int ln_row = (pair * 2 + c) * 16 + warp * 2;
            if (item == 0) {
                const uint8_t* src = ptr_off(x, ln_row * (DM * 2) + lane * 16);
#pragma unroll
                for (int i = 0; i < 8; i++) {
                    const uint4 t = __ldcg(reinterpret_cast<const uint4*>(src + i * 512));
                    pk[4 * i] = t.x; pk[4 * i + 1] = t.y; pk[4 * i + 2] = t.z; pk[4 * i + 3] = t.w;
                }
            }
#pragma unroll 1
            for (int kb = 1; kb < nk; kb++) {
                if (kb == nk - 1 && w == 1) bar_sync(4, 256);
                issue_kblock(1);
                if (kb == nk - 1 && w == 0) bar_arrive(4, 256);
                wg_wait<1>();
                release(g - 2);
                if (kb <= nparts) {
                    if (item == 4 && kb == 1) mbar_wait(sb + BAR_DEP + 16, 0);
                    write_part(kb - 1);
                    if (kb == nk - 1) write_part(nk - 1);
                    if (kb == nparts || kb == nk - 1) mark_done();
                }
                if (g >= 4 && g <= 8) {
                    float s[2], q[2];
                    if (g == 4) {
                        ln_sums<0>(pk, s[0], q[0]);
                        pk[32] = __float_as_uint(s[0]); pk[33] = __float_as_uint(q[0]);
                    }
                    if (g == 5) {
                        ln_sums<16>(pk, s[1], q[1]);
                        pk[34] = __float_as_uint(s[1]); pk[35] = __float_as_uint(q[1]);
                    }
                    if (g == 6) {
#pragma unroll
                        for (int r = 0; r < 2; r++) { s[r] = __uint_as_float(pk[32 + 2 * r]); q[r] = __uint_as_float(pk[33 + 2 * r]); }
                        const bool hi = lane & 16, od = lane & 8;
                        float a = hi ? s[1] : s[0], b = hi ? q[1] : q[0];
                        a += __shfl_xor_sync(~0u, hi ? s[0] : s[1], 16);
                        b += __shfl_xor_sync(~0u, hi ? q[0] : q[1], 16);
                        float t = od ? b : a;
                        t += __shfl_xor_sync(~0u, od ? a : b, 8);
#pragma unroll
                        for (int o = 4; o; o >>= 1) t += __shfl_xor_sync(~0u, t, o);
#pragma unroll
                        for (int r = 0; r < 2; r++) {
                            s[r] = __shfl_sync(~0u, t, 16 * r);
                            q[r] = __shfl_sync(~0u, t, 16 * r + 8);
                        }
                        ln_finish(s[0], q[0], pk[36], pk[37], pk[38]);
                        ln_finish(s[1], q[1], pk[39], pk[40], pk[41]);
                    }
                    if (g == 7) ln_apply<0>(pk, pk[36], pk[37], pk[38], ptr_off(g_xn, image_offset(ln_row, lane)));
                    if (g == 8) {
                        ln_apply<16>(pk, pk[39], pk[40], pk[41], ptr_off(g_xn, image_offset(ln_row + 1, lane)));
                        mark_done();
                    }
                }
            }
            wg_wait<0>();
            reg_fence(acc);
            release(g - 1);
            PROF(2 + 2 * item, w);
            if (w == 0) PROF_GT(2 + 2 * item);
            const float ksc = (QSCALE || c) ? 1.0f : SM_SCALE;
#pragma unroll
            for (int i = 0; i < 64; i++) pk[i] = pack_bf16(acc[chunk_src(i)] * ksc, acc[chunk_src(i) + 1] * ksc);
            const uint32_t vrow = (v >> 1) * 32 + (lane >> 3) * 8 + (v & 1) * 4 + ((lane >> 2) & 1);
            pend = ptr_off(g_kv, ((kv_head(pair) + (item == 1 || item == 4 ? 8 : 0)) * 16 + kv_tokens(pair) * 2) * 65536 + w * 8192 +
                                     (c ? 32768 + vrow * 128 + (((lane & 3) ^ (vrow & 7)) << 4) : v * 2048 + chunk0));
            prow = c ? 0x120 : 0x400;
            PROF(3 + 2 * item, w);
            continue;
        }

        float O[64], S[64];
        auto issue_q = [&](int first_acc) {
            wait_full(g);
            const uint32_t pg = sb + (g & 3) * (3 * PAGE);
            const uint64_t da = make_desc(pg + w * 8192, 16), db = make_desc(pg + 2 * PAGE, 8192);
            const uint64_t dab = make_desc(pg + PAGE + (1 - w) * 8192, 16);
            wg_fence();
#pragma unroll
            for (int q = 0; q < 4; q++) wgmma_n128_ss(S, da + 2 * q, db + 128 * q, q ? 1 : first_acc);
            wg_commit();
#pragma unroll
            for (int q = 0; q < 4; q++) wgmma_n128_ss(O, dab + 2 * q, db + 128 * q, q ? 1 : first_acc);
            wg_commit();
            g++;
        };
        issue_q(0);
#pragma unroll 1
        for (int kb = 1; kb < DM / 64; kb++) {
            if (kb == DM / 64 - 2 && w == 1) bar_sync(4, 256);
            issue_q(1);
            if (kb == DM / 64 - 1 && w == 0) bar_arrive(4, 256);
            wg_wait<QSPLIT ? 2 : 1>();
            release(g - 2);
            if (kb <= 8) {
                write_part(kb - 1);
                if (kb == 8) mark_done();
            }
        }
        uint32_t Q[32], Pm[32];
#pragma unroll
        for (int i = 0; i < 32; i++) Pm[i] = PMINIT ? pk[i] : 0;
        float lim = (float)(v * 16 + (lane >> 2) - 8 * (lane & 3));
        float mc[2] = {0.f, 0.f}, l[2] = {0.f, 0.f}, scale[2] = {0.f, 0.f}, sum[NSUM];
        uint32_t ctl = __shfl_sync(~0u, ctl_tab, 0), nxt = __shfl_sync(~0u, ctl_tab, 1);
        int t = 1;
        asm volatile("" : "+f"(lim), "+f"(mc[0]), "+f"(mc[1]), "+f"(l[0]), "+f"(l[1]), "+r"(ctl), "+r"(nxt), "+r"(t));
        constexpr float qsc = QSCALE ? SM_SCALE : 1.0f;
        wg_wait<QSPLIT ? 1 : 0>();
        reg_fence(S);
#pragma unroll
        for (int i = 0; i < 32; i++) Q[i] = pack_bf16(S[2 * i] * qsc, S[2 * i + 1] * qsc);
        reg_fence(Q);
        wait_full(g);
        wg_wait<0>();
        reg_fence(O);
        release(g - 1);
        PROF(2 + 2 * item, w);
        if (w == 0) PROF_GT(2 + 2 * item);

        const uint32_t qaddr = QOPQ ? __shfl_sync(~0u, stg + lane * 16, lane) : stg + lane * 16;
        auto put_queries = [&](const float (&A)[64]) {
#pragma unroll
            for (int i = 0; i < 8; i++)
                sts128(qaddr + (i >> 2) * 8192 + (i & 3) * 512, pack_bf16(A[8 * i] * qsc, A[8 * i + 1] * qsc), pack_bf16(A[8 * i + 2] * qsc, A[8 * i + 3] * qsc),
                       pack_bf16(A[8 * i + 4] * qsc, A[8 * i + 5] * qsc), pack_bf16(A[8 * i + 6] * qsc, A[8 * i + 7] * qsc));
        };
        auto get_queries = [&](int i0, int i1) {
#pragma unroll
            for (int i = i0; i < i1; i++) lds128(qaddr + (i >> 2) * 8192 + (i & 3) * 512, Q[4 * i], Q[4 * i + 1], Q[4 * i + 2], Q[4 * i + 3]);
        };
        const uint32_t kdesc0 = (uint32_t)make_desc(sb, PAGE), vdesc0 = (uint32_t)make_desc(sb, 16);
        auto wait_block = [&](uint32_t word) { mbar_wait(sb + BAR_FULL + (word & 56), (word >> 6) & 1); };
        auto write_out = [&](auto early) {
            uint8_t* dst = ctx_dst(item == 5, 0);
            uint8_t* d[2] = {ptr_off(dst, chunk0), ptr_off(dst, chunk0 ^ 64)};
#pragma unroll
            for (int i = early.value ? 0 : WN; i < (early.value ? WN : 8); i++) {
                const float sc = scale[i & 1];
                uint32_t q[4];
#pragma unroll
                for (int k = 0; k < 4; k++) q[k] = pack_bf16(O[chunk_src(4 * i + k)] * sc, O[chunk_src(4 * i + k) + 1] * sc);
                if (WINP && early.value && i > 0) {
#pragma unroll
                    for (int k = 0; k < 4; k++) O[4 * (i - 1) + k] = __uint_as_float(q[k]);
                }
                __stcg(reinterpret_cast<uint4*>(d[(i >> 1) & 1] + (i >> 2) * PAGE + (i & 1) * 1024), make_uint4(q[0], q[1], q[2], q[3]));
            }
            if (early.value == (WN == 8)) mark_done();
        };
        put_queries(O);
        bar_sync(2 + w, 256);
        wg_fence();
        issue_qk(S, Q, kdesc0);
        wg_commit();
        wg_fence();
        wg_commit();
        wg_commit();
        bar_arrive(3 - w, 256);
        for (;;) {
            const bool kready = KTRY ? mbar_try(sb + BAR_FULL + (nxt & 56), (nxt >> 6) & 1) : true;
            if (!KTRY) wait_block(nxt);
            wg_wait<2>();
            reg_fence(S);
            if (ctl & (CTL_HALF | CTL_MASKHI | CTL_SHIFT)) {
                if (LQN < 8 && (nxt & CTL_SWITCH)) get_queries(LQN, 8);
                if (ctl & CTL_HALF) mask_half<0>(S, lim, v);
                if (ctl & CTL_MASKHI) mask_half<8>(S, lim, v);
                if (ctl & CTL_SHIFT) shift_rows(S, mc[0], mc[1]);
            }
            float early[4 * EARLY + 1];
#pragma unroll
            for (int j = 0; j < EARLY; j++) {
#pragma unroll
                for (int i = 4 * j; i < 4 * j + 4; i++) early[i] = ex2(S[i]);
                sum[0] = (j ? sum[0] + early[4 * j] : early[4 * j]) + early[4 * j + 1];
                sum[1] = (j ? sum[1] + early[4 * j + 2] : early[4 * j + 2]) + early[4 * j + 3];
            }
            const uint32_t tie = EARLY ? __float_as_uint(sum[0]) & __float_as_uint(sum[1]) & (ctl & 0x80000000u) : 0;
            if (lane < 3) mbar_arrive_cluster(empty_rel + tie + (ctl & 56));
            wg_wait<1>();
#pragma unroll
            for (int j = 0; j < EARLY; j++) {
                asm volatile("" : "+r"(Pm[2 * j]), "+r"(Pm[2 * j + 1])::"memory");
                Pm[2 * j] = pack_bf16(early[4 * j], early[4 * j + 1]);
                Pm[2 * j + 1] = pack_bf16(early[4 * j + 2], early[4 * j + 3]);
            }
            exp_groups<EARLY, 8>(S, Pm, sum);
            const bool half = ctl & CTL_HALF;
            if (!half) {
                wg_wait<0>();
                reg_fence(O);
                if (lane < ((ctl >> 16) & 3)) mbar_arrive_cluster(empty_rel + ((ctl >> 16) & 56));
                exp_groups<8, 16>(S, Pm, sum);
            } else {
                asm volatile("wgmma.wait_group.sync.aligned 0;\n" ::: "memory");
                reg_fence(O);
                if (lane < ((ctl >> 16) & 3)) asm volatile("mbarrier.arrive.shared::cluster.b64 _, [%0];\n" ::"r"(empty_rel + ((ctl >> 16) & 56)) : "memory");
            }
            if (NSUM == 4) { sum[0] += sum[2]; sum[1] += sum[3]; }
            const bool over = !(sum[0] + sum[1] <= SUM_HI);
            if (__any_sync(~0u, over || !kready) || (((ctl & CTL_FIRST) | (nxt & (CTL_SWITCH | CTL_LAST))) != 0)) {
                bool bad = __any_sync(~0u, over);
                if (KTRY && !kready) wait_block(nxt);
                const bool first = ctl & CTL_FIRST;
                if (first) {
                    uint32_t b0 = __ballot_sync(~0u, sum[0] >= SUM_LO), b1 = __ballot_sync(~0u, sum[1] >= SUM_LO);
                    b0 |= b0 >> 1; b1 |= b1 >> 1;
                    b0 |= b0 >> 2; b1 |= b1 >> 2;
                    bad |= (b0 & b1 & 0x11111111u) != 0x11111111u;
                }
                if (bad) {
                    if (half) {
#pragma unroll
                        for (int i = 32; i < 64; i++) S[i] = -INFINITY;
                    }
                    float d0 = fmaxf(S[0], S[1]), d1 = fmaxf(S[2], S[3]);
#pragma unroll
                    for (int j = 1; j < 16; j++) {
                        d0 = fmaxf(d0, fmaxf(S[4 * j], S[4 * j + 1]));
                        d1 = fmaxf(d1, fmaxf(S[4 * j + 2], S[4 * j + 3]));
                    }
                    d0 = fmaxf(d0, __shfl_xor_sync(~0u, d0, 1));
                    d1 = fmaxf(d1, __shfl_xor_sync(~0u, d1, 1));
                    d0 = fmaxf(d0, __shfl_xor_sync(~0u, d0, 2));
                    d1 = fmaxf(d1, __shfl_xor_sync(~0u, d1, 2));
                    if (!first) {
                        d0 = fmaxf(d0, 0.f);
                        d1 = fmaxf(d1, 0.f);
                        const float a0 = ex2(-d0), a1 = ex2(-d1);
#pragma unroll
                        for (int j = 0; j < 16; j++) {
                            O[4 * j] *= a0; O[4 * j + 1] *= a0; O[4 * j + 2] *= a1; O[4 * j + 3] *= a1;
                        }
                        l[0] *= a0; l[1] *= a1;
                    }
                    mc[0] += d0; mc[1] += d1;
                    ctl_tab |= CTL_SHIFT;
                    nxt |= CTL_SHIFT;
                    shift_rows(S, d0, d1);
                    exp_groups<0, 16>(S, Pm, sum);
                    if (NSUM == 4) { sum[0] += sum[2]; sum[1] += sum[3]; }
                }
                if (WN && (ctl & CTL_SWITCH)) write_out(std::true_type());
                if (nxt & CTL_LAST) break;
                if (nxt & CTL_SWITCH) {
                    get_queries(0, LQN);
                    nxt &= ~CTL_SHIFT;
                    ctl_tab &= ~CTL_SHIFT;
                }
            }
            ctl = nxt;
            bar_sync(2 + w, 256);
            wg_fence();
            issue_qk(S, Q, kdesc0 + (ctl & 0x3800));
            wg_commit();
            l[0] += sum[0]; l[1] += sum[1];
            nxt = __shfl_sync(~0u, ctl_tab, ++t);
            if (ctl & (CTL_SWITCH | CTL_WOUT)) {
                if (ctl & CTL_SWITCH) {
                    scale[0] = rcp_approx(quad_sum(l[0]));
                    scale[1] = rcp_approx(quad_sum(l[1]));
                    l[0] = l[1] = mc[0] = mc[1] = 0.f;
                    if (w == 1) { release((ctl >> 3) - 2); release((ctl >> 3) + 1); }
                } else {
                    write_out(std::false_type());
                }
            }
            wait_block(ctl >> 16);
            const uint32_t vdesc = vdesc0 + ((ctl >> 16) & 0x3800);
            if (!(ctl & CTL_PVHALF)) {
                wg_fence();
                issue_pv<0>(O, Pm, vdesc, ctl & CTL_PVACC);
                wg_commit();
                issue_pv<1>(O, Pm, vdesc, 1);
                wg_commit();
            } else {
                wg_fence();
                issue_pv<0>(O, Pm, vdesc, ctl & CTL_PVACC);
                wg_commit();
                wg_commit();
            }
            bar_arrive(3 - w, 256);
        }
        g += 36;
        if (w == 0) release(g - 3);
        if (WN < 8 && (nxt & CTL_WOUT)) write_out(std::false_type());
        const uint32_t vdesc = vdesc0 + (nxt & 0x3800);
        if (nxt & CTL_PVHALF) {
            wg_fence();
            issue_pv<0>(O, Pm, vdesc, nxt & CTL_PVACC);
            wg_commit();
        } else {
            wg_fence();
            issue_pv<0>(O, Pm, vdesc, nxt & CTL_PVACC);
            issue_pv<1>(O, Pm, vdesc, 1);
            wg_commit();
        }
        l[0] += sum[0]; l[1] += sum[1];
        ctl_tab = (ctl_tab & ~(0x00780078u | CTL_SHIFT)) | ((ctl_tab + 0x00200020u) & 0x00780078u);
        const float i0 = rcp_approx(quad_sum(l[0])), i1 = rcp_approx(quad_sum(l[1]));
        wg_wait<0>();
        reg_fence(O);
        if (w == 0) release(g - 2);
        release(g - 1);
#pragma unroll
        for (int i = 0; i < 32; i++) {
            const float sc = (i & 4) ? i1 : i0;
            pk[i] = pack_bf16(O[chunk_src(i)] * sc, O[chunk_src(i) + 1] * sc);
        }
        pend = ptr_off(ctx_dst(item == 5, 1), chunk0);
        prow = 0x400;
#pragma unroll
        for (int i = 32; i < 64; i++) pk[i] = 0;
        PROF(3 + 2 * item, w);
        if (w == 0) PROF_GT(3 + 2 * item);
    }

    float acc[64];
    uint32_t slot = 0;
    auto issue_out = [&](int first_acc) {
        wait_full(g);
        const uint64_t da = make_desc(sb + slot + w * 8192, 16), db = make_desc(sb + slot + PAGE, 8192);
        wg_fence();
#pragma unroll
        for (int q = 0; q < 4; q++) wgmma_n128_ss(acc, da + 2 * q, db + 128 * q, q ? 1 : first_acc);
        wg_commit();
        g++;
        slot = slot == SM_REGION - 2 * PAGE ? 0 : slot + 2 * PAGE;
    };
    issue_out(0);
#pragma unroll 1
    for (int kb = 1; kb < 64; kb++) {
        issue_out(1);
        wg_wait<1>();
        release(g - 2);
        if (kb <= 8 && !(kb & 1)) {
            write_part((kb >> 1) - 1);
            if (kb == 8) mark_done();
        }
        if (kb >= 32 && (kb & 3) == 2 * w) {
            uint32_t u0, u1, u2, u3;
            const uint32_t a = stg + (kb & 16) * 512 + (kb & 12) * 128 + lane * 16;
            mbar_wait(sb + BAR_G + w * 8, 0);
            lds128(a, u0, u1, u2, u3);
            sts128(a, pack_bf16(silu_f(bf_lo(u0)), silu_f(bf_hi(u0))), pack_bf16(silu_f(bf_lo(u1)), silu_f(bf_hi(u1))),
                   pack_bf16(silu_f(bf_lo(u2)), silu_f(bf_hi(u2))), pack_bf16(silu_f(bf_lo(u3)), silu_f(bf_hi(u3))));
        }
    }
    wait_full(g);
    __syncwarp();
    const uint32_t xs = sb + slot + w * PAGE + v * 2048;
    uint32_t xr[32], gr[32];
#pragma unroll
    for (int s = 0; s < 8; s++) {
        ldmatrix_x4(slab_addr(xs, lane, s), xr[4 * s], xr[4 * s + 1], xr[4 * s + 2], xr[4 * s + 3]);
        ldmatrix_x4(slab_addr(stg, lane, s), gr[4 * s], gr[4 * s + 1], gr[4 * s + 2], gr[4 * s + 3]);
    }
    wg_wait<0>();
    reg_fence(acc);
    PROF(14, w);
    if (w == 0) PROF_GT(14);
#pragma unroll
    for (int s = 0; s < 8; s++) {
        uint32_t o[4];
#pragma unroll
        for (int k = 0; k < 4; k++)
            o[k] = bf2_add(xr[4 * s + k], bf2_mul(pack_bf16(acc[8 * s + 2 * k], acc[8 * s + 2 * k + 1]), gr[4 * s + k]));
        stmatrix_x4(slab_addr(stg, lane, s), o[0], o[1], o[2], o[3]);
    }
    fence_async_smem();
    __syncwarp();
    PROF(28, w);
    if (lane == 0) {
        const int orow = ((pair >> 1) & 7) * 256 + c * 128 + w * 64 + v * 16, ocol = (pair >> 4) * 256 + (pair & 1) * 128;
        tma_store_2d(m_out, ocol, orow, stg);
        tma_store_2d(m_out, ocol + 64, orow, stg + 8192);
        bulk_commit();
        bulk_wait_read();
    }
    __syncwarp();
}

__global__ void __cluster_dims__(2, 1, 1) __launch_bounds__(384, 1)
fused_kernel(const __grid_constant__ CUtensorMap m_ckv, const __grid_constant__ CUtensorMap m_wuk,
             const __grid_constant__ CUtensorMap m_wuv, const __grid_constant__ CUtensorMap m_wq,
             const __grid_constant__ CUtensorMap m_wo, const __grid_constant__ CUtensorMap m_x,
             const __grid_constant__ CUtensorMap m_out, const __grid_constant__ CUtensorMap m_gate,
             const __grid_constant__ CUtensorMap m_up, const __grid_constant__ CUtensorMap m_down, const Params P) {
    extern __shared__ __align__(1024) uint8_t smem[];
    const uint32_t sb = __shfl_sync(~0u, smem_u32(smem), 0);
    const int tid = threadIdx.x;
    const int cl = blockIdx.x >> 1, c = blockIdx.x & 1;
    const int pair = cl >= 64 ? cl : cl < 4 ? cl * 16 + 15 : cl < 36 ? ((cl - 4) >> 3) * 16 + ((cl - 4) & 7)
                                                                    : ((cl - 36) / 7) * 16 + 8 + (cl - 36) % 7;
    const bool starter = tid == 256 && pair < NMAIN / 2;
    if (tid == 256) {
#pragma unroll
        for (int i = 0; i < NBAR; i++) mbar_init(sb + SM_BAR + i * 8, (i >> 3) == 1 ? 16 : i >= 25 ? 8 : 1);
        asm volatile("fence.mbarrier_init.release.cluster;" ::: "memory");
    }
    const CUtensorMap* m_wu = c ? &m_wuv : &m_wuk;
    if (starter) {
        prefetch_map(&m_ckv);
#pragma unroll 1
        for (int kb = 0; kb < 4; kb++) {
            mbar_expect_tx(sb + BAR_FULL + kb * 8, 3 * PAGE);
            if (kb < EARLYW) tma_3d(sb + kb * (3 * PAGE), m_wu, 0, kb * 64, kv_head(pair) * 2, sb + BAR_FULL + kb * 8);
        }
    }
    PROF(18, (tid >> 7) & 1);
    __syncthreads();
    cluster_sync();
    PROF(22, (tid >> 7) & 1);
    if (starter) {
#pragma unroll 1
        for (int kb = 0; kb < 4; kb++) {
            if (kb >= EARLYW) tma_3d(sb + kb * (3 * PAGE), m_wu, 0, kb * 64, kv_head(pair) * 2, sb + BAR_FULL + kb * 8);
            tma_3d_mc(sb + kb * (3 * PAGE) + (1 + c) * PAGE, &m_ckv, 0, kv_tokens(pair) * 256 + c * 128, kb, sb + BAR_FULL + kb * 8);
        }
    }
    PROF(19, (tid >> 7) & 1);
    const int warp = __shfl_sync(~0u, tid >> 5, 0), lane = tid & 31;
    auto finish = [&]() {
        PROF(29, tid >> 7);
        cluster_sync();
        if (tid == 0) atomicAdd(&g_sync.done, 1u);
    };
    if (pair >= NMAIN / 2) {
        if (warp < 8) ffn_cta(smem, sb, blockIdx.x - NMAIN, __ldcg(&g_sync.done) / NCTA, P.w_r);
        else if (tid == 256) ffn_producer(sb, blockIdx.x - NMAIN, &m_gate, &m_up, &m_down);
        __syncwarp();
        finish();
    } else if (warp < 8) {
        asm volatile("setmaxnreg.inc.sync.aligned.u32 232;");
        consumer(sb, pair, c, &m_out, (const uint8_t*)P.x);
        finish();
    } else {
        asm volatile("setmaxnreg.dec.sync.aligned.u32 40;");
        if (warp == 10) {
            sync_helper(sb, lane, pair, c);
        } else if (warp & 1) {
            fetch_helper(P, sb, (warp >> 1) & 1, lane, pair, c);
        } else {
            producer(P, sb, pair, c, &m_ckv, m_wu, &m_wq, &m_wo, &m_x, &m_out);
        }
        cluster_sync();
    }
}

typedef CUresult (*EncodeFn)(CUtensorMap*, CUtensorMapDataType, cuuint32_t, void*, const cuuint64_t*, const cuuint64_t*,
                             const cuuint32_t*, const cuuint32_t*, CUtensorMapInterleave, CUtensorMapSwizzle,
                             CUtensorMapL2promotion, CUtensorMapFloatOOBfill);

void make_map_2d(EncodeFn fn, CUtensorMap* m, const void* ptr, int rows, int cols, int box_rows) {
    cuuint64_t dims[2] = {(cuuint64_t)cols, (cuuint64_t)rows};
    cuuint64_t strides[1] = {(cuuint64_t)cols * 2};
    cuuint32_t box[2] = {64, (cuuint32_t)box_rows};
    cuuint32_t es[2] = {1, 1};
    fn(m, CU_TENSOR_MAP_DATA_TYPE_BFLOAT16, 2, const_cast<void*>(ptr), dims, strides, box, es, CU_TENSOR_MAP_INTERLEAVE_NONE,
       CU_TENSOR_MAP_SWIZZLE_128B, CU_TENSOR_MAP_L2_PROMOTION_L2_256B, CU_TENSOR_MAP_FLOAT_OOB_FILL_NONE);
}
void make_map_w(EncodeFn fn, CUtensorMap* m, const void* ptr, int rows, int cols, int blocks, int box_rows = 32) {
    cuuint64_t dims[3] = {64, (cuuint64_t)rows, (cuuint64_t)cols / 64};
    cuuint64_t strides[2] = {(cuuint64_t)cols * 2, 128};
    cuuint32_t box[3] = {64, (cuuint32_t)box_rows, (cuuint32_t)blocks};
    cuuint32_t es[3] = {1, 1, 1};
    fn(m, CU_TENSOR_MAP_DATA_TYPE_BFLOAT16, 3, const_cast<void*>(ptr), dims, strides, box, es, CU_TENSOR_MAP_INTERLEAVE_NONE,
       CU_TENSOR_MAP_SWIZZLE_128B, CU_TENSOR_MAP_L2_PROMOTION_L2_256B, CU_TENSOR_MAP_FLOAT_OOB_FILL_NONE);
}

}

extern "C" void kernel_launch(void* const* d_in, const int* in_sizes, int n_in, void* d_out, int out_size) {
    static EncodeFn fn = nullptr;
    if (!fn) {
        void* f = nullptr;
        cudaDriverEntryPointQueryResult qr;
        cudaGetDriverEntryPoint("cuTensorMapEncodeTiled", &f, cudaEnableDefault, &qr);
        fn = (EncodeFn)f;
        cudaFuncSetAttribute(fused_kernel, cudaFuncAttributeMaxDynamicSharedMemorySize, SMEM_BYTES);
    }
    CUtensorMap m_ckv, m_wuk, m_wuv, m_wq, m_wo, m_x, m_out, m_gate, m_up, m_down;
    make_map_w(fn, &m_gate, d_in[8], DM, FF, FS / 64, 16);
    make_map_w(fn, &m_up, d_in[9], DM, FF, FS / 64, 16);
    make_map_w(fn, &m_down, d_in[10], FF, DM, DM / 64, 16);
    make_map_w(fn, &m_ckv, d_in[1], SEQ, DC, 1, 128);
    make_map_w(fn, &m_wq, d_in[2], DM, NH * 128, 1, 64);
    make_map_w(fn, &m_wuk, d_in[3], DC, NH * 128, 2, 64);
    make_map_w(fn, &m_wuv, d_in[4], DC, NH * 128, 2, 64);
    make_map_w(fn, &m_wo, d_in[5], NH * 128, DM, 1, 64);
    make_map_w(fn, &m_x, d_in[0], SEQ, DM, 2, 64);
    make_map_2d(fn, &m_out, d_out, SEQ, DM, 16);
    Params P;
    P.x = (const __nv_bfloat16*)d_in[0];
    P.w_r = (const __nv_bfloat16*)d_in[7];
    P.c_kv = (const uint8_t*)d_in[1];
    P.w_uk = (const uint8_t*)d_in[3];
    P.w_uv = (const uint8_t*)d_in[4];
    fused_kernel<<<NCTA, 384, SMEM_BYTES>>>(m_ckv, m_wuk, m_wuv, m_wq, m_wo, m_x, m_out, m_gate, m_up, m_down, P);
}
```

```cpp
#include <cuda_runtime.h>
#include <cuda_bf16.h>
#include <cuda.h>
#include <stdint.h>
#define FDELAY 1
#define LNSH 0
#define FETCH_INL __noinline__
#define RDUM 0
#define UBAD 0
#define ACOND ((0x1B >> item) & 1)
#define LATEMC 1
#define START 2
#define XAT 1
#include <type_traits>
#define WN 6
#define WINP 1
#define LQN 8
#define LQPOS 1
#define QOPQ 0
#define NTIE 1
#define KTRY 1
#define MASKV 1
#define EREL 0
#define NSUM 2
#define EARLY 2
#define PMINIT 1
#define QSPLIT 1
#define PARK0 1
#define MG 8
#define LQEND 4
#define QKORD 1
#define BALLOT 1
#define AMAP 1
#define EARLYW 2
#define QSCALE 1
#define INPLACE 1

namespace {

constexpr int SEQ = 2048, DM = 1024, NH = 32, DC = 512, FF = 3584;
constexpr int PAGE = 16384;
constexpr int NRING = 12;
constexpr int NCTA = 132, NMAIN = 128;
constexpr uint32_t SM_REGION = NRING * PAGE;
constexpr uint32_t SM_BAR = (NRING + 2) * PAGE;
constexpr uint32_t BAR_FULL = SM_BAR, BAR_EMPTY = SM_BAR + 64;
constexpr uint32_t BAR_DEP = SM_BAR + 128;
constexpr uint32_t BAR_G = SM_BAR + 184;
constexpr uint32_t BAR_DONE = SM_BAR + 200;
constexpr uint32_t BAR_EMPTYL = SM_BAR + 216;
constexpr int NBAR = 35;
constexpr uint32_t SM_PROF = SM_BAR + 320;
constexpr int SMEM_BYTES = SM_PROF + 512;
constexpr uint32_t SPIN_LIMIT = 1u << 16;
constexpr uint32_t POLL_MASK = 7;

struct SyncBlock {
    unsigned done;       unsigned pad0[31];
    unsigned ln;         unsigned pad1[31];
    unsigned router;     unsigned pad4[31];
    unsigned ffn_ticket; unsigned pad2[31];
    unsigned ffn_done;   unsigned pad3[31];
    unsigned kv[NH * 8];
    unsigned kvfree[16 * 8];
    unsigned ctx[32 * NH];
};

__device__ __align__(1024) uint8_t g_xn[8 * 16 * 4 * 8192];
__device__ __align__(4096) uint8_t g_kv[16 * 16 * 65536];
__device__ __align__(4096) uint8_t g_ctx[16 * 64 * 16384];
__device__ __align__(16) uint4 g_routed[2 * 128];
__device__ int g_sel[2];
__device__ __align__(16) float g_r[SEQ];
__device__ __align__(16) float g_ypart[4 * 2 * DM];
__device__ SyncBlock g_sync;

__device__ __forceinline__ uint32_t smem_u32(const void* p) { return (uint32_t)__cvta_generic_to_shared(p); }

__device__ __forceinline__ void mbar_init(uint32_t bar, uint32_t count) {
    asm volatile("mbarrier.init.shared::cta.b64 [%0], %1;" ::"r"(bar), "r"(count) : "memory");
}
#define MBAR_WAIT_ASM(HINT, LIMIT)                                                                  \
    asm volatile("{\n.reg .pred p;\n.reg .u32 n;\nmov.u32 n, 0;\n"                                  \
                 "WAIT_LOOP:\n"                                                                     \
                 "mbarrier.try_wait.parity.shared::cta.b64 p, [%0], %1" HINT ";\n"                  \
                 "@p bra WAIT_DONE;\n"                                                              \
                 "add.u32 n, n, 1;\n"                                                               \
                 "setp.lt.u32 p, n, " LIMIT ";\n"                                                   \
                 "@p bra WAIT_LOOP;\n"                                                              \
                 "WAIT_DONE:\n}\n" ::"r"(bar), "r"(parity) : "memory")
__device__ __forceinline__ void mbar_wait(uint32_t bar, uint32_t parity) { MBAR_WAIT_ASM("", "131072"); }
__device__ __forceinline__ void mbar_sleep(uint32_t bar, uint32_t parity) { MBAR_WAIT_ASM(", 2000", "8192"); }
__device__ __forceinline__ bool mbar_try(uint32_t bar, uint32_t parity) {
    uint32_t ok;
    asm volatile("{\n.reg .pred p;\nmbarrier.try_wait.parity.shared::cta.b64 p, [%1], %2;\nselp.u32 %0, 1, 0, p;\n}\n"
                 : "=r"(ok) : "r"(bar), "r"(parity) : "memory");
    return ok;
}
__device__ __forceinline__ bool mbar_test(uint32_t bar, uint32_t parity) {
    uint32_t ok;
    asm volatile("{\n.reg .pred p;\nmbarrier.test_wait.parity.shared::cta.b64 p, [%1], %2;\nselp.u32 %0, 1, 0, p;\n}\n"
                 : "=r"(ok) : "r"(bar), "r"(parity) : "memory");
    return ok;
}
__device__ __forceinline__ bool elect_one() {
    uint32_t ok;
    asm volatile("{\n.reg .pred p;\nelect.sync _|p, 0xffffffff;\nselp.u32 %0, 1, 0, p;\n}\n" : "=r"(ok));
    return ok;
}
__device__ __forceinline__ void mbar_arrive(uint32_t bar) {
    asm volatile("mbarrier.arrive.shared::cta.b64 _, [%0];" ::"r"(bar) : "memory");
}
__device__ __forceinline__ void mbar_expect_tx(uint32_t bar, uint32_t bytes) {
    asm volatile("mbarrier.arrive.expect_tx.shared::cta.b64 _, [%0], %1;" ::"r"(bar), "r"(bytes) : "memory");
}
__device__ __forceinline__ void mbar_arrive_cluster(uint32_t cluster_addr) {
    asm volatile("mbarrier.arrive.shared::cluster.b64 _, [%0];" ::"r"(cluster_addr) : "memory");
}
__device__ __forceinline__ uint32_t mapa(uint32_t addr, uint32_t rank) {
    uint32_t r;
    asm("mapa.shared::cluster.u32 %0, %1, %2;" : "=r"(r) : "r"(addr), "r"(rank));
    return r;
}
__device__ __forceinline__ void tma_3d(uint32_t dst, const CUtensorMap* m, int c0, int c1, int c2, uint32_t bar) {
    asm volatile("cp.async.bulk.tensor.3d.shared::cluster.global.mbarrier::complete_tx::bytes [%0], [%1, {%3, %4, %5}], [%2];"
                 ::"r"(dst), "l"(m), "r"(bar), "r"(c0), "r"(c1), "r"(c2) : "memory");
}
__device__ __forceinline__ void tma_3d_hint(uint32_t dst, const CUtensorMap* m, int c0, int c1, int c2, uint32_t bar, uint64_t pol) {
    asm volatile("cp.async.bulk.tensor.3d.shared::cluster.global.mbarrier::complete_tx::bytes.L2::cache_hint [%0], [%1, {%3, %4, %5}], [%2], %6;"
                 ::"r"(dst), "l"(m), "r"(bar), "r"(c0), "r"(c1), "r"(c2), "l"(pol) : "memory");
}
__device__ __forceinline__ void tma_3d_mc(uint32_t dst, const CUtensorMap* m, int c0, int c1, int c2, uint32_t bar) {
    asm volatile("cp.async.bulk.tensor.3d.shared::cluster.global.mbarrier::complete_tx::bytes.multicast::cluster [%0], [%1, {%3, %4, %5}], [%2], %6;"
                 ::"r"(dst), "l"(m), "r"(bar), "r"(c0), "r"(c1), "r"(c2), "h"((uint16_t)3) : "memory");
}
__device__ __forceinline__ void bulk_load(uint32_t dst, const void* src, uint32_t bytes, uint32_t bar) {
    asm volatile("cp.async.bulk.shared::cluster.global.mbarrier::complete_tx::bytes [%0], [%1], %2, [%3];"
                 ::"r"(dst), "l"(src), "r"(bytes), "r"(bar) : "memory");
}
__device__ __forceinline__ void cp_async16(uint32_t dst, const void* src) {
    asm volatile("cp.async.cg.shared.global [%0], [%1], 16;" ::"r"(dst), "l"(src) : "memory");
}
__device__ __forceinline__ void bulk_load_mc(uint32_t dst, const void* src, uint32_t bytes, uint32_t bar) {
    asm volatile("cp.async.bulk.shared::cluster.global.mbarrier::complete_tx::bytes.multicast::cluster [%0], [%1], %2, [%3], %4;"
                 ::"r"(dst), "l"(src), "r"(bytes), "r"(bar), "h"((uint16_t)3) : "memory");
}
__device__ __forceinline__ void tma_store_2d(const CUtensorMap* m, int c0, int c1, uint32_t src) {
    asm volatile("cp.async.bulk.tensor.2d.global.shared::cta.bulk_group [%0, {%2, %3}], [%1];"
                 ::"l"(m), "r"(src), "r"(c0), "r"(c1) : "memory");
}
__device__ __forceinline__ void bulk_commit() { asm volatile("cp.async.bulk.commit_group;" ::: "memory"); }
__device__ __forceinline__ void bulk_wait_read() { asm volatile("cp.async.bulk.wait_group.read 0;" ::: "memory"); }
__device__ __forceinline__ void fence_async_smem() { asm volatile("fence.proxy.async.shared::cta;" ::: "memory"); }
__device__ __forceinline__ void prefetch_map(const CUtensorMap* m) {
    asm volatile("prefetch.tensormap [%0];" ::"l"(m) : "memory");
}
__device__ __forceinline__ void red_release(unsigned* p) {
    asm volatile("red.release.gpu.global.add.u32 [%0], 1;" ::"l"(p) : "memory");
}
__device__ __forceinline__ unsigned ld_relaxed(const unsigned* p) {
    unsigned v;
    asm volatile("ld.relaxed.gpu.global.u32 %0, [%1];" : "=r"(v) : "l"(p) : "memory");
    return v;
}
__device__ __forceinline__ void wait_counter(const unsigned* p, unsigned target) {
    for (uint32_t n = 0; (int)(ld_relaxed(p) - target) < 0 && n < SPIN_LIMIT; n++) __nanosleep(100);
    asm volatile("fence.acquire.gpu;" ::: "memory");
    asm volatile("fence.proxy.async.global;" ::: "memory");
}
__device__ __forceinline__ void bar_sync(int id, int n) { asm volatile("bar.sync %0, %1;" ::"r"(id), "r"(n) : "memory"); }
__device__ __forceinline__ void bar_arrive(int id, int n) { asm volatile("bar.arrive %0, %1;" ::"r"(id), "r"(n) : "memory"); }
__device__ __forceinline__ void cluster_sync() {
    asm volatile("barrier.cluster.arrive.relaxed.aligned;\nbarrier.cluster.wait.aligned;" ::: "memory");
}
__device__ __forceinline__ void wg_fence() { asm volatile("wgmma.fence.sync.aligned;" ::: "memory"); }
__device__ __forceinline__ void wg_commit() { asm volatile("wgmma.commit_group.sync.aligned;" ::: "memory"); }
template <int N> __device__ __forceinline__ void wg_wait() { asm volatile("wgmma.wait_group.sync.aligned %0;" ::"n"(N) : "memory"); }
template <int N> __device__ __forceinline__ void reg_fence(float (&a)[N]) {
#pragma unroll
    for (int i = 0; i < N; i++) asm volatile("" : "+f"(a[i])::"memory");
}
template <int N> __device__ __forceinline__ void reg_fence(uint32_t (&a)[N]) {
#pragma unroll
    for (int i = 0; i < N; i++) asm volatile("" : "+r"(a[i])::"memory");
}
__device__ __forceinline__ uint32_t pack_bf16(float lo, float hi) {
    uint32_t r;
    asm("cvt.rn.bf16x2.f32 %0, %1, %2;" : "=r"(r) : "f"(hi), "f"(lo));
    return r;
}
__device__ __forceinline__ float bf_lo(uint32_t v) { return __uint_as_float(v << 16); }
__device__ __forceinline__ float bf_hi(uint32_t v) { return __uint_as_float(v & 0xffff0000u); }
__device__ __forceinline__ float bf_round(float v) { return __bfloat162float(__float2bfloat16_rn(v)); }
__device__ __forceinline__ float ex2(float v) {
    float r;
    asm("ex2.approx.ftz.f32 %0, %1;" : "=f"(r) : "f"(v));
    return r;
}
__device__ __forceinline__ float sqrt_approx(float v) {
    float r;
    asm("sqrt.approx.ftz.f32 %0, %1;" : "=f"(r) : "f"(v));
    return r;
}
__device__ __forceinline__ float rcp_approx(float v) {
    float r;
    asm("rcp.approx.ftz.f32 %0, %1;" : "=f"(r) : "f"(v));
    return r;
}
__device__ __forceinline__ float silu_f(float v) { return v * rcp_approx(1.0f + ex2(v * -1.4426950408889634f)); }
__device__ __forceinline__ void stmatrix_x4(uint32_t addr, uint32_t r0, uint32_t r1, uint32_t r2, uint32_t r3) {
    asm volatile("stmatrix.sync.aligned.m8n8.x4.shared.b16 [%0], {%1, %2, %3, %4};"
                 ::"r"(addr), "r"(r0), "r"(r1), "r"(r2), "r"(r3) : "memory");
}
__device__ __forceinline__ void sts128(uint32_t addr, uint32_t r0, uint32_t r1, uint32_t r2, uint32_t r3) {
    asm volatile("st.shared.v4.b32 [%0], {%1, %2, %3, %4};" ::"r"(addr), "r"(r0), "r"(r1), "r"(r2), "r"(r3) : "memory");
}
__device__ __forceinline__ void lds128(uint32_t addr, uint32_t& r0, uint32_t& r1, uint32_t& r2, uint32_t& r3) {
    asm volatile("ld.shared.v4.b32 {%0, %1, %2, %3}, [%4];" : "=r"(r0), "=r"(r1), "=r"(r2), "=r"(r3) : "r"(addr) : "memory");
}
__device__ __forceinline__ void ldmatrix_x4(uint32_t addr, uint32_t& r0, uint32_t& r1, uint32_t& r2, uint32_t& r3) {
    asm volatile("ldmatrix.sync.aligned.m8n8.x4.shared.b16 {%0, %1, %2, %3}, [%4];"
                 : "=r"(r0), "=r"(r1), "=r"(r2), "=r"(r3) : "r"(addr) : "memory");
}
__device__ __forceinline__ uint32_t bf2_mul(uint32_t a, uint32_t b) {
    uint32_t r;
    asm("mul.rn.bf16x2 %0, %1, %2;" : "=r"(r) : "r"(a), "r"(b));
    return r;
}
__device__ __forceinline__ uint32_t bf2_add(uint32_t a, uint32_t b) {
    uint32_t r;
    asm("add.rn.bf16x2 %0, %1, %2;" : "=r"(r) : "r"(a), "r"(b));
    return r;
}
__device__ __forceinline__ uint64_t policy_evict_first() {
    uint64_t p;
    asm("createpolicy.fractional.L2::evict_first.b64 %0, 1.0;" : "=l"(p));
    return p;
}

__device__ __forceinline__ uint64_t make_desc(uint32_t addr, uint32_t lbo_bytes) {
    return (uint64_t)((addr & 0x3FFFF) >> 4) | ((uint64_t)(lbo_bytes >> 4) << 16) | ((uint64_t)(1024 >> 4) << 32) | (1ull << 62);
}

__device__ __forceinline__ void wgmma_n256_ss(float (&d)[128], uint64_t da, uint64_t db, int acc) {
    asm volatile(
        "{\n.reg .pred p;\nsetp.ne.b32 p, %130, 0;\n"
        "wgmma.mma_async.sync.aligned.m64n256k16.f32.bf16.bf16 {"
        "%0, %1, %2, %3, %4, %5, %6, %7, %8, %9, %10, %11, %12, %13, %14, %15, "
        "%16, %17, %18, %19, %20, %21, %22, %23, %24, %25, %26, %27, %28, %29, %30, %31, "
        "%32, %33, %34, %35, %36, %37, %38, %39, %40, %41, %42, %43, %44, %45, %46, %47, "
        "%48, %49, %50, %51, %52, %53, %54, %55, %56, %57, %58, %59, %60, %61, %62, %63, "
        "%64, %65, %66, %67, %68, %69, %70, %71, %72, %73, %74, %75, %76, %77, %78, %79, "
        "%80, %81, %82, %83, %84, %85, %86, %87, %88, %89, %90, %91, %92, %93, %94, %95, "
        "%96, %97, %98, %99, %100, %101, %102, %103, %104, %105, %106, %107, %108, %109, %110, %111, "
        "%112, %113, %114, %115, %116, %117, %118, %119, %120, %121, %122, %123, %124, %125, %126, %127"
        "}, %128, %129, p, 1, 1, 1, 0;\n}\n"
        :
        "+f"(d[0]), "+f"(d[1]), "+f"(d[2]), "+f"(d[3]), "+f"(d[4]), "+f"(d[5]), "+f"(d[6]), "+f"(d[7]),
        "+f"(d[8]), "+f"(d[9]), "+f"(d[10]), "+f"(d[11]), "+f"(d[12]), "+f"(d[13]), "+f"(d[14]), "+f"(d[15]),
        "+f"(d[16]), "+f"(d[17]), "+f"(d[18]), "+f"(d[19]), "+f"(d[20]), "+f"(d[21]), "+f"(d[22]), "+f"(d[23]),
        "+f"(d[24]), "+f"(d[25]), "+f"(d[26]), "+f"(d[27]), "+f"(d[28]), "+f"(d[29]), "+f"(d[30]), "+f"(d[31]),
        "+f"(d[32]), "+f"(d[33]), "+f"(d[34]), "+f"(d[35]), "+f"(d[36]), "+f"(d[37]), "+f"(d[38]), "+f"(d[39]),
        "+f"(d[40]), "+f"(d[41]), "+f"(d[42]), "+f"(d[43]), "+f"(d[44]), "+f"(d[45]), "+f"(d[46]), "+f"(d[47]),
        "+f"(d[48]), "+f"(d[49]), "+f"(d[50]), "+f"(d[51]), "+f"(d[52]), "+f"(d[53]), "+f"(d[54]), "+f"(d[55]),
        "+f"(d[56]), "+f"(d[57]), "+f"(d[58]), "+f"(d[59]), "+f"(d[60]), "+f"(d[61]), "+f"(d[62]), "+f"(d[63]),
        "+f"(d[64]), "+f"(d[65]), "+f"(d[66]), "+f"(d[67]), "+f"(d[68]), "+f"(d[69]), "+f"(d[70]), "+f"(d[71]),
        "+f"(d[72]), "+f"(d[73]), "+f"(d[74]), "+f"(d[75]), "+f"(d[76]), "+f"(d[77]), "+f"(d[78]), "+f"(d[79]),
        "+f"(d[80]), "+f"(d[81]), "+f"(d[82]), "+f"(d[83]), "+f"(d[84]), "+f"(d[85]), "+f"(d[86]), "+f"(d[87]),
        "+f"(d[88]), "+f"(d[89]), "+f"(d[90]), "+f"(d[91]), "+f"(d[92]), "+f"(d[93]), "+f"(d[94]), "+f"(d[95]),
        "+f"(d[96]), "+f"(d[97]), "+f"(d[98]), "+f"(d[99]), "+f"(d[100]), "+f"(d[101]), "+f"(d[102]), "+f"(d[103]),
        "+f"(d[104]), "+f"(d[105]), "+f"(d[106]), "+f"(d[107]), "+f"(d[108]), "+f"(d[109]), "+f"(d[110]), "+f"(d[111]),
        "+f"(d[112]), "+f"(d[113]), "+f"(d[114]), "+f"(d[115]), "+f"(d[116]), "+f"(d[117]), "+f"(d[118]), "+f"(d[119]),
        "+f"(d[120]), "+f"(d[121]), "+f"(d[122]), "+f"(d[123]), "+f"(d[124]), "+f"(d[125]), "+f"(d[126]), "+f"(d[127])
        : "l"(da), "l"(db), "r"(acc));
}

template <int TB>
__device__ __forceinline__ void wgmma_n128_rs(float (&d)[64], uint32_t a0, uint32_t a1, uint32_t a2, uint32_t a3, uint32_t db, int acc) {
    asm volatile(
        "{\n.reg .pred p;\n.reg .b64 db;\nsetp.ne.b32 p, %69, 0;\nmov.b64 db, {%68, 0x40000040};\n"
        "wgmma.mma_async.sync.aligned.m64n128k16.f32.bf16.bf16 {"
        "%0, %1, %2, %3, %4, %5, %6, %7, %8, %9, %10, %11, %12, %13, %14, %15, "
        "%16, %17, %18, %19, %20, %21, %22, %23, %24, %25, %26, %27, %28, %29, %30, %31, "
        "%32, %33, %34, %35, %36, %37, %38, %39, %40, %41, %42, %43, %44, %45, %46, %47, "
        "%48, %49, %50, %51, %52, %53, %54, %55, %56, %57, %58, %59, %60, %61, %62, %63"
        "}, {%64, %65, %66, %67}, db, p, 1, 1, %70;\n}\n"
        :
        "+f"(d[0]), "+f"(d[1]), "+f"(d[2]), "+f"(d[3]), "+f"(d[4]), "+f"(d[5]), "+f"(d[6]), "+f"(d[7]),
        "+f"(d[8]), "+f"(d[9]), "+f"(d[10]), "+f"(d[11]), "+f"(d[12]), "+f"(d[13]), "+f"(d[14]), "+f"(d[15]),
        "+f"(d[16]), "+f"(d[17]), "+f"(d[18]), "+f"(d[19]), "+f"(d[20]), "+f"(d[21]), "+f"(d[22]), "+f"(d[23]),
        "+f"(d[24]), "+f"(d[25]), "+f"(d[26]), "+f"(d[27]), "+f"(d[28]), "+f"(d[29]), "+f"(d[30]), "+f"(d[31]),
        "+f"(d[32]), "+f"(d[33]), "+f"(d[34]), "+f"(d[35]), "+f"(d[36]), "+f"(d[37]), "+f"(d[38]), "+f"(d[39]),
        "+f"(d[40]), "+f"(d[41]), "+f"(d[42]), "+f"(d[43]), "+f"(d[44]), "+f"(d[45]), "+f"(d[46]), "+f"(d[47]),
        "+f"(d[48]), "+f"(d[49]), "+f"(d[50]), "+f"(d[51]), "+f"(d[52]), "+f"(d[53]), "+f"(d[54]), "+f"(d[55]),
        "+f"(d[56]), "+f"(d[57]), "+f"(d[58]), "+f"(d[59]), "+f"(d[60]), "+f"(d[61]), "+f"(d[62]), "+f"(d[63])
        : "r"(a0), "r"(a1), "r"(a2), "r"(a3), "r"(db), "r"(acc), "n"(TB));
}

__device__ __forceinline__ void wgmma_n128_ss(float* d, uint64_t da, uint64_t db, int acc) {
    asm volatile(
        "{\n.reg .pred p;\nsetp.ne.b32 p, %66, 0;\n"
        "wgmma.mma_async.sync.aligned.m64n128k16.f32.bf16.bf16 {"
        "%0, %1, %2, %3, %4, %5, %6, %7, %8, %9, %10, %11, %12, %13, %14, %15, "
        "%16, %17, %18, %19, %20, %21, %22, %23, %24, %25, %26, %27, %28, %29, %30, %31, "
        "%32, %33, %34, %35, %36, %37, %38, %39, %40, %41, %42, %43, %44, %45, %46, %47, "
        "%48, %49, %50, %51, %52, %53, %54, %55, %56, %57, %58, %59, %60, %61, %62, %63"
        "}, %64, %65, p, 1, 1, 0, 1;\n}\n"
        :
        "+f"(d[0]), "+f"(d[1]), "+f"(d[2]), "+f"(d[3]), "+f"(d[4]), "+f"(d[5]), "+f"(d[6]), "+f"(d[7]),
        "+f"(d[8]), "+f"(d[9]), "+f"(d[10]), "+f"(d[11]), "+f"(d[12]), "+f"(d[13]), "+f"(d[14]), "+f"(d[15]),
        "+f"(d[16]), "+f"(d[17]), "+f"(d[18]), "+f"(d[19]), "+f"(d[20]), "+f"(d[21]), "+f"(d[22]), "+f"(d[23]),
        "+f"(d[24]), "+f"(d[25]), "+f"(d[26]), "+f"(d[27]), "+f"(d[28]), "+f"(d[29]), "+f"(d[30]), "+f"(d[31]),
        "+f"(d[32]), "+f"(d[33]), "+f"(d[34]), "+f"(d[35]), "+f"(d[36]), "+f"(d[37]), "+f"(d[38]), "+f"(d[39]),
        "+f"(d[40]), "+f"(d[41]), "+f"(d[42]), "+f"(d[43]), "+f"(d[44]), "+f"(d[45]), "+f"(d[46]), "+f"(d[47]),
        "+f"(d[48]), "+f"(d[49]), "+f"(d[50]), "+f"(d[51]), "+f"(d[52]), "+f"(d[53]), "+f"(d[54]), "+f"(d[55]),
        "+f"(d[56]), "+f"(d[57]), "+f"(d[58]), "+f"(d[59]), "+f"(d[60]), "+f"(d[61]), "+f"(d[62]), "+f"(d[63])
        : "l"(da), "l"(db), "r"(acc));
}

__device__ __forceinline__ void wgmma_n8_ta(float* d, uint64_t da, uint64_t db) {
    asm volatile("wgmma.mma_async.sync.aligned.m64n8k16.f32.bf16.bf16 {%0, %1, %2, %3}, %4, %5, 1, 1, 1, 1, 0;\n"
                 : "+f"(d[0]), "+f"(d[1]), "+f"(d[2]), "+f"(d[3]) : "l"(da), "l"(db));
}

#define PROF(slot, role)
#undef PROF_GT
#define PROF_GT(slot)

struct Params {
    const __nv_bfloat16* x;
    const __nv_bfloat16* w_r;
    const uint8_t *c_kv, *w_uk, *w_uv;
};
__device__ __forceinline__ void lsu_prefetch(const void* p) { asm volatile("prefetch.global.L2 [%0];" ::"l"(p) : "memory"); }

template <typename T>
__device__ __forceinline__ T* ptr_off(T* base, uint32_t off) {
    uint32_t lo, hi;
    asm("mov.b64 {%0, %1}, %2;" : "=r"(lo), "=r"(hi) : "l"(base));
    asm("add.cc.u32 %0, %0, %2;\naddc.u32 %1, %1, 0;" : "+r"(lo), "+r"(hi) : "r"(off));
    T* r;
    asm("mov.b64 %0, {%1, %2};" : "=l"(r) : "r"(lo), "r"(hi));
    return r;
}
__device__ __forceinline__ int kv_head(int pair) { return AMAP ? (pair & 15) >> 1 : pair >> 3; }
__device__ __forceinline__ int kv_tokens(int pair) { return AMAP ? (pair & 1) * 4 + (pair >> 4) : pair & 7; }
__device__ __forceinline__ int attn_rowblock(int pair, int seg) {
    int j = pair & 3, hl = pair >> 2;
    return ((hl & 1) ^ seg) ? j : 7 - j;
}
__device__ __forceinline__ int outproj_head(int i, int ib) {
    if (i < 16) return i;
    return 16 + 2 * (i & 7) + ((ib < 4) ^ ((i >> 3) & 1));
}

__device__ __forceinline__ void pin_value(uint32_t& v) { asm volatile("" : "+r"(v)); }
__device__ __forceinline__ void pin_value(int& v) { asm volatile("" : "+r"(v)); }
__device__ __forceinline__ void pin_value(const uint8_t*& v) { asm volatile("" : "+l"(v)); }

__device__ __forceinline__ void producer(const Params& P, uint32_t sb, int pair, int c,
                                         const CUtensorMap* m_ckv, const CUtensorMap* m_wu,
                                         const CUtensorMap* m_wq, const CUtensorMap* m_wo, const CUtensorMap* m_x,
                                         const CUtensorMap* m_out) {
    const int hl = pair >> 2;
    const int ibA = attn_rowblock(pair, 0), nA = 2 * ibA + 2;
    const int ib = (pair >> 1) & 7, mi = 2 * ib + c, nb = (pair >> 4) * 4 + (pair & 1) * 2;
    const bool leader = elect_one();
    uint32_t g = 4, tail = 0;
    if (leader) prefetch_map(m_wq);
    auto wait_released = [&](uint32_t need) {
#pragma unroll 1
        for (; tail <= need; tail++) mbar_wait(sb + BAR_EMPTY + (tail & 7) * 8, (tail >> 3) & 1);
    };
    auto wait_released_here = [&](uint32_t need) {
#pragma unroll 1
        for (; tail < need; tail++) mbar_wait(sb + BAR_EMPTY + (tail & 7) * 8, (tail >> 3) & 1);
        if (tail == need) mbar_wait(sb + BAR_EMPTYL + (need & 7) * 8, (need >> 3) & 1);
    };
    auto wait_released_peer = [&](uint32_t need) {
        if (tail == need) {
            uint32_t eb = sb + BAR_EMPTY + (need & 7) * 8, ep = (need >> 3) & 1;
            tail++;
            mbar_wait(eb, ep);
        }
    };
    auto full_bar = [&]() { return sb + BAR_FULL + (g & 7) * 8; };
    auto pin = [](auto&... v) { (pin_value(v), ...); };
#pragma unroll 1
    for (int rnd = 0; rnd < 2; rnd++) {
#pragma unroll 1
        for (int i = rnd ? 0 : 4; i < 16; i++) {
            int kb = i & 7, h2 = (kv_head(pair) + (i & 8) + rnd * 16) * 2, krow = kb * 64;
            uint32_t pg = sb + (i & 3) * (3 * PAGE), pb = pg + (1 + c) * PAGE, bar = full_bar();
            pin(kb, h2, krow, pg, pb, bar);
            const uint32_t need = g - 4 - (i < 2);
            wait_released_here(need);
            if (leader) {
                mbar_expect_tx(bar, 3 * PAGE);
                tma_3d(pg, m_wu, 0, krow, h2, bar);
            }
            wait_released_peer(need);
            if (leader) {
                tma_3d_mc(pb, m_ckv, 0, kv_tokens(pair) * 256 + c * 128, kb, bar);
                if (rnd == 1 && i == 3) asm volatile("red.relaxed.gpu.global.add.u32 [%0], 1;" ::"l"(ptr_off(g_sync.kvfree, hl * 32)) : "memory");
            }
            g++;
        }
        mbar_sleep(sb + BAR_DEP, 0);
        const uint8_t* xa = ptr_off(g_xn, ibA * (16 * 32768) + c * PAGE);
        const uint8_t* xb = ptr_off(g_xn, (7 - ibA) * (16 * 32768) + (1 - c) * PAGE);
#pragma unroll 1
        for (int kb = 0; kb < DM / 64; kb++) {
            uint32_t pg = sb + (kb & 3) * (3 * PAGE), pw = pg + 2 * PAGE + c * 8192, bar = full_bar(), p2 = pg + PAGE;
            int krow = kb * 64;
            pin(pg, pw, p2, bar, krow);
            wait_released_here(g - 4);
            if (leader) {
                mbar_expect_tx(bar, 3 * PAGE);
                bulk_load(pg, xa, PAGE, bar);
            }
            wait_released_peer(g - 4);
            if (leader) {
                tma_3d_mc(pw, m_wq, 0, krow, (rnd * 16 + hl) * 2 + c, bar);
                bulk_load(p2, xb, PAGE, bar);
            }
            g++;
            xa += 32768;
            xb += 32768;
        }
        mbar_sleep(sb + BAR_DEP + 8 + rnd * 16, 0);
        if (rnd == 1 && leader) prefetch_map(m_wo);
        uint32_t pg = sb + c * PAGE;
#pragma unroll 1
        for (int j = 0; j < 36; j++) {
            const bool isk = j == 0 || ((j & 1) && j != 35);
            const int t = isk ? (j + 1) >> 1 : (j - 1) >> 1;
            const uint8_t* src = ptr_off(g_kv, (hl * 16 + (t >= nA ? t - nA : t)) * 65536 + (isk ? 0 : 32768) + c * PAGE);
            uint32_t bar = full_bar(), need = g - 6 + (j < 2) + (j < 5);
            pin(src, bar, need);
            wait_released(need);
            if (leader) {
                mbar_expect_tx(bar, 2 * PAGE);
                bulk_load_mc(pg, src, PAGE, bar);
            }
            g++;
            if (rnd == 0 && j >= 22 && j < 34) {
                const int cta = pair * 2 + c, i = j - 22;
                const uint32_t l = (threadIdx.x & 31) * 128;
                if (i < 8) lsu_prefetch(ptr_off(i & 1 ? P.w_uv : P.w_uk, cta * 32768 + (i >> 1) * 8192 + 4096 + l));
                else lsu_prefetch(ptr_off(P.c_kv, cta * 16384 + (i - 8) * 4096 + l));
            }
            pg = pg >= sb + SM_REGION - 2 * PAGE ? pg - (SM_REGION - 2 * PAGE) : pg + 2 * PAGE;
        }
    }
    uint32_t pg = sb;
#pragma unroll 1
    for (int i = 0; i < 64; i++) {
        if (i == 32 && leader) { prefetch_map(m_x); prefetch_map(m_out); }
        if ((i & 15) == 0 && i != 16) mbar_sleep(sb + BAR_DEP + 32 + (i >> 1) - (i ? 8 : 0), 0);
        const int kb = outproj_head(i >> 1, ib) * 2 + (i & 1);
        const uint8_t* src = ptr_off(g_ctx, (mi * 64 + kb) * PAGE);
        uint32_t bar = full_bar(), pw = pg + PAGE + c * 8192;
        int krow = kb * 64;
        pin(src, bar, pw, krow);
        wait_released_here(g - 6);
        if (leader) {
            mbar_expect_tx(bar, 2 * PAGE);
            bulk_load(pg, src, PAGE, bar);
        }
        wait_released_peer(g - 6);
        if (leader) tma_3d_mc(pw, m_wo, 0, krow, nb + c, bar);
        g++;
        pg = pg == sb + SM_REGION - 2 * PAGE ? sb : pg + 2 * PAGE;
    }
    const uint32_t bar = full_bar();
    wait_released(g - 6);
    if (leader) {
        mbar_expect_tx(bar, 2 * PAGE);
        tma_3d(pg, m_x, 0, mi * 128, nb, bar);
        tma_3d(pg + PAGE, m_x, 0, mi * 128 + 64, nb, bar);
    }
}

__device__ __forceinline__ uint32_t xn_block(int row64, int kb) {
    return (((row64 >> 2) * 16 + kb) * 4 + ((row64 & 1) * 2 + (((row64 >> 1) & 1) ^ 1))) * 8192;
}
__device__ __forceinline__ uint32_t image_offset(int row, int ch) {
    return xn_block(row >> 6, ch >> 3) + (row & 63) * 128 + (((ch & 7) ^ (row & 7)) << 4);
}
__device__ __forceinline__ uint32_t bf2_sub(uint32_t a, uint32_t b) {
    uint32_t r;
    asm("sub.rn.bf16x2 %0, %1, %2;" : "=r"(r) : "r"(a), "r"(b));
    return r;
}
__device__ __forceinline__ uint32_t bf2_fma(uint32_t a, uint32_t b, uint32_t c) {
    uint32_t r;
    asm("fma.rn.bf16x2 %0, %1, %2, %3;" : "=r"(r) : "r"(a), "r"(b), "r"(c));
    return r;
}
template <int N0, int N>
__device__ __forceinline__ void ln_sums(const uint32_t (&u)[N], float& sum, float& sq) {
    float s0 = 0.f, s1 = 0.f, q0 = 0.f, q1 = 0.f;
#pragma unroll
    for (int k = N0; k < N0 + 16; k++) {
        const float a = bf_lo(u[k]), b = bf_hi(u[k]);
        s0 += a; s1 += b;
        q0 = fmaf(a, a, q0); q1 = fmaf(b, b, q1);
    }
    sum = s0 + s1;
    sq = q0 + q1;
}
__device__ __forceinline__ void ln_finish(float sum, float sq, uint32_t& mean2, uint32_t& rhi2, uint32_t& rlo2) {
    const float ms = sum * (1.0f / DM);
    const float var = fmaxf(fmaf(-ms, ms, sq * (1.0f / DM)), 0.f);
    const float rden = rcp_approx(bf_round(sqrt_approx(bf_round(bf_round(var) + 1e-5f))));
    const float rhi = bf_round(rden);
    mean2 = pack_bf16(ms, ms);
    rhi2 = pack_bf16(rhi, rhi);
    rlo2 = pack_bf16(rden - rhi, rden - rhi);
}
template <int N0, int N>
__device__ __forceinline__ void ln_apply(uint32_t (&u)[N], uint32_t mean2, uint32_t rhi2, uint32_t rlo2, uint8_t* dst) {
#pragma unroll
    for (int i = 0; i < 4; i++) {
        uint32_t o[4];
#pragma unroll
        for (int k = 0; k < 4; k++) {
            const uint32_t d = bf2_sub(u[N0 + 4 * i + k], mean2);
            o[k] = bf2_fma(d, rhi2, bf2_mul(d, rlo2));
        }
#pragma unroll
        for (int k = 0; k < 4; k++) u[N0 + 4 * i + k] = o[k];
        __stcg(reinterpret_cast<uint4*>(dst + i * 131072), make_uint4(o[0], o[1], o[2], o[3]));
    }
}
__device__ __forceinline__ int query_rowblock(int pair, int c, int w, int seg) {
    const int qA = (w ? 0 : 2) + c;
    return 4 * attn_rowblock(pair, seg) + (seg ? 3 - qA : qA);
}

__device__ FETCH_INL void fetch_helper(const uint8_t* w_u, uint32_t sb, int w, int lane, int pair, int c) {
    const uint32_t page = sb + SM_REGION + w * PAGE + lane * 16;
    mbar_sleep(sb + BAR_FULL + 5 * 8, 0);
#pragma unroll 1
    for (int i = 0; i < 2; i++) {
        lsu_prefetch(ptr_off(w_u, ((pair * 2 + c) * 4 + i * 2 + (lane >> 4)) * 8192 + 2048 + (lane & 15) * 128));
        __nanosleep(300);
    }
    const unsigned e1 = __ldcg(&g_sync.done) / NCTA + 1;
#pragma unroll 1
    for (int e = 1; e <= 7; e += 2) mbar_sleep(sb + BAR_DONE + 8, (e >> 1) & 1);
    const int rb = ((pair >> 1) & 7) * 4 + c * 2 + w, kb0 = (pair >> 4) * 4 + (pair & 1) * 2;
    const uint8_t* src = ptr_off(g_xn, xn_block(rb, kb0) + lane * 16);
#pragma unroll 1
    for (int i = 0; i < 32; i += 4) {
#pragma unroll
        for (int k = 0; k < 4; k++) cp_async16(page + (i + k) * 512, src + (i + k) * 512 + (i >> 4) * (32768 - 8192));
        __nanosleep(200);
    }
    wait_counter(&g_sync.ffn_done, e1);
    const int r = __ldcg(ptr_off(g_sel, (lane >> 4) * 4)) - rb * 64, ch = lane & 15;
    const uint4 t = __ldcg(ptr_off(g_routed, ((lane >> 4) * 128 + kb0 * 8 + ch) * 16));
    asm volatile("cp.async.wait_all;" ::: "memory");
    __syncwarp();
    if (r >= 0 && r < 64)
        sts128(sb + SM_REGION + w * PAGE + (ch >> 3) * 8192 + r * 128 + (((ch & 7) ^ (r & 7)) << 4), t.x, t.y, t.z, t.w);
    __syncwarp();
    if (lane == 0) mbar_arrive(sb + BAR_G + w * 8);
    PROF(20, 2);
}

__device__ __noinline__ void sync_helper(uint32_t sb, int lane, int pair, int c) {
    const unsigned e1 = __ldcg(&g_sync.done) / NCTA + 1;
    const int ib = (pair >> 1) & 7;
    int e = 0, b = 0;
#pragma unroll 1
    for (uint32_t n = 0; (e < 9 || b < 7) && n < SPIN_LIMIT; n++) {
        if (e < 9 && __all_sync(~0u, mbar_test(sb + BAR_DONE + (e & 1) * 8, (e >> 1) & 1))) {
            const int rnd = e > 4, ev = (e - 1) & 3;
            unsigned* flag = e == 0 ? &g_sync.ln
                           : ev < 2 ? ptr_off(g_sync.kv, (rnd * 16 + kv_head(pair) + 8 * ev) * 32)
                                    : ptr_off(g_sync.ctx, (query_rowblock(pair, c, lane & 1, ev & 1) * NH + rnd * 16 + (pair >> 2)) * 4);
            asm volatile("fence.proxy.async.global;\nfence.release.gpu;" ::: "memory");
            if (lane < ((e == 0 || ev < 2) ? 1 : 2)) asm volatile("red.relaxed.gpu.global.add.u32 [%0], 1;" ::"l"(flag) : "memory");
            PROF(10 + e, 2);
            e++;
        }
        if (b < 7 && e > 0 && (b < 4 || (n & POLL_MASK) == 0)) {
            const int i = b == 4 ? lane >> 1 : 8 * b - 24 + ((lane >> 1) & 7);
            const unsigned* cnt = b == 0 ? &g_sync.ln
                                : b == 2 ? ptr_off(g_sync.kvfree, (kv_head(pair) + 8 * (lane & 1)) * 32)
                                : b < 4 ? ptr_off(g_sync.kv, ((b >> 1) * 16 + (pair >> 2)) * 32)
                                        : ptr_off(g_sync.ctx, ((4 * ib + 2 * c + (lane & 1)) * NH + outproj_head(i & 31, ib)) * 4);
            if (__all_sync(~0u, (int)(ld_relaxed(cnt) - e1 * (b == 0 ? NMAIN : b == 2 ? 8 : b < 4 ? 16 : 1)) >= 0)) {
                asm volatile("fence.acquire.gpu;\nfence.proxy.async.global;" ::: "memory");
                __syncwarp();
                if (lane == 0) mbar_arrive(sb + BAR_DEP + b * 8);
                PROF(1 + b, 2);
                b++;
            }
        }
        __nanosleep(150);
    }
}

__device__ __forceinline__ unsigned long long block_max_key(unsigned long long k, unsigned long long* red, int tid) {
#pragma unroll
    for (int o = 16; o; o >>= 1) {
        unsigned long long t = __shfl_xor_sync(~0u, k, o);
        k = t > k ? t : k;
    }
    bar_sync(1, 256);
    if ((tid & 31) == 0) red[tid >> 5] = k;
    bar_sync(1, 256);
    k = red[0];
#pragma unroll
    for (int i = 1; i < 8; i++) k = red[i] > k ? red[i] : k;
    return k;
}

constexpr int FS = FF / 4;
constexpr int FSTAGE = 32768, FNST = 6;
constexpr int FN1 = 2 * (DM / 16), FN2 = FS / 16;

__device__ __forceinline__ void ffn_producer(uint32_t sb, int s, const CUtensorMap* m_gate, const CUtensorMap* m_up,
                                             const CUtensorMap* m_down) {
    const uint64_t pol = policy_evict_first();
    if (FDELAY) wait_counter(&g_sync.ln, (__ldcg(&g_sync.done) / NCTA + 1) * NMAIN);
    int slot = 0, ph = 1;
#pragma unroll 1
    for (int st = 0; st < FN1 + FN2; st++) {
        mbar_sleep(sb + BAR_EMPTY + slot * 8, ph);
        const uint32_t bar = sb + BAR_FULL + slot * 8;
        const bool up = st < FN1;
        mbar_expect_tx(bar, up ? FS * 32 : DM * 32);
        tma_3d_hint(sb + slot * FSTAGE, up ? ((st & 1) ? m_up : m_gate) : m_down, 0,
                    up ? (st >> 1) * 16 : s * FS + (st - FN1) * 16, up ? s * (FS / 64) : 0, bar, pol);
        if (++slot == FNST) { slot = 0; ph ^= 1; }
    }
}

__device__ __forceinline__ void ffn_cta(uint8_t* smem, uint32_t sb, int s, unsigned epoch, const __nv_bfloat16* w_r) {
    const int tid = threadIdx.x, lane = tid & 31;
    const int warp = __shfl_sync(~0u, tid >> 5, 0), w = warp >> 2;
    constexpr uint32_t XB = FNST * FSTAGE, HB = XB + 16384, AUX = HB + 14336;
    unsigned long long* red = reinterpret_cast<unsigned long long*>(smem + AUX);
    unsigned* flag = reinterpret_cast<unsigned*>(smem + AUX + 128);
    const unsigned e1 = epoch + 1;
    for (int i = tid; i < (16384 + 14336) / 16; i += 256) reinterpret_cast<uint4*>(smem + XB)[i] = make_uint4(0, 0, 0, 0);
    {
        float wf[32];
#pragma unroll
        for (int i = 0; i < 4; i++) {
            const uint4 t = __ldg(reinterpret_cast<const uint4*>(w_r) + lane + 32 * i);
            const uint32_t tu[4] = {t.x, t.y, t.z, t.w};
#pragma unroll
            for (int k = 0; k < 4; k++) { wf[8 * i + 2 * k] = bf_lo(tu[k]); wf[8 * i + 2 * k + 1] = bf_hi(tu[k]); }
        }
        if (tid == 0) wait_counter(&g_sync.ln, e1 * NMAIN);
        bar_sync(1, 256);
#pragma unroll 1
        for (int r0 = s * (SEQ / 4) + warp * (SEQ / 32); r0 < s * (SEQ / 4) + (warp + 1) * (SEQ / 32); r0 += 4) {
            uint4 t[4][4];
#pragma unroll
            for (int r = 0; r < 4; r++)
#pragma unroll
                for (int i = 0; i < 4; i++) t[r][i] = __ldcg(reinterpret_cast<const uint4*>(g_xn + image_offset(r0 + r, lane) + i * 131072));
            float acc[4];
#pragma unroll
            for (int r = 0; r < 4; r++) {
                float a = 0.f, b = 0.f;
#pragma unroll
                for (int i = 0; i < 4; i++) {
                    const uint32_t tu[4] = {t[r][i].x, t[r][i].y, t[r][i].z, t[r][i].w};
#pragma unroll
                    for (int k = 0; k < 4; k++) {
                        a = fmaf(bf_lo(tu[k]), wf[8 * i + 2 * k], a);
                        b = fmaf(bf_hi(tu[k]), wf[8 * i + 2 * k + 1], b);
                    }
                }
                acc[r] = a + b;
            }
#pragma unroll
            for (int o = 16; o; o >>= 1)
#pragma unroll
                for (int r = 0; r < 4; r++) acc[r] += __shfl_xor_sync(~0u, acc[r], o);
            if (lane < 4) __stcg(&g_r[r0 + lane], bf_round(lane == 0 ? acc[0] : lane == 1 ? acc[1] : lane == 2 ? acc[2] : acc[3]));
        }
        __threadfence();
        bar_sync(1, 256);
        if (tid == 0) {
            red_release(&g_sync.router);
            wait_counter(&g_sync.router, e1 * 4);
        }
        bar_sync(1, 256);
    }
    unsigned long long keys[8];
    unsigned long long best = 0;
#pragma unroll
    for (int i = 0; i < 8; i++) {
        int idx = tid + 256 * i;
        uint32_t b = __float_as_uint(__ldcg(&g_r[idx]) + 0.0f);
        b = (b & 0x80000000u) ? ~b : (b | 0x80000000u);
        keys[i] = ((unsigned long long)b << 32) | (unsigned)(SEQ - 1 - idx);
        best = keys[i] > best ? keys[i] : best;
    }
    const unsigned long long k0 = block_max_key(best, red, tid);
    best = 0;
#pragma unroll
    for (int i = 0; i < 8; i++) best = (keys[i] != k0 && keys[i] > best) ? keys[i] : best;
    const unsigned long long k1 = block_max_key(best, red, tid);
    const int row = SEQ - 1 - (int)((w ? k1 : k0) & 0xffffffffu);
    const int ch = tid & 127;
    const uint4 xrow = __ldcg(reinterpret_cast<const uint4*>(g_xn + image_offset(row, ch)));
    *reinterpret_cast<uint4*>(smem + XB + (ch >> 3) * 1024 + w * 128 + (((ch & 7) ^ w) << 4)) = xrow;
    fence_async_smem();
    bar_sync(1, 256);
    PROF(20, tid >> 7);
    int slot = 0, ph = 0, prev = 0;
    auto next_stage = [&](bool has_prev) {
        wg_commit();
        wg_wait<1>();
        if (has_prev && lane < 2) mbar_arrive(sb + BAR_EMPTY + prev * 8);
        prev = slot;
        if (++slot == FNST) { slot = 0; ph ^= 1; }
    };
    {
        float ag[28], au[28];
#pragma unroll
        for (int i = 0; i < 28; i++) ag[i] = au[i] = 0.f;
#pragma unroll 1
        for (int ks = 0; ks < DM / 16; ks++) {
            const uint64_t db = make_desc(sb + XB + (ks >> 2) * 1024 + (ks & 3) * 32, 16);
            mbar_wait(sb + BAR_FULL + slot * 8, ph);
            uint64_t da = make_desc(sb + slot * FSTAGE + w * (7 * 2048), 16);
            wg_fence();
#pragma unroll
            for (int b = 0; b < 7; b++) wgmma_n8_ta(ag + 4 * b, da + b * 128, db);
            next_stage(ks > 0);
            mbar_wait(sb + BAR_FULL + slot * 8, ph);
            da = make_desc(sb + slot * FSTAGE + w * (7 * 2048), 16);
            wg_fence();
#pragma unroll
            for (int b = 0; b < 7; b++) wgmma_n8_ta(au + 4 * b, da + b * 128, db);
            next_stage(true);
        }
        wg_wait<0>();
        reg_fence(ag);
        reg_fence(au);
        if ((lane & 3) == 0) {
#pragma unroll
            for (int i = 0; i < 28; i++) {
                const int f = (warp & 3) * 16 + (lane >> 2) + (i & 2) * 4, tok = i & 1;
                const float h = bf_round(silu_f(bf_round(ag[i]))) * bf_round(au[i]);
                *reinterpret_cast<__nv_bfloat16*>(smem + HB + (w * 7 + (i >> 2)) * 1024 + tok * 128 + (((f >> 3) ^ tok) << 4) + (f & 7) * 2) =
                    __float2bfloat16_rn(h);
            }
        }
    }
    fence_async_smem();
    bar_sync(1, 256);
    PROF(21, tid >> 7);
    {
        float ay[32];
#pragma unroll
        for (int i = 0; i < 32; i++) ay[i] = 0.f;
#pragma unroll 1
        for (int ks = 0; ks < FN2; ks++) {
            const uint64_t db = make_desc(sb + HB + (ks >> 2) * 1024 + (ks & 3) * 32, 16);
            mbar_wait(sb + BAR_FULL + slot * 8, ph);
            const uint64_t da = make_desc(sb + slot * FSTAGE + w * (8 * 2048), 16);
            wg_fence();
#pragma unroll
            for (int b = 0; b < 8; b++) wgmma_n8_ta(ay + 4 * b, da + b * 128, db);
            next_stage(true);
        }
        wg_wait<0>();
        reg_fence(ay);
        if ((lane & 3) == 0) {
#pragma unroll
            for (int i = 0; i < 32; i++)
                g_ypart[(s * 2 + (i & 1)) * DM + (w * 8 + (i >> 2)) * 64 + (warp & 3) * 16 + (lane >> 2) + (i & 2) * 4] = ay[i];
        }
    }
    PROF(23, tid >> 7);
    __threadfence();
    bar_sync(1, 256);
    if (tid == 0) {
        *flag = atomicAdd(&g_sync.ffn_ticket, 1u) == epoch * 4 + 3;
        __threadfence();
    }
    bar_sync(1, 256);
    if (*flag) {
        const float sg = bf_round(__fdividef(1.0f, 1.0f + __expf(-__ldcg(&g_r[row]))));
        const uint32_t xu[4] = {xrow.x, xrow.y, xrow.z, xrow.w};
        uint32_t o[4];
#pragma unroll
        for (int k = 0; k < 4; k++) {
            float y0 = 0.f, y1 = 0.f;
#pragma unroll
            for (int q = 0; q < 4; q++) {
                const float2 y = __ldcg(reinterpret_cast<const float2*>(&g_ypart[(q * 2 + w) * DM + ch * 8 + 2 * k]));
                y0 += y.x; y1 += y.y;
            }
            o[k] = pack_bf16(bf_lo(xu[k]) + bf_round(bf_round(y0) * sg), bf_hi(xu[k]) + bf_round(bf_round(y1) * sg));
        }
        g_routed[w * 128 + ch] = make_uint4(o[0], o[1], o[2], o[3]);
        if (ch == 0) g_sel[w] = row;
        bar_sync(1, 256);
        if (tid == 0) red_release(&g_sync.ffn_done);
    }
}

__device__ __forceinline__ uint32_t slab_addr(uint32_t stg, int lane, int s) {
    const int row = ((lane >> 3) & 1) * 8 + (lane & 7);
    const int chunk = 2 * (s & 3) + (lane >> 4);
    return stg + row * 128 + (s >> 2) * 8192 + ((chunk ^ (lane & 7)) << 4);
}

constexpr float SM_SCALE = 0.08838834764831845f * 1.4426950408889634f;
constexpr float SUM_HI = 1048576.f, SUM_LO = 1.0f / 1048576.f;

template <int I0, int I1, int J0>
__device__ __forceinline__ void mask_range(float (&S)[64], float limf) {
#pragma unroll
    for (int i = I0; i < I1; i++) {
        const int j = i >> 2;
        float t;
        asm("add.sat.f32 %0, %1, %2;" : "=f"(t) : "f"((float)(32 * (j >> 2) + 2 * (j & 3) + (i & 1) - (i & 2) * 4)), "f"(-limf));
        S[4 * J0 + i] = fmaf(t, -1e30f, S[4 * J0 + i]);
    }
}
template <int J0>
__device__ __forceinline__ void mask_half(float (&S)[64], float limf, int v) {
    asm volatile("" : "+f"(limf));
    if (v < 2) {
        mask_range<0, 16, J0>(S, limf);
#pragma unroll
        for (int i = 16; i < 32; i++) S[4 * J0 + i] = -1e30f;
    } else {
        mask_range<16, 32, J0>(S, limf);
    }
}
__device__ __forceinline__ void issue_qk(float (&S)[64], const uint32_t (&Q)[32], uint32_t d0) {
#pragma unroll
    for (int s = 0; s < 8; s++)
        wgmma_n128_rs<1>(S, Q[4 * s], Q[4 * s + 1], Q[4 * s + 2], Q[4 * s + 3], d0 + s * 128, s > 0);
}
template <int H>
__device__ __forceinline__ void issue_pv(float (&O)[64], const uint32_t (&Pm)[32], uint32_t d0, int acc) {
#pragma unroll
    for (int s = 4 * H; s < 4 * H + 4; s++)
        wgmma_n128_rs<0>(O, Pm[4 * s], Pm[4 * s + 1], Pm[4 * s + 2], Pm[4 * s + 3], d0 + H * (PAGE >> 4) + (s & 3) * 2, s > 0 ? 1 : acc);
}
template <int J0, int J1>
__device__ __forceinline__ void exp_groups(const float (&S)[64], uint32_t (&Pm)[32], float (&sum)[NSUM]) {
#pragma unroll
    for (int i = 2 * J0; i < 2 * J1; i++) asm volatile("" : "+r"(Pm[i])::"memory");
#pragma unroll
    for (int j = J0; j < J1; j++) {
        const float e0 = ex2(S[4 * j]), e1 = ex2(S[4 * j + 1]), e2 = ex2(S[4 * j + 2]), e3 = ex2(S[4 * j + 3]);
        if (NSUM == 4) {
            sum[0] = j ? sum[0] + e0 : e0; sum[2] = j ? sum[2] + e1 : e1; sum[1] = j ? sum[1] + e2 : e2; sum[3] = j ? sum[3] + e3 : e3;
        } else {
            sum[0] = (j ? sum[0] + e0 : e0) + e1; sum[1] = (j ? sum[1] + e2 : e2) + e3;
        }
        Pm[2 * j] = pack_bf16(e0, e1);
        Pm[2 * j + 1] = pack_bf16(e2, e3);
    }
}
__device__ __forceinline__ void shift_rows(float (&S)[64], float d0, float d1) {
#pragma unroll
    for (int j = 0; j < 16; j++) {
        S[4 * j] -= d0; S[4 * j + 1] -= d0; S[4 * j + 2] -= d1; S[4 * j + 3] -= d1;
    }
}
__device__ constexpr int chunk_src(int i) { return 4 * (4 * (i >> 3) + (i & 3)) + 2 * ((i >> 2) & 1); }
enum : uint32_t { CTL_FIRST = 1, CTL_SWITCH = 2, CTL_LAST = 4, CTL_HALF = 128, CTL_MASKHI = 256, CTL_WOUT = 512, CTL_PVHALF = 1024, CTL_PVACC = 16384,
                  CTL_SHIFT = 32768 };
__device__ __forceinline__ float quad_sum(float v) {
    v += __shfl_xor_sync(~0u, v, 1);
    return v + __shfl_xor_sync(~0u, v, 2);
}

__device__ __forceinline__ void store_part(uint8_t* base, uint32_t row_bits, int p, const uint32_t (&pk)[64]) {
    asm volatile("{\n.reg .b64 d0, d1;\nxor.b64 d0, %0, %1;\nxor.b64 d1, d0, 64;\n"
                 "TS: .branchtargets P0, P1, P2, P3, P4, P5, P6, P7;\n"
                 "brx.idx.uni %2, TS;\n"
                 "P0:\n st.global.cg.v4.u32 [d0 + 0], {%3, %4, %5, %6};\n st.global.cg.v4.u32 [d1 + 0], {%11, %12, %13, %14};\n bra.uni DONE;\n"
                 "P1:\n st.global.cg.v4.u32 [d0 + 0], {%7, %8, %9, %10};\n st.global.cg.v4.u32 [d1 + 0], {%15, %16, %17, %18};\n bra.uni DONE;\n"
                 "P2:\n st.global.cg.v4.u32 [d0 + 16384], {%19, %20, %21, %22};\n st.global.cg.v4.u32 [d1 + 16384], {%27, %28, %29, %30};\n bra.uni DONE;\n"
                 "P3:\n st.global.cg.v4.u32 [d0 + 16384], {%23, %24, %25, %26};\n st.global.cg.v4.u32 [d1 + 16384], {%31, %32, %33, %34};\n bra.uni DONE;\n"
                 "P4:\n st.global.cg.v4.u32 [d0 + 65536], {%35, %36, %37, %38};\n st.global.cg.v4.u32 [d1 + 65536], {%43, %44, %45, %46};\n bra.uni DONE;\n"
                 "P5:\n st.global.cg.v4.u32 [d0 + 65536], {%39, %40, %41, %42};\n st.global.cg.v4.u32 [d1 + 65536], {%47, %48, %49, %50};\n bra.uni DONE;\n"
                 "P6:\n st.global.cg.v4.u32 [d0 + 81920], {%51, %52, %53, %54};\n st.global.cg.v4.u32 [d1 + 81920], {%59, %60, %61, %62};\n bra.uni DONE;\n"
                 "P7:\n st.global.cg.v4.u32 [d0 + 81920], {%55, %56, %57, %58};\n st.global.cg.v4.u32 [d1 + 81920], {%63, %64, %65, %66};\n bra.uni DONE;\n"
                 "DONE:\n}\n"
                 ::"l"(base), "l"((uint64_t)((p & 1) ? row_bits : 0)), "r"(p), "r"(pk[0]), "r"(pk[1]), "r"(pk[2]), "r"(pk[3]), "r"(pk[4]), "r"(pk[5]), "r"(pk[6]), "r"(pk[7]), "r"(pk[8]), "r"(pk[9]), "r"(pk[10]), "r"(pk[11]), "r"(pk[12]), "r"(pk[13]), "r"(pk[14]), "r"(pk[15]), "r"(pk[16]), "r"(pk[17]), "r"(pk[18]), "r"(pk[19]), "r"(pk[20]), "r"(pk[21]), "r"(pk[22]), "r"(pk[23]), "r"(pk[24]), "r"(pk[25]), "r"(pk[26]), "r"(pk[27]), "r"(pk[28]), "r"(pk[29]), "r"(pk[30]), "r"(pk[31]), "r"(pk[32]), "r"(pk[33]), "r"(pk[34]), "r"(pk[35]), "r"(pk[36]), "r"(pk[37]), "r"(pk[38]), "r"(pk[39]), "r"(pk[40]), "r"(pk[41]), "r"(pk[42]), "r"(pk[43]), "r"(pk[44]), "r"(pk[45]), "r"(pk[46]), "r"(pk[47]), "r"(pk[48]), "r"(pk[49]), "r"(pk[50]), "r"(pk[51]), "r"(pk[52]), "r"(pk[53]), "r"(pk[54]), "r"(pk[55]), "r"(pk[56]), "r"(pk[57]), "r"(pk[58]), "r"(pk[59]), "r"(pk[60]), "r"(pk[61]), "r"(pk[62]), "r"(pk[63])
                 : "memory");
}

__device__ __forceinline__ void consumer(uint32_t sb, int pair, int c, const CUtensorMap* m_out, const uint8_t* x) {
    const int tid = threadIdx.x;
    const int warp = __shfl_sync(~0u, tid >> 5, 0);
    const int w = warp >> 2, v = warp & 3, lane = tid & 31;

    const uint32_t empty_rel = lane == 2 ? mapa(sb + BAR_EMPTYL, c) : mapa(sb + BAR_EMPTY, lane & 1);
    auto release = [&](uint32_t grp) {
        if (lane < 3) mbar_arrive_cluster(empty_rel + (grp & 7) * 8);
    };
    auto wait_full = [&](uint32_t grp) { mbar_wait(sb + BAR_FULL + (grp & 7) * 8, (grp >> 3) & 1); };

    uint32_t g = 0;
    const uint32_t stg = sb + SM_REGION + w * PAGE + v * 2048;
    const uint32_t chunk0 = (lane >> 2) * 128 + (((lane & 3) ^ (lane >> 2)) << 4);
    uint32_t ndone = 0;
    auto mark_done = [&]() {
        __syncwarp();
        if (lane == 0) mbar_arrive(sb + BAR_DONE + (ndone & 1) * 8);
        ndone++;
    };
    auto ctx_dst = [&](int rnd, int seg) {
        const int rb = query_rowblock(pair, c, w, seg);
        return ptr_off(g_ctx, ((rb >> 1) * 64 + (rnd * 16 + (pair >> 2)) * 2) * PAGE + (rb & 1) * 8192 + v * 2048);
    };

    uint32_t ctl_tab;
    {
        const int t = lane, firstB = 2 * attn_rowblock(pair, 0) + 2 - w;
        auto is_half = [&](int u) { return (u == firstB - 1 || u == 16) && c == (u >= firstB); };
        auto block = [&](int u) { return u + (w == 1 && u >= firstB); };
        auto place = [](int j) { return ((j & 15) << 3) | ((j - (j * 43 >> 8) * 6) << 11); };
        const int jv = min(2 * block(t - 1) + 2, 35), jk = t == 17 ? jv : max(2 * block(t) - 1, 0);
        const bool diag = t == firstB - 1 || t == 16;
        ctl_tab = ((t == 0 || t == firstB) ? CTL_FIRST : 0) | (t == firstB ? CTL_SWITCH : 0) | (t == 17 ? CTL_LAST : 0) |
                  (diag ? (is_half(t) ? CTL_HALF : CTL_MASKHI) : 0) | (t == firstB + 1 ? CTL_WOUT : 0) |
                  (is_half(t - 1) ? CTL_PVHALF : 0) | ((t == 1 || t == firstB + 1) ? 0 : CTL_PVACC) |
                  place(jk) | ((place(jv) | (t ? 3 : 0)) << 16);
    }

    uint32_t pk[64];
#pragma unroll
    for (int i = 0; i < 64; i++) pk[i] = 0;
    uint8_t* pend = nullptr;
    uint32_t prow = 0x400;
    auto write_part = [&](int p) { store_part(pend, prow, p, pk); };
    if (w == 1) bar_arrive(2, 256);

    for (int item = 0; item < 6; item++) {
        if (ACOND) {
            constexpr int nk = DC / 64;
            float acc[128];
            auto issue_kblock = [&](int first_acc) {
                wait_full(g);
                const uint32_t pg = sb + (g & 3) * (3 * PAGE);
                const uint64_t da = make_desc(pg + w * 8192, 16), db = make_desc(pg + PAGE, 16);
                wg_fence();
                wgmma_n256_ss(acc, da, db, first_acc);
                wgmma_n256_ss(acc, da + 128, db + 2, 1);
                wgmma_n256_ss(acc, da + 256, db + 4, 1);
                wgmma_n256_ss(acc, da + 384, db + 6, 1);
                wg_commit();
                g++;
            };
            if (item == 0) PROF(17, w);
            issue_kblock(0);
            if (item == 0) PROF(1, w);
            if (item == 0 && w == 0) PROF_GT(1);
            const int nparts = item == 0 ? 0 : (item == 3 ? 4 : 8);
            const int ln_row = (pair * 2 + c) * 16 + warp * 2;
            auto load_x = [&]() {
                const uint8_t* src = ptr_off(x, ln_row * (DM * 2) + lane * 16);
#pragma unroll
                for (int i = 0; i < 8; i++) {
                    const uint4 t = __ldcg(reinterpret_cast<const uint4*>(src + i * 512));
                    pk[4 * i] = t.x; pk[4 * i + 1] = t.y; pk[4 * i + 2] = t.z; pk[4 * i + 3] = t.w;
                }
            };
            if (XAT == 1 && item == 0) load_x();
#pragma unroll 1
            for (int kb = 1; kb < nk; kb++) {
                if (kb == nk - 1 && w == 1) bar_sync(4, 256);
                issue_kblock(1);
                if (kb == nk - 1 && w == 0) bar_arrive(4, 256);
                wg_wait<1>();
                release(g - 2);
                if (kb <= nparts) {
                    if (item == 4 && kb == 1) mbar_wait(sb + BAR_DEP + 16, 0);
                    write_part(kb - 1);
                    if (kb == nk - 1) write_part(nk - 1);
                    if (kb == nparts || kb == nk - 1) mark_done();
                }
                if (g <= 8) {
                    if (XAT > 1 && g == XAT) load_x();
                    float s[2], q[2];
                    if (g == 4 + (LNSH > 0)) {
                        ln_sums<0>(pk, s[0], q[0]);
                        pk[32] = __float_as_uint(s[0]); pk[33] = __float_as_uint(q[0]);
                    }
                    if (g == 5 + (LNSH == 2)) {
                        ln_sums<16>(pk, s[1], q[1]);
                        pk[34] = __float_as_uint(s[1]); pk[35] = __float_as_uint(q[1]);
                    }
                    if (g == 6) {
#pragma unroll
                        for (int r = 0; r < 2; r++) { s[r] = __uint_as_float(pk[32 + 2 * r]); q[r] = __uint_as_float(pk[33 + 2 * r]); }
                        const bool hi = lane & 16, od = lane & 8;
                        float a = hi ? s[1] : s[0], b = hi ? q[1] : q[0];
                        a += __shfl_xor_sync(~0u, hi ? s[0] : s[1], 16);
                        b += __shfl_xor_sync(~0u, hi ? q[0] : q[1], 16);
                        float t = od ? b : a;
                        t += __shfl_xor_sync(~0u, od ? a : b, 8);
#pragma unroll
                        for (int o = 4; o; o >>= 1) t += __shfl_xor_sync(~0u, t, o);
#pragma unroll
                        for (int r = 0; r < 2; r++) {
                            s[r] = __shfl_sync(~0u, t, 16 * r);
                            q[r] = __shfl_sync(~0u, t, 16 * r + 8);
                        }
                        ln_finish(s[0], q[0], pk[36], pk[37], pk[38]);
                        ln_finish(s[1], q[1], pk[39], pk[40], pk[41]);
                    }
                    if (g == 7) ln_apply<0>(pk, pk[36], pk[37], pk[38], ptr_off(g_xn, image_offset(ln_row, lane)));
                    if (g == 8) {
                        ln_apply<16>(pk, pk[39], pk[40], pk[41], ptr_off(g_xn, image_offset(ln_row + 1, lane)));
                        mark_done();
                    }
                }
            }
            wg_wait<0>();
            reg_fence(acc);
            release(g - 1);
            PROF(2 + 2 * item, w);
            if (w == 0) PROF_GT(2 + 2 * item);
            const float ksc = (QSCALE || c) ? 1.0f : SM_SCALE;
#pragma unroll
            for (int i = 0; i < 64; i++) pk[i] = pack_bf16(acc[chunk_src(i)] * ksc, acc[chunk_src(i) + 1] * ksc);
            const uint32_t vrow = (v >> 1) * 32 + (lane >> 3) * 8 + (v & 1) * 4 + ((lane >> 2) & 1);
            pend = ptr_off(g_kv, ((kv_head(pair) + (item == 1 || item == 4 ? 8 : 0)) * 16 + kv_tokens(pair) * 2) * 65536 + w * 8192 +
                                     (c ? 32768 + vrow * 128 + (((lane & 3) ^ (vrow & 7)) << 4) : v * 2048 + chunk0));
            prow = c ? 0x120 : 0x400;
            PROF(3 + 2 * item, w);
            continue;
        }

        float O[64], S[64];
        auto issue_q = [&](int first_acc) {
            wait_full(g);
            const uint32_t pg = sb + (g & 3) * (3 * PAGE);
            const uint64_t da = make_desc(pg + w * 8192, 16), db = make_desc(pg + 2 * PAGE, 8192);
            const uint64_t dab = make_desc(pg + PAGE + (1 - w) * 8192, 16);
            wg_fence();
#pragma unroll
            for (int q = 0; q < 4; q++) wgmma_n128_ss(S, da + 2 * q, db + 128 * q, q ? 1 : first_acc);
            wg_commit();
#pragma unroll
            for (int q = 0; q < 4; q++) wgmma_n128_ss(O, dab + 2 * q, db + 128 * q, q ? 1 : first_acc);
            wg_commit();
            g++;
        };
        issue_q(0);
#pragma unroll 1
        for (int kb = 1; kb < DM / 64; kb++) {
            if (kb == DM / 64 - 2 && w == 1) bar_sync(4, 256);
            issue_q(1);
            if (kb == DM / 64 - 1 && w == 0) bar_arrive(4, 256);
            wg_wait<QSPLIT ? 2 : 1>();
            release(g - 2);
            if (kb <= 8) {
                write_part(kb - 1);
                if (kb == 8) mark_done();
            }
        }
        uint32_t Q[32], Pm[32];
#pragma unroll
        for (int i = 0; i < 32; i++) Pm[i] = PMINIT ? pk[i] : 0;
        float lim = (float)(v * 16 + (lane >> 2) - 8 * (lane & 3));
        float mc[2] = {0.f, 0.f}, l[2] = {0.f, 0.f}, scale[2] = {0.f, 0.f}, sum[NSUM];
        uint32_t ctl = __shfl_sync(~0u, ctl_tab, 0), nxt = __shfl_sync(~0u, ctl_tab, 1);
        int t = 1;
        asm volatile("" : "+f"(lim), "+f"(mc[0]), "+f"(mc[1]), "+f"(l[0]), "+f"(l[1]), "+r"(ctl), "+r"(nxt), "+r"(t));
        constexpr float qsc = QSCALE ? SM_SCALE : 1.0f;
        wg_wait<QSPLIT ? 1 : 0>();
        reg_fence(S);
#pragma unroll
        for (int i = 0; i < 32; i++) Q[i] = pack_bf16(S[2 * i] * qsc, S[2 * i + 1] * qsc);
        reg_fence(Q);
        wait_full(g);
        wg_wait<0>();
        reg_fence(O);
        release(g - 1);
        PROF(2 + 2 * item, w);
        if (w == 0) PROF_GT(2 + 2 * item);

        const uint32_t qaddr = QOPQ ? __shfl_sync(~0u, stg + lane * 16, lane) : stg + lane * 16;
        auto put_queries = [&](const float (&A)[64]) {
#pragma unroll
            for (int i = 0; i < 8; i++)
                sts128(qaddr + (i >> 2) * 8192 + (i & 3) * 512, pack_bf16(A[8 * i] * qsc, A[8 * i + 1] * qsc), pack_bf16(A[8 * i + 2] * qsc, A[8 * i + 3] * qsc),
                       pack_bf16(A[8 * i + 4] * qsc, A[8 * i + 5] * qsc), pack_bf16(A[8 * i + 6] * qsc, A[8 * i + 7] * qsc));
        };
        auto get_queries = [&](int i0, int i1) {
#pragma unroll
            for (int i = i0; i < i1; i++) lds128(qaddr + (i >> 2) * 8192 + (i & 3) * 512, Q[4 * i], Q[4 * i + 1], Q[4 * i + 2], Q[4 * i + 3]);
        };
        const uint32_t kdesc0 = (uint32_t)make_desc(sb, PAGE), vdesc0 = (uint32_t)make_desc(sb, 16);
        auto wait_block = [&](uint32_t word) { mbar_wait(sb + BAR_FULL + (word & 56), (word >> 6) & 1); };
        auto write_out = [&](auto early) {
            uint8_t* dst = ctx_dst(item == 5, 0);
            uint8_t* d[2] = {ptr_off(dst, chunk0), ptr_off(dst, chunk0 ^ 64)};
#pragma unroll
            for (int i = early.value ? 0 : WN; i < (early.value ? WN : 8); i++) {
                const float sc = scale[i & 1];
                uint32_t q[4];
#pragma unroll
                for (int k = 0; k < 4; k++) q[k] = pack_bf16(O[chunk_src(4 * i + k)] * sc, O[chunk_src(4 * i + k) + 1] * sc);
                if (WINP && early.value && i > 0) {
#pragma unroll
                    for (int k = 0; k < 4; k++) O[4 * (i - 1) + k] = __uint_as_float(q[k]);
                }
                __stcg(reinterpret_cast<uint4*>(d[(i >> 1) & 1] + (i >> 2) * PAGE + (i & 1) * 1024), make_uint4(q[0], q[1], q[2], q[3]));
            }
            if (early.value == (WN == 8)) mark_done();
        };
        put_queries(O);
        bar_sync(2 + w, 256);
        wg_fence();
        issue_qk(S, Q, kdesc0);
        wg_commit();
        wg_fence();
        wg_commit();
        wg_commit();
        bar_arrive(3 - w, 256);
        for (;;) {
            const bool kready = KTRY ? mbar_try(sb + BAR_FULL + (nxt & 56), (nxt >> 6) & 1) : true;
            if (!KTRY) wait_block(nxt);
            wg_wait<2>();
            reg_fence(S);
            if (ctl & (CTL_HALF | CTL_MASKHI | CTL_SHIFT)) {
                if (LQN < 8 && (nxt & CTL_SWITCH)) get_queries(LQN, 8);
                if (ctl & CTL_HALF) mask_half<0>(S, lim, v);
                if (ctl & CTL_MASKHI) mask_half<8>(S, lim, v);
                if (ctl & CTL_SHIFT) shift_rows(S, mc[0], mc[1]);
            }
            float early[4 * EARLY + 1];
#pragma unroll
            for (int j = 0; j < EARLY; j++) {
#pragma unroll
                for (int i = 4 * j; i < 4 * j + 4; i++) early[i] = ex2(S[i]);
                sum[0] = (j ? sum[0] + early[4 * j] : early[4 * j]) + early[4 * j + 1];
                sum[1] = (j ? sum[1] + early[4 * j + 2] : early[4 * j + 2]) + early[4 * j + 3];
            }
            const uint32_t tie = EARLY ? __float_as_uint(sum[0]) & __float_as_uint(sum[1]) & (ctl & 0x80000000u) : 0;
            if (lane < 3) mbar_arrive_cluster(empty_rel + tie + (ctl & 56));
            wg_wait<1>();
#pragma unroll
            for (int j = 0; j < EARLY; j++) {
                asm volatile("" : "+r"(Pm[2 * j]), "+r"(Pm[2 * j + 1])::"memory");
                Pm[2 * j] = pack_bf16(early[4 * j], early[4 * j + 1]);
                Pm[2 * j + 1] = pack_bf16(early[4 * j + 2], early[4 * j + 3]);
            }
            exp_groups<EARLY, 8>(S, Pm, sum);
            const bool half = ctl & CTL_HALF;
            if (!half) {
                wg_wait<0>();
                reg_fence(O);
                if (lane < ((ctl >> 16) & 3)) mbar_arrive_cluster(empty_rel + ((ctl >> 16) & 56));
                exp_groups<8, 16>(S, Pm, sum);
            } else {
                asm volatile("wgmma.wait_group.sync.aligned 0;\n" ::: "memory");
                reg_fence(O);
                if (lane < ((ctl >> 16) & 3)) asm volatile("mbarrier.arrive.shared::cluster.b64 _, [%0];\n" ::"r"(empty_rel + ((ctl >> 16) & 56)) : "memory");
            }
            if (NSUM == 4) { sum[0] += sum[2]; sum[1] += sum[3]; }
            const bool over = !(sum[0] + sum[1] <= SUM_HI);
            if (__any_sync(~0u, over || !kready) || (((ctl & CTL_FIRST) | (nxt & (CTL_SWITCH | CTL_LAST))) != 0)) {
                bool bad = __any_sync(~0u, over);
                if (KTRY && !kready) wait_block(nxt);
                const bool first = ctl & CTL_FIRST;
                if (first) {
                    uint32_t b0 = __ballot_sync(~0u, sum[0] >= SUM_LO), b1 = __ballot_sync(~0u, sum[1] >= SUM_LO);
                    b0 |= b0 >> 1; b1 |= b1 >> 1;
                    b0 |= b0 >> 2; b1 |= b1 >> 2;
                    bad |= (b0 & b1 & 0x11111111u) != 0x11111111u;
                }
                if (bad) {
                    if (half) {
#pragma unroll
                        for (int i = 32; i < 64; i++) S[i] = -INFINITY;
                    }
                    float d0 = fmaxf(S[0], S[1]), d1 = fmaxf(S[2], S[3]);
#pragma unroll
                    for (int j = 1; j < 16; j++) {
                        d0 = fmaxf(d0, fmaxf(S[4 * j], S[4 * j + 1]));
                        d1 = fmaxf(d1, fmaxf(S[4 * j + 2], S[4 * j + 3]));
                    }
                    d0 = fmaxf(d0, __shfl_xor_sync(~0u, d0, 1));
                    d1 = fmaxf(d1, __shfl_xor_sync(~0u, d1, 1));
                    d0 = fmaxf(d0, __shfl_xor_sync(~0u, d0, 2));
                    d1 = fmaxf(d1, __shfl_xor_sync(~0u, d1, 2));
                    if (!first) {
                        d0 = fmaxf(d0, 0.f);
                        d1 = fmaxf(d1, 0.f);
                        const float a0 = ex2(-d0), a1 = ex2(-d1);
#pragma unroll
                        for (int j = 0; j < 16; j++) {
                            O[4 * j] *= a0; O[4 * j + 1] *= a0; O[4 * j + 2] *= a1; O[4 * j + 3] *= a1;
                        }
                        l[0] *= a0; l[1] *= a1;
                    }
                    mc[0] += d0; mc[1] += d1;
                    ctl_tab |= CTL_SHIFT;
                    nxt |= CTL_SHIFT;
                    shift_rows(S, d0, d1);
                    exp_groups<0, 16>(S, Pm, sum);
                    if (NSUM == 4) { sum[0] += sum[2]; sum[1] += sum[3]; }
                }
                if (WN && (ctl & CTL_SWITCH)) write_out(std::true_type());
                if (nxt & CTL_LAST) break;
                if (nxt & CTL_SWITCH) {
                    get_queries(0, LQN);
                    nxt &= ~CTL_SHIFT;
                    ctl_tab &= ~CTL_SHIFT;
                }
            }
            ctl = nxt;
            bar_sync(2 + w, 256);
            wg_fence();
            issue_qk(S, Q, kdesc0 + (ctl & 0x3800));
            wg_commit();
            l[0] += sum[0]; l[1] += sum[1];
            nxt = __shfl_sync(~0u, ctl_tab, ++t);
            if (ctl & (CTL_SWITCH | CTL_WOUT)) {
                if (ctl & CTL_SWITCH) {
                    scale[0] = rcp_approx(quad_sum(l[0]));
                    scale[1] = rcp_approx(quad_sum(l[1]));
                    l[0] = l[1] = mc[0] = mc[1] = 0.f;
                    if (w == 1) { release((ctl >> 3) - 2); release((ctl >> 3) + 1); }
                } else {
                    write_out(std::false_type());
                }
            }
            wait_block(ctl >> 16);
            const uint32_t vdesc = vdesc0 + ((ctl >> 16) & 0x3800);
            if (!(ctl & CTL_PVHALF)) {
                wg_fence();
                issue_pv<0>(O, Pm, vdesc, ctl & CTL_PVACC);
                wg_commit();
                issue_pv<1>(O, Pm, vdesc, 1);
                wg_commit();
            } else {
                wg_fence();
                issue_pv<0>(O, Pm, vdesc, ctl & CTL_PVACC);
                wg_commit();
                wg_commit();
            }
            bar_arrive(3 - w, 256);
        }
        g += 36;
        if (w == 0) release(g - 3);
        if (WN < 8 && (nxt & CTL_WOUT)) write_out(std::false_type());
        const uint32_t vdesc = vdesc0 + (nxt & 0x3800);
        if (nxt & CTL_PVHALF) {
            wg_fence();
            issue_pv<0>(O, Pm, vdesc, nxt & CTL_PVACC);
            wg_commit();
        } else {
            wg_fence();
            issue_pv<0>(O, Pm, vdesc, nxt & CTL_PVACC);
            issue_pv<1>(O, Pm, vdesc, 1);
            wg_commit();
        }
        l[0] += sum[0]; l[1] += sum[1];
        ctl_tab = (ctl_tab & ~(0x00780078u | CTL_SHIFT)) | ((ctl_tab + 0x00200020u) & 0x00780078u);
        const float i0 = rcp_approx(quad_sum(l[0])), i1 = rcp_approx(quad_sum(l[1]));
        wg_wait<0>();
        reg_fence(O);
        if (w == 0) release(g - 2);
        release(g - 1);
#pragma unroll
        for (int i = 0; i < 32; i++) {
            const float sc = (i & 4) ? i1 : i0;
            pk[i] = pack_bf16(O[chunk_src(i)] * sc, O[chunk_src(i) + 1] * sc);
        }
        pend = ptr_off(ctx_dst(item == 5, 1), chunk0);
        prow = 0x400;
#pragma unroll
        for (int i = 32; i < 64; i++) pk[i] = 0;
        PROF(3 + 2 * item, w);
        if (w == 0) PROF_GT(3 + 2 * item);
    }

    float acc[64];
    uint32_t slot = 0;
    auto issue_out = [&](int first_acc) {
        wait_full(g);
        const uint64_t da = make_desc(sb + slot + w * 8192, 16), db = make_desc(sb + slot + PAGE, 8192);
        wg_fence();
#pragma unroll
        for (int q = 0; q < 4; q++) wgmma_n128_ss(acc, da + 2 * q, db + 128 * q, q ? 1 : first_acc);
        wg_commit();
        g++;
        slot = slot == SM_REGION - 2 * PAGE ? 0 : slot + 2 * PAGE;
    };
    issue_out(0);
#pragma unroll 1
    for (int kb = 1; kb < 64; kb++) {
        issue_out(1);
        wg_wait<1>();
        release(g - 2);
        if (kb <= 8 && !(kb & 1)) {
            write_part((kb >> 1) - 1);
            if (kb == 8) mark_done();
        }
        if (kb >= 32 && (kb & 3) == 2 * w) {
            uint32_t u0, u1, u2, u3;
            const uint32_t a = stg + (kb & 16) * 512 + (kb & 12) * 128 + lane * 16;
            mbar_wait(sb + BAR_G + w * 8, 0);
            lds128(a, u0, u1, u2, u3);
            sts128(a, pack_bf16(silu_f(bf_lo(u0)), silu_f(bf_hi(u0))), pack_bf16(silu_f(bf_lo(u1)), silu_f(bf_hi(u1))),
                   pack_bf16(silu_f(bf_lo(u2)), silu_f(bf_hi(u2))), pack_bf16(silu_f(bf_lo(u3)), silu_f(bf_hi(u3))));
        }
    }
    wait_full(g);
    __syncwarp();
    const uint32_t xs = sb + slot + w * PAGE + v * 2048;
    uint32_t xr[32], gr[32];
#pragma unroll
    for (int s = 0; s < 8; s++) {
        ldmatrix_x4(slab_addr(xs, lane, s), xr[4 * s], xr[4 * s + 1], xr[4 * s + 2], xr[4 * s + 3]);
        ldmatrix_x4(slab_addr(stg, lane, s), gr[4 * s], gr[4 * s + 1], gr[4 * s + 2], gr[4 * s + 3]);
    }
    wg_wait<0>();
    reg_fence(acc);
    PROF(14, w);
    if (w == 0) PROF_GT(14);
#pragma unroll
    for (int s = 0; s < 8; s++) {
        uint32_t o[4];
#pragma unroll
        for (int k = 0; k < 4; k++)
            o[k] = bf2_add(xr[4 * s + k], bf2_mul(pack_bf16(acc[8 * s + 2 * k], acc[8 * s + 2 * k + 1]), gr[4 * s + k]));
        stmatrix_x4(slab_addr(stg, lane, s), o[0], o[1], o[2], o[3]);
    }
    fence_async_smem();
    __syncwarp();
    PROF(28, w);
    if (lane == 0) {
        const int orow = ((pair >> 1) & 7) * 256 + c * 128 + w * 64 + v * 16, ocol = (pair >> 4) * 256 + (pair & 1) * 128;
        tma_store_2d(m_out, ocol, orow, stg);
        tma_store_2d(m_out, ocol + 64, orow, stg + 8192);
        bulk_commit();
        bulk_wait_read();
    }
    __syncwarp();
}

__global__ void __cluster_dims__(2, 1, 1) __launch_bounds__(384, 1)
fused_kernel(const __grid_constant__ CUtensorMap m_ckv, const __grid_constant__ CUtensorMap m_wuk,
             const __grid_constant__ CUtensorMap m_wuv, const __grid_constant__ CUtensorMap m_wq,
             const __grid_constant__ CUtensorMap m_wo, const __grid_constant__ CUtensorMap m_x,
             const __grid_constant__ CUtensorMap m_out, const __grid_constant__ CUtensorMap m_gate,
             const __grid_constant__ CUtensorMap m_up, const __grid_constant__ CUtensorMap m_down, const Params P) {
    extern __shared__ __align__(1024) uint8_t smem[];
    const uint32_t sb = __shfl_sync(~0u, smem_u32(smem), 0);
    const int tid = threadIdx.x;
    const int cl = blockIdx.x >> 1, c = blockIdx.x & 1;
    const int pair = cl >= 64 ? cl : cl < 4 ? cl * 16 + 15 : cl < 36 ? ((cl - 4) >> 3) * 16 + ((cl - 4) & 7)
                                                                    : ((cl - 36) / 7) * 16 + 8 + (cl - 36) % 7;
    const bool starter = tid == 256 && pair < NMAIN / 2;
    const CUtensorMap* m_wu = c ? &m_wuv : &m_wuk;
    if (tid == 256) {
        mbar_init(sb + BAR_FULL, 1);
        if (starter) {
            asm volatile("fence.mbarrier_init.release.cluster;" ::: "memory");
            mbar_expect_tx(sb + BAR_FULL, 3 * PAGE);
            tma_3d(sb, m_wu, 0, 0, kv_head(pair) * 2, sb + BAR_FULL);
            tma_3d(sb + PAGE, &m_ckv, 0, kv_tokens(pair) * 256, 0, sb + BAR_FULL);
            tma_3d(sb + 2 * PAGE, &m_ckv, 0, kv_tokens(pair) * 256 + 128, 0, sb + BAR_FULL);
        }
#pragma unroll
        for (int i = START == 2; i < NBAR; i++) mbar_init(sb + SM_BAR + i * 8, (i >> 3) == 1 ? 16 : i >= 25 ? 8 : 1);
        asm volatile("fence.mbarrier_init.release.cluster;" ::: "memory");
    }
    if (starter) {
        if (START != 2) prefetch_map(&m_ckv);
        if (START == 1) mbar_arrive(sb + BAR_FULL);
#pragma unroll 1
        for (int kb = START ? 1 : 0; kb < 4; kb++) {
            mbar_expect_tx(sb + BAR_FULL + kb * 8, 3 * PAGE);
            if (kb < EARLYW) tma_3d(sb + kb * (3 * PAGE), m_wu, 0, kb * 64, kv_head(pair) * 2, sb + BAR_FULL + kb * 8);
        }
    }
    PROF(18, (tid >> 7) & 1);
    __syncthreads();
    cluster_sync();
    PROF(22, (tid >> 7) & 1);
    auto start_loads = [&]() {
#pragma unroll 1
        for (int kb = START ? 1 : 0; kb < 4; kb++) {
            if (kb >= EARLYW) tma_3d(sb + kb * (3 * PAGE), m_wu, 0, kb * 64, kv_head(pair) * 2, sb + BAR_FULL + kb * 8);
            tma_3d_mc(sb + kb * (3 * PAGE) + (1 + c) * PAGE, &m_ckv, 0, kv_tokens(pair) * 256 + c * 128, kb, sb + BAR_FULL + kb * 8);
        }
    };
    if (!LATEMC && starter) start_loads();
    PROF(19, (tid >> 7) & 1);
    const int warp = __shfl_sync(~0u, tid >> 5, 0), lane = tid & 31;
    auto finish = [&]() {
        PROF(29, tid >> 7);
        cluster_sync();
        if (tid == 0) atomicAdd(&g_sync.done, 1u);
    };
    if (pair >= NMAIN / 2) {
        if (warp < 8) ffn_cta(smem, sb, blockIdx.x - NMAIN, __ldcg(&g_sync.done) / NCTA, P.w_r);
        else if (tid == 256) ffn_producer(sb, blockIdx.x - NMAIN, &m_gate, &m_up, &m_down);
        __syncwarp();
        finish();
    } else if (warp < 8) {
        asm volatile("setmaxnreg.inc.sync.aligned.u32 232;");
        consumer(sb, pair, c, &m_out, (const uint8_t*)P.x);
        finish();
    } else {
        asm volatile("setmaxnreg.dec.sync.aligned.u32 40;");
        if (LATEMC && starter) start_loads();
        if (warp == 10) {
            sync_helper(sb, lane, pair, c);
        } else if (warp & 1) {
            fetch_helper((warp & 2) ? P.w_uv : P.w_uk, sb, (warp >> 1) & 1, lane, pair, c);
        } else {
            producer(P, sb, pair, c, &m_ckv, m_wu, &m_wq, &m_wo, &m_x, &m_out);
        }
        cluster_sync();
    }
}

typedef CUresult (*EncodeFn)(CUtensorMap*, CUtensorMapDataType, cuuint32_t, void*, const cuuint64_t*, const cuuint64_t*,
                             const cuuint32_t*, const cuuint32_t*, CUtensorMapInterleave, CUtensorMapSwizzle,
                             CUtensorMapL2promotion, CUtensorMapFloatOOBfill);

void make_map_2d(EncodeFn fn, CUtensorMap* m, const void* ptr, int rows, int cols, int box_rows) {
    cuuint64_t dims[2] = {(cuuint64_t)cols, (cuuint64_t)rows};
    cuuint64_t strides[1] = {(cuuint64_t)cols * 2};
    cuuint32_t box[2] = {64, (cuuint32_t)box_rows};
    cuuint32_t es[2] = {1, 1};
    fn(m, CU_TENSOR_MAP_DATA_TYPE_BFLOAT16, 2, const_cast<void*>(ptr), dims, strides, box, es, CU_TENSOR_MAP_INTERLEAVE_NONE,
       CU_TENSOR_MAP_SWIZZLE_128B, CU_TENSOR_MAP_L2_PROMOTION_L2_256B, CU_TENSOR_MAP_FLOAT_OOB_FILL_NONE);
}
void make_map_w(EncodeFn fn, CUtensorMap* m, const void* ptr, int rows, int cols, int blocks, int box_rows = 32) {
    cuuint64_t dims[3] = {64, (cuuint64_t)rows, (cuuint64_t)cols / 64};
    cuuint64_t strides[2] = {(cuuint64_t)cols * 2, 128};
    cuuint32_t box[3] = {64, (cuuint32_t)box_rows, (cuuint32_t)blocks};
    cuuint32_t es[3] = {1, 1, 1};
    fn(m, CU_TENSOR_MAP_DATA_TYPE_BFLOAT16, 3, const_cast<void*>(ptr), dims, strides, box, es, CU_TENSOR_MAP_INTERLEAVE_NONE,
       CU_TENSOR_MAP_SWIZZLE_128B, CU_TENSOR_MAP_L2_PROMOTION_L2_256B, CU_TENSOR_MAP_FLOAT_OOB_FILL_NONE);
}

}

extern "C" void kernel_launch(void* const* d_in, const int* in_sizes, int n_in, void* d_out, int out_size) {
    static EncodeFn fn = nullptr;
    if (!fn) {
        void* f = nullptr;
        cudaDriverEntryPointQueryResult qr;
        cudaGetDriverEntryPoint("cuTensorMapEncodeTiled", &f, cudaEnableDefault, &qr);
        fn = (EncodeFn)f;
        cudaFuncSetAttribute(fused_kernel, cudaFuncAttributeMaxDynamicSharedMemorySize, SMEM_BYTES);
    }
    CUtensorMap m_ckv, m_wuk, m_wuv, m_wq, m_wo, m_x, m_out, m_gate, m_up, m_down;
    make_map_w(fn, &m_gate, d_in[8], DM, FF, FS / 64, 16);
    make_map_w(fn, &m_up, d_in[9], DM, FF, FS / 64, 16);
    make_map_w(fn, &m_down, d_in[10], FF, DM, DM / 64, 16);
    make_map_w(fn, &m_ckv, d_in[1], SEQ, DC, 1, 128);
    make_map_w(fn, &m_wq, d_in[2], DM, NH * 128, 1, 64);
    make_map_w(fn, &m_wuk, d_in[3], DC, NH * 128, 2, 64);
    make_map_w(fn, &m_wuv, d_in[4], DC, NH * 128, 2, 64);
    make_map_w(fn, &m_wo, d_in[5], NH * 128, DM, 1, 64);
    make_map_w(fn, &m_x, d_in[0], SEQ, DM, 2, 64);
    make_map_2d(fn, &m_out, d_out, SEQ, DM, 16);
    Params P;
    P.x = (const __nv_bfloat16*)d_in[0];
    P.w_r = (const __nv_bfloat16*)d_in[7];
    P.c_kv = (const uint8_t*)d_in[1];
    P.w_uk = (const uint8_t*)d_in[3];
    P.w_uv = (const uint8_t*)d_in[4];
    fused_kernel<<<NCTA, 384, SMEM_BYTES>>>(m_ckv, m_wuk, m_wuv, m_wq, m_wo, m_x, m_out, m_gate, m_up, m_down, P);
}
```

```cpp
#include <cuda_runtime.h>
#include <cuda_bf16.h>
#include <cuda.h>
#include <stdint.h>
#define PEEL 5
#define PF4 0
#define FDELAY 1
#define LNSH 0
#define FETCH_INL __noinline__
#define RDUM 0
#define UBAD 0
#define ACOND ((0x1B >> item) & 1)
#define LATEMC 1
#define START 2
#define XAT 1
#include <type_traits>
#define WN 6
#define WINP 1
#define LQN 8
#define LQPOS 1
#define QOPQ 0
#define NTIE 1
#define KTRY 1
#define MASKV 1
#define EREL 0
#define NSUM 2
#define EARLY 2
#define PMINIT 1
#define QSPLIT 1
#define PARK0 1
#define MG 8
#define LQEND 4
#define QKORD 1
#define BALLOT 1
#define AMAP 1
#define EARLYW 2
#define QSCALE 1
#define INPLACE 1

namespace {

constexpr int SEQ = 2048, DM = 1024, NH = 32, DC = 512, FF = 3584;
constexpr int PAGE = 16384;
constexpr int NRING = 12;
constexpr int NCTA = 132, NMAIN = 128;
constexpr uint32_t SM_REGION = NRING * PAGE;
constexpr uint32_t SM_BAR = (NRING + 2) * PAGE;
constexpr uint32_t BAR_FULL = SM_BAR, BAR_EMPTY = SM_BAR + 64;
constexpr uint32_t BAR_DEP = SM_BAR + 128;
constexpr uint32_t BAR_G = SM_BAR + 184;
constexpr uint32_t BAR_DONE = SM_BAR + 200;
constexpr uint32_t BAR_EMPTYL = SM_BAR + 216;
constexpr int NBAR = 35;
constexpr uint32_t SM_PROF = SM_BAR + 320;
constexpr int SMEM_BYTES = SM_PROF + 512;
constexpr uint32_t SPIN_LIMIT = 1u << 16;
constexpr uint32_t POLL_MASK = 7;

struct SyncBlock {
    unsigned done;       unsigned pad0[31];
    unsigned ln;         unsigned pad1[31];
    unsigned router;     unsigned pad4[31];
    unsigned ffn_ticket; unsigned pad2[31];
    unsigned ffn_done;   unsigned pad3[31];
    unsigned kv[NH * 8];
    unsigned kvfree[16 * 8];
    unsigned ctx[32 * NH];
};

__device__ __align__(1024) uint8_t g_xn[8 * 16 * 4 * 8192];
__device__ __align__(4096) uint8_t g_kv[16 * 16 * 65536];
__device__ __align__(4096) uint8_t g_ctx[16 * 64 * 16384];
__device__ __align__(16) uint4 g_routed[2 * 128];
__device__ int g_sel[2];
__device__ __align__(16) float g_r[SEQ];
__device__ __align__(16) float g_ypart[4 * 2 * DM];
__device__ SyncBlock g_sync;

__device__ __forceinline__ uint32_t smem_u32(const void* p) { return (uint32_t)__cvta_generic_to_shared(p); }

__device__ __forceinline__ void mbar_init(uint32_t bar, uint32_t count) {
    asm volatile("mbarrier.init.shared::cta.b64 [%0], %1;" ::"r"(bar), "r"(count) : "memory");
}
#define MBAR_WAIT_ASM(HINT, LIMIT)                                                                  \
    asm volatile("{\n.reg .pred p;\n.reg .u32 n;\nmov.u32 n, 0;\n"                                  \
                 "WAIT_LOOP:\n"                                                                     \
                 "mbarrier.try_wait.parity.shared::cta.b64 p, [%0], %1" HINT ";\n"                  \
                 "@p bra WAIT_DONE;\n"                                                              \
                 "add.u32 n, n, 1;\n"                                                               \
                 "setp.lt.u32 p, n, " LIMIT ";\n"                                                   \
                 "@p bra WAIT_LOOP;\n"                                                              \
                 "WAIT_DONE:\n}\n" ::"r"(bar), "r"(parity) : "memory")
__device__ __forceinline__ void mbar_wait(uint32_t bar, uint32_t parity) { MBAR_WAIT_ASM("", "131072"); }
__device__ __forceinline__ void mbar_sleep(uint32_t bar, uint32_t parity) { MBAR_WAIT_ASM(", 2000", "8192"); }
__device__ __forceinline__ bool mbar_try(uint32_t bar, uint32_t parity) {
    uint32_t ok;
    asm volatile("{\n.reg .pred p;\nmbarrier.try_wait.parity.shared::cta.b64 p, [%1], %2;\nselp.u32 %0, 1, 0, p;\n}\n"
                 : "=r"(ok) : "r"(bar), "r"(parity) : "memory");
    return ok;
}
__device__ __forceinline__ bool mbar_test(uint32_t bar, uint32_t parity) {
    uint32_t ok;
    asm volatile("{\n.reg .pred p;\nmbarrier.test_wait.parity.shared::cta.b64 p, [%1], %2;\nselp.u32 %0, 1, 0, p;\n}\n"
                 : "=r"(ok) : "r"(bar), "r"(parity) : "memory");
    return ok;
}
__device__ __forceinline__ bool elect_one() {
    uint32_t ok;
    asm volatile("{\n.reg .pred p;\nelect.sync _|p, 0xffffffff;\nselp.u32 %0, 1, 0, p;\n}\n" : "=r"(ok));
    return ok;
}
__device__ __forceinline__ void mbar_arrive(uint32_t bar) {
    asm volatile("mbarrier.arrive.shared::cta.b64 _, [%0];" ::"r"(bar) : "memory");
}
__device__ __forceinline__ void mbar_expect_tx(uint32_t bar, uint32_t bytes) {
    asm volatile("mbarrier.arrive.expect_tx.shared::cta.b64 _, [%0], %1;" ::"r"(bar), "r"(bytes) : "memory");
}
__device__ __forceinline__ void mbar_arrive_cluster(uint32_t cluster_addr) {
    asm volatile("mbarrier.arrive.shared::cluster.b64 _, [%0];" ::"r"(cluster_addr) : "memory");
}
__device__ __forceinline__ uint32_t mapa(uint32_t addr, uint32_t rank) {
    uint32_t r;
    asm("mapa.shared::cluster.u32 %0, %1, %2;" : "=r"(r) : "r"(addr), "r"(rank));
    return r;
}
__device__ __forceinline__ void tma_3d(uint32_t dst, const CUtensorMap* m, int c0, int c1, int c2, uint32_t bar) {
    asm volatile("cp.async.bulk.tensor.3d.shared::cluster.global.mbarrier::complete_tx::bytes [%0], [%1, {%3, %4, %5}], [%2];"
                 ::"r"(dst), "l"(m), "r"(bar), "r"(c0), "r"(c1), "r"(c2) : "memory");
}
__device__ __forceinline__ void tma_3d_hint(uint32_t dst, const CUtensorMap* m, int c0, int c1, int c2, uint32_t bar, uint64_t pol) {
    asm volatile("cp.async.bulk.tensor.3d.shared::cluster.global.mbarrier::complete_tx::bytes.L2::cache_hint [%0], [%1, {%3, %4, %5}], [%2], %6;"
                 ::"r"(dst), "l"(m), "r"(bar), "r"(c0), "r"(c1), "r"(c2), "l"(pol) : "memory");
}
__device__ __forceinline__ void tma_3d_mc(uint32_t dst, const CUtensorMap* m, int c0, int c1, int c2, uint32_t bar) {
    asm volatile("cp.async.bulk.tensor.3d.shared::cluster.global.mbarrier::complete_tx::bytes.multicast::cluster [%0], [%1, {%3, %4, %5}], [%2], %6;"
                 ::"r"(dst), "l"(m), "r"(bar), "r"(c0), "r"(c1), "r"(c2), "h"((uint16_t)3) : "memory");
}
__device__ __forceinline__ void bulk_load(uint32_t dst, const void* src, uint32_t bytes, uint32_t bar) {
    asm volatile("cp.async.bulk.shared::cluster.global.mbarrier::complete_tx::bytes [%0], [%1], %2, [%3];"
                 ::"r"(dst), "l"(src), "r"(bytes), "r"(bar) : "memory");
}
__device__ __forceinline__ void cp_async16(uint32_t dst, const void* src) {
    asm volatile("cp.async.cg.shared.global [%0], [%1], 16;" ::"r"(dst), "l"(src) : "memory");
}
__device__ __forceinline__ void bulk_load_mc(uint32_t dst, const void* src, uint32_t bytes, uint32_t bar) {
    asm volatile("cp.async.bulk.shared::cluster.global.mbarrier::complete_tx::bytes.multicast::cluster [%0], [%1], %2, [%3], %4;"
                 ::"r"(dst), "l"(src), "r"(bytes), "r"(bar), "h"((uint16_t)3) : "memory");
}
__device__ __forceinline__ void tma_store_2d(const CUtensorMap* m, int c0, int c1, uint32_t src) {
    asm volatile("cp.async.bulk.tensor.2d.global.shared::cta.bulk_group [%0, {%2, %3}], [%1];"
                 ::"l"(m), "r"(src), "r"(c0), "r"(c1) : "memory");
}
__device__ __forceinline__ void bulk_commit() { asm volatile("cp.async.bulk.commit_group;" ::: "memory"); }
__device__ __forceinline__ void bulk_wait_read() { asm volatile("cp.async.bulk.wait_group.read 0;" ::: "memory"); }
__device__ __forceinline__ void fence_async_smem() { asm volatile("fence.proxy.async.shared::cta;" ::: "memory"); }
__device__ __forceinline__ void prefetch_map(const CUtensorMap* m) {
    asm volatile("prefetch.tensormap [%0];" ::"l"(m) : "memory");
}
__device__ __forceinline__ void red_release(unsigned* p) {
    asm volatile("red.release.gpu.global.add.u32 [%0], 1;" ::"l"(p) : "memory");
}
__device__ __forceinline__ unsigned ld_relaxed(const unsigned* p) {
    unsigned v;
    asm volatile("ld.relaxed.gpu.global.u32 %0, [%1];" : "=r"(v) : "l"(p) : "memory");
    return v;
}
__device__ __forceinline__ void wait_counter(const unsigned* p, unsigned target) {
    for (uint32_t n = 0; (int)(ld_relaxed(p) - target) < 0 && n < SPIN_LIMIT; n++) __nanosleep(100);
    asm volatile("fence.acquire.gpu;" ::: "memory");
    asm volatile("fence.proxy.async.global;" ::: "memory");
}
__device__ __forceinline__ void bar_sync(int id, int n) { asm volatile("bar.sync %0, %1;" ::"r"(id), "r"(n) : "memory"); }
__device__ __forceinline__ void bar_arrive(int id, int n) { asm volatile("bar.arrive %0, %1;" ::"r"(id), "r"(n) : "memory"); }
__device__ __forceinline__ void cluster_sync() {
    asm volatile("barrier.cluster.arrive.relaxed.aligned;\nbarrier.cluster.wait.aligned;" ::: "memory");
}
__device__ __forceinline__ void wg_fence() { asm volatile("wgmma.fence.sync.aligned;" ::: "memory"); }
__device__ __forceinline__ void wg_commit() { asm volatile("wgmma.commit_group.sync.aligned;" ::: "memory"); }
template <int N> __device__ __forceinline__ void wg_wait() { asm volatile("wgmma.wait_group.sync.aligned %0;" ::"n"(N) : "memory"); }
template <int N> __device__ __forceinline__ void reg_fence(float (&a)[N]) {
#pragma unroll
    for (int i = 0; i < N; i++) asm volatile("" : "+f"(a[i])::"memory");
}
template <int N> __device__ __forceinline__ void reg_fence(uint32_t (&a)[N]) {
#pragma unroll
    for (int i = 0; i < N; i++) asm volatile("" : "+r"(a[i])::"memory");
}
__device__ __forceinline__ uint32_t pack_bf16(float lo, float hi) {
    uint32_t r;
    asm("cvt.rn.bf16x2.f32 %0, %1, %2;" : "=r"(r) : "f"(hi), "f"(lo));
    return r;
}
__device__ __forceinline__ float bf_lo(uint32_t v) { return __uint_as_float(v << 16); }
__device__ __forceinline__ float bf_hi(uint32_t v) { return __uint_as_float(v & 0xffff0000u); }
__device__ __forceinline__ float bf_round(float v) { return __bfloat162float(__float2bfloat16_rn(v)); }
__device__ __forceinline__ float ex2(float v) {
    float r;
    asm("ex2.approx.ftz.f32 %0, %1;" : "=f"(r) : "f"(v));
    return r;
}
__device__ __forceinline__ float sqrt_approx(float v) {
    float r;
    asm("sqrt.approx.ftz.f32 %0, %1;" : "=f"(r) : "f"(v));
    return r;
}
__device__ __forceinline__ float rcp_approx(float v) {
    float r;
    asm("rcp.approx.ftz.f32 %0, %1;" : "=f"(r) : "f"(v));
    return r;
}
__device__ __forceinline__ float silu_f(float v) { return v * rcp_approx(1.0f + ex2(v * -1.4426950408889634f)); }
__device__ __forceinline__ void stmatrix_x4(uint32_t addr, uint32_t r0, uint32_t r1, uint32_t r2, uint32_t r3) {
    asm volatile("stmatrix.sync.aligned.m8n8.x4.shared.b16 [%0], {%1, %2, %3, %4};"
                 ::"r"(addr), "r"(r0), "r"(r1), "r"(r2), "r"(r3) : "memory");
}
__device__ __forceinline__ void sts128(uint32_t addr, uint32_t r0, uint32_t r1, uint32_t r2, uint32_t r3) {
    asm volatile("st.shared.v4.b32 [%0], {%1, %2, %3, %4};" ::"r"(addr), "r"(r0), "r"(r1), "r"(r2), "r"(r3) : "memory");
}
__device__ __forceinline__ void lds128(uint32_t addr, uint32_t& r0, uint32_t& r1, uint32_t& r2, uint32_t& r3) {
    asm volatile("ld.shared.v4.b32 {%0, %1, %2, %3}, [%4];" : "=r"(r0), "=r"(r1), "=r"(r2), "=r"(r3) : "r"(addr) : "memory");
}
__device__ __forceinline__ void ldmatrix_x4(uint32_t addr, uint32_t& r0, uint32_t& r1, uint32_t& r2, uint32_t& r3) {
    asm volatile("ldmatrix.sync.aligned.m8n8.x4.shared.b16 {%0, %1, %2, %3}, [%4];"
                 : "=r"(r0), "=r"(r1), "=r"(r2), "=r"(r3) : "r"(addr) : "memory");
}
__device__ __forceinline__ uint32_t bf2_mul(uint32_t a, uint32_t b) {
    uint32_t r;
    asm("mul.rn.bf16x2 %0, %1, %2;" : "=r"(r) : "r"(a), "r"(b));
    return r;
}
__device__ __forceinline__ uint32_t bf2_add(uint32_t a, uint32_t b) {
    uint32_t r;
    asm("add.rn.bf16x2 %0, %1, %2;" : "=r"(r) : "r"(a), "r"(b));
    return r;
}
__device__ __forceinline__ uint64_t policy_evict_first() {
    uint64_t p;
    asm("createpolicy.fractional.L2::evict_first.b64 %0, 1.0;" : "=l"(p));
    return p;
}

__device__ __forceinline__ uint64_t make_desc(uint32_t addr, uint32_t lbo_bytes) {
    return (uint64_t)((addr & 0x3FFFF) >> 4) | ((uint64_t)(lbo_bytes >> 4) << 16) | ((uint64_t)(1024 >> 4) << 32) | (1ull << 62);
}

__device__ __forceinline__ void wgmma_n256_ss(float (&d)[128], uint64_t da, uint64_t db, int acc) {
    asm volatile(
        "{\n.reg .pred p;\nsetp.ne.b32 p, %130, 0;\n"
        "wgmma.mma_async.sync.aligned.m64n256k16.f32.bf16.bf16 {"
        "%0, %1, %2, %3, %4, %5, %6, %7, %8, %9, %10, %11, %12, %13, %14, %15, "
        "%16, %17, %18, %19, %20, %21, %22, %23, %24, %25, %26, %27, %28, %29, %30, %31, "
        "%32, %33, %34, %35, %36, %37, %38, %39, %40, %41, %42, %43, %44, %45, %46, %47, "
        "%48, %49, %50, %51, %52, %53, %54, %55, %56, %57, %58, %59, %60, %61, %62, %63, "
        "%64, %65, %66, %67, %68, %69, %70, %71, %72, %73, %74, %75, %76, %77, %78, %79, "
        "%80, %81, %82, %83, %84, %85, %86, %87, %88, %89, %90, %91, %92, %93, %94, %95, "
        "%96, %97, %98, %99, %100, %101, %102, %103, %104, %105, %106, %107, %108, %109, %110, %111, "
        "%112, %113, %114, %115, %116, %117, %118, %119, %120, %121, %122, %123, %124, %125, %126, %127"
        "}, %128, %129, p, 1, 1, 1, 0;\n}\n"
        :
        "+f"(d[0]), "+f"(d[1]), "+f"(d[2]), "+f"(d[3]), "+f"(d[4]), "+f"(d[5]), "+f"(d[6]), "+f"(d[7]),
        "+f"(d[8]), "+f"(d[9]), "+f"(d[10]), "+f"(d[11]), "+f"(d[12]), "+f"(d[13]), "+f"(d[14]), "+f"(d[15]),
        "+f"(d[16]), "+f"(d[17]), "+f"(d[18]), "+f"(d[19]), "+f"(d[20]), "+f"(d[21]), "+f"(d[22]), "+f"(d[23]),
        "+f"(d[24]), "+f"(d[25]), "+f"(d[26]), "+f"(d[27]), "+f"(d[28]), "+f"(d[29]), "+f"(d[30]), "+f"(d[31]),
        "+f"(d[32]), "+f"(d[33]), "+f"(d[34]), "+f"(d[35]), "+f"(d[36]), "+f"(d[37]), "+f"(d[38]), "+f"(d[39]),
        "+f"(d[40]), "+f"(d[41]), "+f"(d[42]), "+f"(d[43]), "+f"(d[44]), "+f"(d[45]), "+f"(d[46]), "+f"(d[47]),
        "+f"(d[48]), "+f"(d[49]), "+f"(d[50]), "+f"(d[51]), "+f"(d[52]), "+f"(d[53]), "+f"(d[54]), "+f"(d[55]),
        "+f"(d[56]), "+f"(d[57]), "+f"(d[58]), "+f"(d[59]), "+f"(d[60]), "+f"(d[61]), "+f"(d[62]), "+f"(d[63]),
        "+f"(d[64]), "+f"(d[65]), "+f"(d[66]), "+f"(d[67]), "+f"(d[68]), "+f"(d[69]), "+f"(d[70]), "+f"(d[71]),
        "+f"(d[72]), "+f"(d[73]), "+f"(d[74]), "+f"(d[75]), "+f"(d[76]), "+f"(d[77]), "+f"(d[78]), "+f"(d[79]),
        "+f"(d[80]), "+f"(d[81]), "+f"(d[82]), "+f"(d[83]), "+f"(d[84]), "+f"(d[85]), "+f"(d[86]), "+f"(d[87]),
        "+f"(d[88]), "+f"(d[89]), "+f"(d[90]), "+f"(d[91]), "+f"(d[92]), "+f"(d[93]), "+f"(d[94]), "+f"(d[95]),
        "+f"(d[96]), "+f"(d[97]), "+f"(d[98]), "+f"(d[99]), "+f"(d[100]), "+f"(d[101]), "+f"(d[102]), "+f"(d[103]),
        "+f"(d[104]), "+f"(d[105]), "+f"(d[106]), "+f"(d[107]), "+f"(d[108]), "+f"(d[109]), "+f"(d[110]), "+f"(d[111]),
        "+f"(d[112]), "+f"(d[113]), "+f"(d[114]), "+f"(d[115]), "+f"(d[116]), "+f"(d[117]), "+f"(d[118]), "+f"(d[119]),
        "+f"(d[120]), "+f"(d[121]), "+f"(d[122]), "+f"(d[123]), "+f"(d[124]), "+f"(d[125]), "+f"(d[126]), "+f"(d[127])
        : "l"(da), "l"(db), "r"(acc));
}

template <int TB>
__device__ __forceinline__ void wgmma_n128_rs(float (&d)[64], uint32_t a0, uint32_t a1, uint32_t a2, uint32_t a3, uint32_t db, int acc) {
    asm volatile(
        "{\n.reg .pred p;\n.reg .b64 db;\nsetp.ne.b32 p, %69, 0;\nmov.b64 db, {%68, 0x40000040};\n"
        "wgmma.mma_async.sync.aligned.m64n128k16.f32.bf16.bf16 {"
        "%0, %1, %2, %3, %4, %5, %6, %7, %8, %9, %10, %11, %12, %13, %14, %15, "
        "%16, %17, %18, %19, %20, %21, %22, %23, %24, %25, %26, %27, %28, %29, %30, %31, "
        "%32, %33, %34, %35, %36, %37, %38, %39, %40, %41, %42, %43, %44, %45, %46, %47, "
        "%48, %49, %50, %51, %52, %53, %54, %55, %56, %57, %58, %59, %60, %61, %62, %63"
        "}, {%64, %65, %66, %67}, db, p, 1, 1, %70;\n}\n"
        :
        "+f"(d[0]), "+f"(d[1]), "+f"(d[2]), "+f"(d[3]), "+f"(d[4]), "+f"(d[5]), "+f"(d[6]), "+f"(d[7]),
        "+f"(d[8]), "+f"(d[9]), "+f"(d[10]), "+f"(d[11]), "+f"(d[12]), "+f"(d[13]), "+f"(d[14]), "+f"(d[15]),
        "+f"(d[16]), "+f"(d[17]), "+f"(d[18]), "+f"(d[19]), "+f"(d[20]), "+f"(d[21]), "+f"(d[22]), "+f"(d[23]),
        "+f"(d[24]), "+f"(d[25]), "+f"(d[26]), "+f"(d[27]), "+f"(d[28]), "+f"(d[29]), "+f"(d[30]), "+f"(d[31]),
        "+f"(d[32]), "+f"(d[33]), "+f"(d[34]), "+f"(d[35]), "+f"(d[36]), "+f"(d[37]), "+f"(d[38]), "+f"(d[39]),
        "+f"(d[40]), "+f"(d[41]), "+f"(d[42]), "+f"(d[43]), "+f"(d[44]), "+f"(d[45]), "+f"(d[46]), "+f"(d[47]),
        "+f"(d[48]), "+f"(d[49]), "+f"(d[50]), "+f"(d[51]), "+f"(d[52]), "+f"(d[53]), "+f"(d[54]), "+f"(d[55]),
        "+f"(d[56]), "+f"(d[57]), "+f"(d[58]), "+f"(d[59]), "+f"(d[60]), "+f"(d[61]), "+f"(d[62]), "+f"(d[63])
        : "r"(a0), "r"(a1), "r"(a2), "r"(a3), "r"(db), "r"(acc), "n"(TB));
}

__device__ __forceinline__ void wgmma_n128_ss(float* d, uint64_t da, uint64_t db, int acc) {
    asm volatile(
        "{\n.reg .pred p;\nsetp.ne.b32 p, %66, 0;\n"
        "wgmma.mma_async.sync.aligned.m64n128k16.f32.bf16.bf16 {"
        "%0, %1, %2, %3, %4, %5, %6, %7, %8, %9, %10, %11, %12, %13, %14, %15, "
        "%16, %17, %18, %19, %20, %21, %22, %23, %24, %25, %26, %27, %28, %29, %30, %31, "
        "%32, %33, %34, %35, %36, %37, %38, %39, %40, %41, %42, %43, %44, %45, %46, %47, "
        "%48, %49, %50, %51, %52, %53, %54, %55, %56, %57, %58, %59, %60, %61, %62, %63"
        "}, %64, %65, p, 1, 1, 0, 1;\n}\n"
        :
        "+f"(d[0]), "+f"(d[1]), "+f"(d[2]), "+f"(d[3]), "+f"(d[4]), "+f"(d[5]), "+f"(d[6]), "+f"(d[7]),
        "+f"(d[8]), "+f"(d[9]), "+f"(d[10]), "+f"(d[11]), "+f"(d[12]), "+f"(d[13]), "+f"(d[14]), "+f"(d[15]),
        "+f"(d[16]), "+f"(d[17]), "+f"(d[18]), "+f"(d[19]), "+f"(d[20]), "+f"(d[21]), "+f"(d[22]), "+f"(d[23]),
        "+f"(d[24]), "+f"(d[25]), "+f"(d[26]), "+f"(d[27]), "+f"(d[28]), "+f"(d[29]), "+f"(d[30]), "+f"(d[31]),
        "+f"(d[32]), "+f"(d[33]), "+f"(d[34]), "+f"(d[35]), "+f"(d[36]), "+f"(d[37]), "+f"(d[38]), "+f"(d[39]),
        "+f"(d[40]), "+f"(d[41]), "+f"(d[42]), "+f"(d[43]), "+f"(d[44]), "+f"(d[45]), "+f"(d[46]), "+f"(d[47]),
        "+f"(d[48]), "+f"(d[49]), "+f"(d[50]), "+f"(d[51]), "+f"(d[52]), "+f"(d[53]), "+f"(d[54]), "+f"(d[55]),
        "+f"(d[56]), "+f"(d[57]), "+f"(d[58]), "+f"(d[59]), "+f"(d[60]), "+f"(d[61]), "+f"(d[62]), "+f"(d[63])
        : "l"(da), "l"(db), "r"(acc));
}

__device__ __forceinline__ void wgmma_n8_ta(float* d, uint64_t da, uint64_t db) {
    asm volatile("wgmma.mma_async.sync.aligned.m64n8k16.f32.bf16.bf16 {%0, %1, %2, %3}, %4, %5, 1, 1, 1, 1, 0;\n"
                 : "+f"(d[0]), "+f"(d[1]), "+f"(d[2]), "+f"(d[3]) : "l"(da), "l"(db));
}

#define PROF(slot, role)
#undef PROF_GT
#define PROF_GT(slot)

struct Params {
    const __nv_bfloat16* x;
    const __nv_bfloat16* w_r;
    const uint8_t *c_kv, *w_uk, *w_uv;
    uint8_t* out;
};
__device__ __forceinline__ void lsu_prefetch(const void* p) { asm volatile("prefetch.global.L2 [%0];" ::"l"(p) : "memory"); }

template <typename T>
__device__ __forceinline__ T* ptr_off(T* base, uint32_t off) {
    uint32_t lo, hi;
    asm("mov.b64 {%0, %1}, %2;" : "=r"(lo), "=r"(hi) : "l"(base));
    asm("add.cc.u32 %0, %0, %2;\naddc.u32 %1, %1, 0;" : "+r"(lo), "+r"(hi) : "r"(off));
    T* r;
    asm("mov.b64 %0, {%1, %2};" : "=l"(r) : "r"(lo), "r"(hi));
    return r;
}
__device__ __forceinline__ int kv_head(int pair) { return AMAP ? (pair & 15) >> 1 : pair >> 3; }
__device__ __forceinline__ int kv_tokens(int pair) { return AMAP ? (pair & 1) * 4 + (pair >> 4) : pair & 7; }
__device__ __forceinline__ int attn_rowblock(int pair, int seg) {
    int j = pair & 3, hl = pair >> 2;
    return ((hl & 1) ^ seg) ? j : 7 - j;
}
__device__ __forceinline__ int outproj_head(int i, int ib) {
    if (i < 16) return i;
    return 16 + 2 * (i & 7) + ((ib < 4) ^ ((i >> 3) & 1));
}

__device__ __forceinline__ void pin_value(uint32_t& v) { asm volatile("" : "+r"(v)); }
__device__ __forceinline__ void pin_value(int& v) { asm volatile("" : "+r"(v)); }
__device__ __forceinline__ void pin_value(const uint8_t*& v) { asm volatile("" : "+l"(v)); }

__device__ __forceinline__ void producer(const Params& P, uint32_t sb, int pair, int c,
                                         const CUtensorMap* m_ckv, const CUtensorMap* m_wu,
                                         const CUtensorMap* m_wq, const CUtensorMap* m_wo) {
    const int hl = pair >> 2;
    const int ibA = attn_rowblock(pair, 0), nA = 2 * ibA + 2;
    const int ib = (pair >> 1) & 7, mi = 2 * ib + c, nb = (pair >> 4) * 4 + (pair & 1) * 2;
    const bool leader = elect_one();
    uint32_t g = 4, tail = 0;
    if (leader) prefetch_map(m_wq);
    auto wait_released = [&](uint32_t need) {
#pragma unroll 1
        for (; tail <= need; tail++) mbar_wait(sb + BAR_EMPTY + (tail & 7) * 8, (tail >> 3) & 1);
    };
    auto wait_released_here = [&](uint32_t need) {
#pragma unroll 1
        for (; tail < need; tail++) mbar_wait(sb + BAR_EMPTY + (tail & 7) * 8, (tail >> 3) & 1);
        if (tail == need) mbar_wait(sb + BAR_EMPTYL + (need & 7) * 8, (need >> 3) & 1);
    };
    auto wait_released_peer = [&](uint32_t need) {
        if (tail == need) {
            uint32_t eb = sb + BAR_EMPTY + (need & 7) * 8, ep = (need >> 3) & 1;
            tail++;
            mbar_wait(eb, ep);
        }
    };
    auto full_bar = [&]() { return sb + BAR_FULL + (g & 7) * 8; };
    auto pin = [](auto&... v) { (pin_value(v), ...); };
#pragma unroll 1
    for (int rnd = 0; rnd < 2; rnd++) {
#pragma unroll 1
        for (int i = rnd ? 0 : 4; i < 16; i++) {
            int kb = i & 7, h2 = (kv_head(pair) + (i & 8) + rnd * 16) * 2, krow = kb * 64;
            uint32_t pg = sb + (i & 3) * (3 * PAGE), pb = pg + (1 + c) * PAGE, bar = full_bar();
            pin(kb, h2, krow, pg, pb, bar);
            const uint32_t need = g - 4 - (i < 2);
            wait_released_here(need);
            if (leader) {
                mbar_expect_tx(bar, 3 * PAGE);
                tma_3d(pg, m_wu, 0, krow, h2, bar);
            }
            wait_released_peer(need);
            if (leader) {
                tma_3d_mc(pb, m_ckv, 0, kv_tokens(pair) * 256 + c * 128, kb, bar);
                if (rnd == 1 && i == 3) asm volatile("red.relaxed.gpu.global.add.u32 [%0], 1;" ::"l"(ptr_off(g_sync.kvfree, hl * 32)) : "memory");
            }
            g++;
        }
        mbar_sleep(sb + BAR_DEP, 0);
        const uint8_t* xa = ptr_off(g_xn, ibA * (16 * 32768) + c * PAGE);
        const uint8_t* xb = ptr_off(g_xn, (7 - ibA) * (16 * 32768) + (1 - c) * PAGE);
#pragma unroll 1
        for (int kb = 0; kb < DM / 64; kb++) {
            uint32_t pg = sb + (kb & 3) * (3 * PAGE), pw = pg + 2 * PAGE + c * 8192, bar = full_bar(), p2 = pg + PAGE;
            int krow = kb * 64;
            pin(pg, pw, p2, bar, krow);
            wait_released_here(g - 4);
            if (leader) {
                mbar_expect_tx(bar, 3 * PAGE);
                bulk_load(pg, xa, PAGE, bar);
            }
            wait_released_peer(g - 4);
            if (leader) {
                tma_3d_mc(pw, m_wq, 0, krow, (rnd * 16 + hl) * 2 + c, bar);
                bulk_load(p2, xb, PAGE, bar);
            }
            g++;
            xa += 32768;
            xb += 32768;
        }
        mbar_sleep(sb + BAR_DEP + 8 + rnd * 16, 0);
        if (rnd == 1 && leader) prefetch_map(m_wo);
        uint32_t pg = sb + c * PAGE;
#pragma unroll 1
        for (int j = 0; j < 36; j++) {
            const bool isk = j == 0 || ((j & 1) && j != 35);
            const int t = isk ? (j + 1) >> 1 : (j - 1) >> 1;
            const uint8_t* src = ptr_off(g_kv, (hl * 16 + (t >= nA ? t - nA : t)) * 65536 + (isk ? 0 : 32768) + c * PAGE);
            uint32_t bar = full_bar(), need = g - 6 + (j < 2) + (j < 5);
            pin(src, bar, need);
            wait_released(need);
            if (leader) {
                mbar_expect_tx(bar, 2 * PAGE);
                bulk_load_mc(pg, src, PAGE, bar);
            }
            g++;
            if (rnd == 0 && j >= 22 && j < 34) {
                const int cta = pair * 2 + c, i = j - 22;
                const uint32_t l = (threadIdx.x & 31) * 128;
                if (i < 8) lsu_prefetch(ptr_off(i & 1 ? P.w_uv : P.w_uk, cta * 32768 + (i >> 1) * 8192 + 4096 + l));
                else lsu_prefetch(ptr_off(P.c_kv, cta * 16384 + (i - 8) * 4096 + l));
            }
            pg = pg >= sb + SM_REGION - 2 * PAGE ? pg - (SM_REGION - 2 * PAGE) : pg + 2 * PAGE;
        }
    }
    uint32_t pg = sb;
#pragma unroll 1
    for (int i = 0; i < 64; i++) {
        if ((i & 15) == 0 && i != 16) mbar_sleep(sb + BAR_DEP + 32 + (i >> 1) - (i ? 8 : 0), 0);
        const int kb = outproj_head(i >> 1, ib) * 2 + (i & 1);
        const uint8_t* src = ptr_off(g_ctx, (mi * 64 + kb) * PAGE);
        uint32_t bar = full_bar(), pw = pg + PAGE + c * 8192;
        int krow = kb * 64;
        pin(src, bar, pw, krow);
        wait_released_here(g - 6);
        if (leader) {
            mbar_expect_tx(bar, 2 * PAGE);
            bulk_load(pg, src, PAGE, bar);
        }
        wait_released_peer(g - 6);
        if (leader) tma_3d_mc(pw, m_wo, 0, krow, nb + c, bar);
        g++;
        pg = pg == sb + SM_REGION - 2 * PAGE ? sb : pg + 2 * PAGE;
    }
}

__device__ __forceinline__ uint32_t xn_block(int row64, int kb) {
    return (((row64 >> 2) * 16 + kb) * 4 + ((row64 & 1) * 2 + (((row64 >> 1) & 1) ^ 1))) * 8192;
}
__device__ __forceinline__ uint32_t image_offset(int row, int ch) {
    return xn_block(row >> 6, ch >> 3) + (row & 63) * 128 + (((ch & 7) ^ (row & 7)) << 4);
}
__device__ __forceinline__ uint32_t bf2_sub(uint32_t a, uint32_t b) {
    uint32_t r;
    asm("sub.rn.bf16x2 %0, %1, %2;" : "=r"(r) : "r"(a), "r"(b));
    return r;
}
__device__ __forceinline__ uint32_t bf2_fma(uint32_t a, uint32_t b, uint32_t c) {
    uint32_t r;
    asm("fma.rn.bf16x2 %0, %1, %2, %3;" : "=r"(r) : "r"(a), "r"(b), "r"(c));
    return r;
}
template <int N0, int N>
__device__ __forceinline__ void ln_sums(const uint32_t (&u)[N], float& sum, float& sq) {
    float s0 = 0.f, s1 = 0.f, q0 = 0.f, q1 = 0.f;
#pragma unroll
    for (int k = N0; k < N0 + 16; k++) {
        const float a = bf_lo(u[k]), b = bf_hi(u[k]);
        s0 += a; s1 += b;
        q0 = fmaf(a, a, q0); q1 = fmaf(b, b, q1);
    }
    sum = s0 + s1;
    sq = q0 + q1;
}
__device__ __forceinline__ void ln_finish(float sum, float sq, uint32_t& mean2, uint32_t& rhi2, uint32_t& rlo2) {
    const float ms = sum * (1.0f / DM);
    const float var = fmaxf(fmaf(-ms, ms, sq * (1.0f / DM)), 0.f);
    const float rden = rcp_approx(bf_round(sqrt_approx(bf_round(bf_round(var) + 1e-5f))));
    const float rhi = bf_round(rden);
    mean2 = pack_bf16(ms, ms);
    rhi2 = pack_bf16(rhi, rhi);
    rlo2 = pack_bf16(rden - rhi, rden - rhi);
}
template <int N0, int N>
__device__ __forceinline__ void ln_apply(uint32_t (&u)[N], uint32_t mean2, uint32_t rhi2, uint32_t rlo2, uint8_t* dst) {
#pragma unroll
    for (int i = 0; i < 4; i++) {
        uint32_t o[4];
#pragma unroll
        for (int k = 0; k < 4; k++) {
            const uint32_t d = bf2_sub(u[N0 + 4 * i + k], mean2);
            o[k] = bf2_fma(d, rhi2, bf2_mul(d, rlo2));
        }
#pragma unroll
        for (int k = 0; k < 4; k++) u[N0 + 4 * i + k] = o[k];
        __stcg(reinterpret_cast<uint4*>(dst + i * 131072), make_uint4(o[0], o[1], o[2], o[3]));
    }
}
__device__ __forceinline__ int query_rowblock(int pair, int c, int w, int seg) {
    const int qA = (w ? 0 : 2) + c;
    return 4 * attn_rowblock(pair, seg) + (seg ? 3 - qA : qA);
}

__device__ FETCH_INL void fetch_helper(const uint8_t* w_u, const uint8_t* x, uint32_t sb, int w, int lane, int pair, int c) {
    const uint32_t page = sb + SM_REGION + w * PAGE + lane * 16;
    mbar_sleep(sb + BAR_FULL + 5 * 8, 0);
#pragma unroll 1
    for (int i = 0; i < 2; i++) {
        lsu_prefetch(ptr_off(w_u, ((pair * 2 + c) * 4 + i * 2 + (lane >> 4)) * 8192 + 2048 + (lane & 15) * 128));
        __nanosleep(300);
    }
    const unsigned e1 = __ldcg(&g_sync.done) / NCTA + 1;
#pragma unroll 1
    for (int e = 1; e <= 7; e += 2) mbar_sleep(sb + BAR_DONE + 8, (e >> 1) & 1);
    const int rb = ((pair >> 1) & 7) * 4 + c * 2 + w, kb0 = (pair >> 4) * 4 + (pair & 1) * 2;
    const uint8_t* src = ptr_off(g_xn, xn_block(rb, kb0) + lane * 16);
#pragma unroll 1
    for (int i = 0; i < 32; i += 4) {
#pragma unroll
        for (int k = 0; k < 4; k++) cp_async16(page + (i + k) * 512, src + (i + k) * 512 + (i >> 4) * (32768 - 8192));
        __nanosleep(200);
    }
#pragma unroll 1
    for (int i = 0; i < 4; i++) lsu_prefetch(ptr_off(x, (rb * 64 + i * 16 + (lane >> 1)) * (DM * 2) + kb0 * 128 + (lane & 1) * 128));
    wait_counter(&g_sync.ffn_done, e1);
    const int r = __ldcg(ptr_off(g_sel, (lane >> 4) * 4)) - rb * 64, ch = lane & 15;
    const uint4 t = __ldcg(ptr_off(g_routed, ((lane >> 4) * 128 + kb0 * 8 + ch) * 16));
    asm volatile("cp.async.wait_all;" ::: "memory");
    __syncwarp();
    if (r >= 0 && r < 64)
        sts128(sb + SM_REGION + w * PAGE + (ch >> 3) * 8192 + r * 128 + (((ch & 7) ^ (r & 7)) << 4), t.x, t.y, t.z, t.w);
    __syncwarp();
    if (lane == 0) mbar_arrive(sb + BAR_G + w * 8);
    PROF(20, 2);
}

__device__ __noinline__ void sync_helper(uint32_t sb, int lane, int pair, int c) {
    const unsigned e1 = __ldcg(&g_sync.done) / NCTA + 1;
    const int ib = (pair >> 1) & 7;
    int e = 0, b = 0;
#pragma unroll 1
    for (uint32_t n = 0; (e < 9 || b < 7) && n < SPIN_LIMIT; n++) {
        if (e < 9 && __all_sync(~0u, mbar_test(sb + BAR_DONE + (e & 1) * 8, (e >> 1) & 1))) {
            const int rnd = e > 4, ev = (e - 1) & 3;
            unsigned* flag = e == 0 ? &g_sync.ln
                           : ev < 2 ? ptr_off(g_sync.kv, (rnd * 16 + kv_head(pair) + 8 * ev) * 32)
                                    : ptr_off(g_sync.ctx, (query_rowblock(pair, c, lane & 1, ev & 1) * NH + rnd * 16 + (pair >> 2)) * 4);
            asm volatile("fence.proxy.async.global;\nfence.release.gpu;" ::: "memory");
            if (lane < ((e == 0 || ev < 2) ? 1 : 2)) asm volatile("red.relaxed.gpu.global.add.u32 [%0], 1;" ::"l"(flag) : "memory");
            PROF(10 + e, 2);
            e++;
        }
        if (b < 7 && e > 0 && (b < 4 || (n & POLL_MASK) == 0)) {
            const int i = b == 4 ? lane >> 1 : 8 * b - 24 + ((lane >> 1) & 7);
            const unsigned* cnt = b == 0 ? &g_sync.ln
                                : b == 2 ? ptr_off(g_sync.kvfree, (kv_head(pair) + 8 * (lane & 1)) * 32)
                                : b < 4 ? ptr_off(g_sync.kv, ((b >> 1) * 16 + (pair >> 2)) * 32)
                                        : ptr_off(g_sync.ctx, ((4 * ib + 2 * c + (lane & 1)) * NH + outproj_head(i & 31, ib)) * 4);
            if (__all_sync(~0u, (int)(ld_relaxed(cnt) - e1 * (b == 0 ? NMAIN : b == 2 ? 8 : b < 4 ? 16 : 1)) >= 0)) {
                asm volatile("fence.acquire.gpu;\nfence.proxy.async.global;" ::: "memory");
                __syncwarp();
                if (lane == 0) mbar_arrive(sb + BAR_DEP + b * 8);
                PROF(1 + b, 2);
                b++;
            }
        }
        __nanosleep(150);
    }
}

__device__ __forceinline__ unsigned long long block_max_key(unsigned long long k, unsigned long long* red, int tid) {
#pragma unroll
    for (int o = 16; o; o >>= 1) {
        unsigned long long t = __shfl_xor_sync(~0u, k, o);
        k = t > k ? t : k;
    }
    bar_sync(1, 256);
    if ((tid & 31) == 0) red[tid >> 5] = k;
    bar_sync(1, 256);
    k = red[0];
#pragma unroll
    for (int i = 1; i < 8; i++) k = red[i] > k ? red[i] : k;
    return k;
}

constexpr int FS = FF / 4;
constexpr int FSTAGE = 32768, FNST = 6;
constexpr int FN1 = 2 * (DM / 16), FN2 = FS / 16;

__device__ __forceinline__ void ffn_producer(uint32_t sb, int s, const CUtensorMap* m_gate, const CUtensorMap* m_up,
                                             const CUtensorMap* m_down) {
    const uint64_t pol = policy_evict_first();
    if (FDELAY) wait_counter(&g_sync.ln, (__ldcg(&g_sync.done) / NCTA + 1) * NMAIN);
    int slot = 0, ph = 1;
#pragma unroll 1
    for (int st = 0; st < FN1 + FN2; st++) {
        mbar_sleep(sb + BAR_EMPTY + slot * 8, ph);
        const uint32_t bar = sb + BAR_FULL + slot * 8;
        const bool up = st < FN1;
        mbar_expect_tx(bar, up ? FS * 32 : DM * 32);
        tma_3d_hint(sb + slot * FSTAGE, up ? ((st & 1) ? m_up : m_gate) : m_down, 0,
                    up ? (st >> 1) * 16 : s * FS + (st - FN1) * 16, up ? s * (FS / 64) : 0, bar, pol);
        if (++slot == FNST) { slot = 0; ph ^= 1; }
    }
}

__device__ __forceinline__ void ffn_cta(uint8_t* smem, uint32_t sb, int s, unsigned epoch, const __nv_bfloat16* w_r) {
    const int tid = threadIdx.x, lane = tid & 31;
    const int warp = __shfl_sync(~0u, tid >> 5, 0), w = warp >> 2;
    constexpr uint32_t XB = FNST * FSTAGE, HB = XB + 16384, AUX = HB + 14336;
    unsigned long long* red = reinterpret_cast<unsigned long long*>(smem + AUX);
    unsigned* flag = reinterpret_cast<unsigned*>(smem + AUX + 128);
    const unsigned e1 = epoch + 1;
    for (int i = tid; i < (16384 + 14336) / 16; i += 256) reinterpret_cast<uint4*>(smem + XB)[i] = make_uint4(0, 0, 0, 0);
    {
        float wf[32];
#pragma unroll
        for (int i = 0; i < 4; i++) {
            const uint4 t = __ldg(reinterpret_cast<const uint4*>(w_r) + lane + 32 * i);
            const uint32_t tu[4] = {t.x, t.y, t.z, t.w};
#pragma unroll
            for (int k = 0; k < 4; k++) { wf[8 * i + 2 * k] = bf_lo(tu[k]); wf[8 * i + 2 * k + 1] = bf_hi(tu[k]); }
        }
        if (tid == 0) wait_counter(&g_sync.ln, e1 * NMAIN);
        bar_sync(1, 256);
#pragma unroll 1
        for (int r0 = s * (SEQ / 4) + warp * (SEQ / 32); r0 < s * (SEQ / 4) + (warp + 1) * (SEQ / 32); r0 += 4) {
            uint4 t[4][4];
#pragma unroll
            for (int r = 0; r < 4; r++)
#pragma unroll
                for (int i = 0; i < 4; i++) t[r][i] = __ldcg(reinterpret_cast<const uint4*>(g_xn + image_offset(r0 + r, lane) + i * 131072));
            float acc[4];
#pragma unroll
            for (int r = 0; r < 4; r++) {
                float a = 0.f, b = 0.f;
#pragma unroll
                for (int i = 0; i < 4; i++) {
                    const uint32_t tu[4] = {t[r][i].x, t[r][i].y, t[r][i].z, t[r][i].w};
#pragma unroll
                    for (int k = 0; k < 4; k++) {
                        a = fmaf(bf_lo(tu[k]), wf[8 * i + 2 * k], a);
                        b = fmaf(bf_hi(tu[k]), wf[8 * i + 2 * k + 1], b);
                    }
                }
                acc[r] = a + b;
            }
#pragma unroll
            for (int o = 16; o; o >>= 1)
#pragma unroll
                for (int r = 0; r < 4; r++) acc[r] += __shfl_xor_sync(~0u, acc[r], o);
            if (lane < 4) __stcg(&g_r[r0 + lane], bf_round(lane == 0 ? acc[0] : lane == 1 ? acc[1] : lane == 2 ? acc[2] : acc[3]));
        }
        __threadfence();
        bar_sync(1, 256);
        if (tid == 0) {
            red_release(&g_sync.router);
            wait_counter(&g_sync.router, e1 * 4);
        }
        bar_sync(1, 256);
    }
    unsigned long long keys[8];
    unsigned long long best = 0;
#pragma unroll
    for (int i = 0; i < 8; i++) {
        int idx = tid + 256 * i;
        uint32_t b = __float_as_uint(__ldcg(&g_r[idx]) + 0.0f);
        b = (b & 0x80000000u) ? ~b : (b | 0x80000000u);
        keys[i] = ((unsigned long long)b << 32) | (unsigned)(SEQ - 1 - idx);
        best = keys[i] > best ? keys[i] : best;
    }
    const unsigned long long k0 = block_max_key(best, red, tid);
    best = 0;
#pragma unroll
    for (int i = 0; i < 8; i++) best = (keys[i] != k0 && keys[i] > best) ? keys[i] : best;
    const unsigned long long k1 = block_max_key(best, red, tid);
    const int row = SEQ - 1 - (int)((w ? k1 : k0) & 0xffffffffu);
    const int ch = tid & 127;
    const uint4 xrow = __ldcg(reinterpret_cast<const uint4*>(g_xn + image_offset(row, ch)));
    *reinterpret_cast<uint4*>(smem + XB + (ch >> 3) * 1024 + w * 128 + (((ch & 7) ^ w) << 4)) = xrow;
    fence_async_smem();
    bar_sync(1, 256);
    PROF(20, tid >> 7);
    int slot = 0, ph = 0, prev = 0;
    auto next_stage = [&](bool has_prev) {
        wg_commit();
        wg_wait<1>();
        if (has_prev && lane < 2) mbar_arrive(sb + BAR_EMPTY + prev * 8);
        prev = slot;
        if (++slot == FNST) { slot = 0; ph ^= 1; }
    };
    {
        float ag[28], au[28];
#pragma unroll
        for (int i = 0; i < 28; i++) ag[i] = au[i] = 0.f;
#pragma unroll 1
        for (int ks = 0; ks < DM / 16; ks++) {
            const uint64_t db = make_desc(sb + XB + (ks >> 2) * 1024 + (ks & 3) * 32, 16);
            mbar_wait(sb + BAR_FULL + slot * 8, ph);
            uint64_t da = make_desc(sb + slot * FSTAGE + w * (7 * 2048), 16);
            wg_fence();
#pragma unroll
            for (int b = 0; b < 7; b++) wgmma_n8_ta(ag + 4 * b, da + b * 128, db);
            next_stage(ks > 0);
            mbar_wait(sb + BAR_FULL + slot * 8, ph);
            da = make_desc(sb + slot * FSTAGE + w * (7 * 2048), 16);
            wg_fence();
#pragma unroll
            for (int b = 0; b < 7; b++) wgmma_n8_ta(au + 4 * b, da + b * 128, db);
            next_stage(true);
        }
        wg_wait<0>();
        reg_fence(ag);
        reg_fence(au);
        if ((lane & 3) == 0) {
#pragma unroll
            for (int i = 0; i < 28; i++) {
                const int f = (warp & 3) * 16 + (lane >> 2) + (i & 2) * 4, tok = i & 1;
                const float h = bf_round(silu_f(bf_round(ag[i]))) * bf_round(au[i]);
                *reinterpret_cast<__nv_bfloat16*>(smem + HB + (w * 7 + (i >> 2)) * 1024 + tok * 128 + (((f >> 3) ^ tok) << 4) + (f & 7) * 2) =
                    __float2bfloat16_rn(h);
            }
        }
    }
    fence_async_smem();
    bar_sync(1, 256);
    PROF(21, tid >> 7);
    {
        float ay[32];
#pragma unroll
        for (int i = 0; i < 32; i++) ay[i] = 0.f;
#pragma unroll 1
        for (int ks = 0; ks < FN2; ks++) {
            const uint64_t db = make_desc(sb + HB + (ks >> 2) * 1024 + (ks & 3) * 32, 16);
            mbar_wait(sb + BAR_FULL + slot * 8, ph);
            const uint64_t da = make_desc(sb + slot * FSTAGE + w * (8 * 2048), 16);
            wg_fence();
#pragma unroll
            for (int b = 0; b < 8; b++) wgmma_n8_ta(ay + 4 * b, da + b * 128, db);
            next_stage(true);
        }
        wg_wait<0>();
        reg_fence(ay);
        if ((lane & 3) == 0) {
#pragma unroll
            for (int i = 0; i < 32; i++)
                g_ypart[(s * 2 + (i & 1)) * DM + (w * 8 + (i >> 2)) * 64 + (warp & 3) * 16 + (lane >> 2) + (i & 2) * 4] = ay[i];
        }
    }
    PROF(23, tid >> 7);
    __threadfence();
    bar_sync(1, 256);
    if (tid == 0) {
        *flag = atomicAdd(&g_sync.ffn_ticket, 1u) == epoch * 4 + 3;
        __threadfence();
    }
    bar_sync(1, 256);
    if (*flag) {
        const float sg = bf_round(__fdividef(1.0f, 1.0f + __expf(-__ldcg(&g_r[row]))));
        const uint32_t xu[4] = {xrow.x, xrow.y, xrow.z, xrow.w};
        uint32_t o[4];
#pragma unroll
        for (int k = 0; k < 4; k++) {
            float y0 = 0.f, y1 = 0.f;
#pragma unroll
            for (int q = 0; q < 4; q++) {
                const float2 y = __ldcg(reinterpret_cast<const float2*>(&g_ypart[(q * 2 + w) * DM + ch * 8 + 2 * k]));
                y0 += y.x; y1 += y.y;
            }
            o[k] = pack_bf16(bf_lo(xu[k]) + bf_round(bf_round(y0) * sg), bf_hi(xu[k]) + bf_round(bf_round(y1) * sg));
        }
        g_routed[w * 128 + ch] = make_uint4(o[0], o[1], o[2], o[3]);
        if (ch == 0) g_sel[w] = row;
        bar_sync(1, 256);
        if (tid == 0) red_release(&g_sync.ffn_done);
    }
}

__device__ __forceinline__ uint32_t slab_addr(uint32_t stg, int lane, int s) {
    const int row = ((lane >> 3) & 1) * 8 + (lane & 7);
    const int chunk = 2 * (s & 3) + (lane >> 4);
    return stg + row * 128 + (s >> 2) * 8192 + ((chunk ^ (lane & 7)) << 4);
}

constexpr float SM_SCALE = 0.08838834764831845f * 1.4426950408889634f;
constexpr float SUM_HI = 1048576.f, SUM_LO = 1.0f / 1048576.f;

template <int I0, int I1, int J0>
__device__ __forceinline__ void mask_range(float (&S)[64], float limf) {
#pragma unroll
    for (int i = I0; i < I1; i++) {
        const int j = i >> 2;
        float t;
        asm("add.sat.f32 %0, %1, %2;" : "=f"(t) : "f"((float)(32 * (j >> 2) + 2 * (j & 3) + (i & 1) - (i & 2) * 4)), "f"(-limf));
        S[4 * J0 + i] = fmaf(t, -1e30f, S[4 * J0 + i]);
    }
}
template <int J0>
__device__ __forceinline__ void mask_half(float (&S)[64], float limf, int v) {
    asm volatile("" : "+f"(limf));
    if (v < 2) {
        mask_range<0, 16, J0>(S, limf);
#pragma unroll
        for (int i = 16; i < 32; i++) S[4 * J0 + i] = -1e30f;
    } else {
        mask_range<16, 32, J0>(S, limf);
    }
}
__device__ __forceinline__ void issue_qk(float (&S)[64], const uint32_t (&Q)[32], uint32_t d0) {
#pragma unroll
    for (int s = 0; s < 8; s++)
        wgmma_n128_rs<1>(S, Q[4 * s], Q[4 * s + 1], Q[4 * s + 2], Q[4 * s + 3], d0 + s * 128, s > 0);
}
template <int H>
__device__ __forceinline__ void issue_pv(float (&O)[64], const uint32_t (&Pm)[32], uint32_t d0, int acc) {
#pragma unroll
    for (int s = 4 * H; s < 4 * H + 4; s++)
        wgmma_n128_rs<0>(O, Pm[4 * s], Pm[4 * s + 1], Pm[4 * s + 2], Pm[4 * s + 3], d0 + H * (PAGE >> 4) + (s & 3) * 2, s > 0 ? 1 : acc);
}
template <int J0, int J1>
__device__ __forceinline__ void exp_groups(const float (&S)[64], uint32_t (&Pm)[32], float (&sum)[NSUM]) {
#pragma unroll
    for (int i = 2 * J0; i < 2 * J1; i++) asm volatile("" : "+r"(Pm[i])::"memory");
#pragma unroll
    for (int j = J0; j < J1; j++) {
        const float e0 = ex2(S[4 * j]), e1 = ex2(S[4 * j + 1]), e2 = ex2(S[4 * j + 2]), e3 = ex2(S[4 * j + 3]);
        if (NSUM == 4) {
            sum[0] = j ? sum[0] + e0 : e0; sum[2] = j ? sum[2] + e1 : e1; sum[1] = j ? sum[1] + e2 : e2; sum[3] = j ? sum[3] + e3 : e3;
        } else {
            sum[0] = (j ? sum[0] + e0 : e0) + e1; sum[1] = (j ? sum[1] + e2 : e2) + e3;
        }
        Pm[2 * j] = pack_bf16(e0, e1);
        Pm[2 * j + 1] = pack_bf16(e2, e3);
    }
}
__device__ __forceinline__ void shift_rows(float (&S)[64], float d0, float d1) {
#pragma unroll
    for (int j = 0; j < 16; j++) {
        S[4 * j] -= d0; S[4 * j + 1] -= d0; S[4 * j + 2] -= d1; S[4 * j + 3] -= d1;
    }
}
__device__ constexpr int chunk_src(int i) { return 4 * (4 * (i >> 3) + (i & 3)) + 2 * ((i >> 2) & 1); }
enum : uint32_t { CTL_FIRST = 1, CTL_SWITCH = 2, CTL_LAST = 4, CTL_HALF = 128, CTL_MASKHI = 256, CTL_WOUT = 512, CTL_PVHALF = 1024, CTL_PVACC = 16384,
                  CTL_SHIFT = 32768 };
__device__ __forceinline__ float quad_sum(float v) {
    v += __shfl_xor_sync(~0u, v, 1);
    return v + __shfl_xor_sync(~0u, v, 2);
}

__device__ __forceinline__ void store_part(uint8_t* base, uint32_t row_bits, int p, const uint32_t (&pk)[64]) {
    asm volatile("{\n.reg .b64 d0, d1;\nxor.b64 d0, %0, %1;\nxor.b64 d1, d0, 64;\n"
                 "TS: .branchtargets P0, P1, P2, P3, P4, P5, P6, P7;\n"
                 "brx.idx.uni %2, TS;\n"
                 "P0:\n st.global.cg.v4.u32 [d0 + 0], {%3, %4, %5, %6};\n st.global.cg.v4.u32 [d1 + 0], {%11, %12, %13, %14};\n bra.uni DONE;\n"
                 "P1:\n st.global.cg.v4.u32 [d0 + 0], {%7, %8, %9, %10};\n st.global.cg.v4.u32 [d1 + 0], {%15, %16, %17, %18};\n bra.uni DONE;\n"
                 "P2:\n st.global.cg.v4.u32 [d0 + 16384], {%19, %20, %21, %22};\n st.global.cg.v4.u32 [d1 + 16384], {%27, %28, %29, %30};\n bra.uni DONE;\n"
                 "P3:\n st.global.cg.v4.u32 [d0 + 16384], {%23, %24, %25, %26};\n st.global.cg.v4.u32 [d1 + 16384], {%31, %32, %33, %34};\n bra.uni DONE;\n"
                 "P4:\n st.global.cg.v4.u32 [d0 + 65536], {%35, %36, %37, %38};\n st.global.cg.v4.u32 [d1 + 65536], {%43, %44, %45, %46};\n bra.uni DONE;\n"
                 "P5:\n st.global.cg.v4.u32 [d0 + 65536], {%39, %40, %41, %42};\n st.global.cg.v4.u32 [d1 + 65536], {%47, %48, %49, %50};\n bra.uni DONE;\n"
                 "P6:\n st.global.cg.v4.u32 [d0 + 81920], {%51, %52, %53, %54};\n st.global.cg.v4.u32 [d1 + 81920], {%59, %60, %61, %62};\n bra.uni DONE;\n"
                 "P7:\n st.global.cg.v4.u32 [d0 + 81920], {%55, %56, %57, %58};\n st.global.cg.v4.u32 [d1 + 81920], {%63, %64, %65, %66};\n bra.uni DONE;\n"
                 "DONE:\n}\n"
                 ::"l"(base), "l"((uint64_t)((p & 1) ? row_bits : 0)), "r"(p), "r"(pk[0]), "r"(pk[1]), "r"(pk[2]), "r"(pk[3]), "r"(pk[4]), "r"(pk[5]), "r"(pk[6]), "r"(pk[7]), "r"(pk[8]), "r"(pk[9]), "r"(pk[10]), "r"(pk[11]), "r"(pk[12]), "r"(pk[13]), "r"(pk[14]), "r"(pk[15]), "r"(pk[16]), "r"(pk[17]), "r"(pk[18]), "r"(pk[19]), "r"(pk[20]), "r"(pk[21]), "r"(pk[22]), "r"(pk[23]), "r"(pk[24]), "r"(pk[25]), "r"(pk[26]), "r"(pk[27]), "r"(pk[28]), "r"(pk[29]), "r"(pk[30]), "r"(pk[31]), "r"(pk[32]), "r"(pk[33]), "r"(pk[34]), "r"(pk[35]), "r"(pk[36]), "r"(pk[37]), "r"(pk[38]), "r"(pk[39]), "r"(pk[40]), "r"(pk[41]), "r"(pk[42]), "r"(pk[43]), "r"(pk[44]), "r"(pk[45]), "r"(pk[46]), "r"(pk[47]), "r"(pk[48]), "r"(pk[49]), "r"(pk[50]), "r"(pk[51]), "r"(pk[52]), "r"(pk[53]), "r"(pk[54]), "r"(pk[55]), "r"(pk[56]), "r"(pk[57]), "r"(pk[58]), "r"(pk[59]), "r"(pk[60]), "r"(pk[61]), "r"(pk[62]), "r"(pk[63])
                 : "memory");
}

__device__ __forceinline__ void consumer(uint32_t sb, int pair, int c, uint8_t* out, const uint8_t* x) {
    const int tid = threadIdx.x;
    const int warp = __shfl_sync(~0u, tid >> 5, 0);
    const int w = warp >> 2, v = warp & 3, lane = tid & 31;

    const uint32_t empty_rel = lane == 2 ? mapa(sb + BAR_EMPTYL, c) : mapa(sb + BAR_EMPTY, lane & 1);
    auto release = [&](uint32_t grp) {
        if (lane < 3) mbar_arrive_cluster(empty_rel + (grp & 7) * 8);
    };
    auto wait_full = [&](uint32_t grp) { mbar_wait(sb + BAR_FULL + (grp & 7) * 8, (grp >> 3) & 1); };

    uint32_t g = 0;
    const uint32_t stg = sb + SM_REGION + w * PAGE + v * 2048;
    const uint32_t chunk0 = (lane >> 2) * 128 + (((lane & 3) ^ (lane >> 2)) << 4);
    uint32_t ndone = 0;
    auto mark_done = [&]() {
        __syncwarp();
        if (lane == 0) mbar_arrive(sb + BAR_DONE + (ndone & 1) * 8);
        ndone++;
    };
    auto ctx_dst = [&](int rnd, int seg) {
        const int rb = query_rowblock(pair, c, w, seg);
        return ptr_off(g_ctx, ((rb >> 1) * 64 + (rnd * 16 + (pair >> 2)) * 2) * PAGE + (rb & 1) * 8192 + v * 2048);
    };

    uint32_t ctl_tab;
    {
        const int t = lane, firstB = 2 * attn_rowblock(pair, 0) + 2 - w;
        auto is_half = [&](int u) { return (u == firstB - 1 || u == 16) && c == (u >= firstB); };
        auto block = [&](int u) { return u + (w == 1 && u >= firstB); };
        auto place = [](int j) { return ((j & 15) << 3) | ((j - (j * 43 >> 8) * 6) << 11); };
        const int jv = min(2 * block(t - 1) + 2, 35), jk = t == 17 ? jv : max(2 * block(t) - 1, 0);
        const bool diag = t == firstB - 1 || t == 16;
        ctl_tab = ((t == 0 || t == firstB) ? CTL_FIRST : 0) | (t == firstB ? CTL_SWITCH : 0) | (t == 17 ? CTL_LAST : 0) |
                  (diag ? (is_half(t) ? CTL_HALF : CTL_MASKHI) : 0) | (t == firstB + 1 ? CTL_WOUT : 0) |
                  (is_half(t - 1) ? CTL_PVHALF : 0) | ((t == 1 || t == firstB + 1) ? 0 : CTL_PVACC) |
                  place(jk) | ((place(jv) | (t ? 3 : 0)) << 16);
    }

    uint32_t pk[64];
#pragma unroll
    for (int i = 0; i < 64; i++) pk[i] = 0;
    uint8_t* pend = nullptr;
    uint32_t prow = 0x400;
    auto write_part = [&](int p) { store_part(pend, prow, p, pk); };
    if (w == 1) bar_arrive(2, 256);

    for (int item = 0; item < 6; item++) {
        if (ACOND) {
            constexpr int nk = DC / 64;
            float acc[128];
            auto issue_kblock = [&](int first_acc) {
                wait_full(g);
                const uint32_t pg = sb + (g & 3) * (3 * PAGE);
                const uint64_t da = make_desc(pg + w * 8192, 16), db = make_desc(pg + PAGE, 16);
                wg_fence();
                wgmma_n256_ss(acc, da, db, first_acc);
                wgmma_n256_ss(acc, da + 128, db + 2, 1);
                wgmma_n256_ss(acc, da + 256, db + 4, 1);
                wgmma_n256_ss(acc, da + 384, db + 6, 1);
                wg_commit();
                g++;
            };
            if (XAT == 0 && item == 0) {
                const uint8_t* src = ptr_off(x, ((pair * 2 + c) * 16 + warp * 2) * (DM * 2) + lane * 16);
#pragma unroll
                for (int i = 0; i < 8; i++) {
                    const uint4 t = __ldcg(reinterpret_cast<const uint4*>(src + i * 512));
                    pk[4 * i] = t.x; pk[4 * i + 1] = t.y; pk[4 * i + 2] = t.z; pk[4 * i + 3] = t.w;
                }
            }
            if (XAT == 3 && item == 0) {
                if (lane < 16) lsu_prefetch(ptr_off(x, ((pair * 2 + c) * 16 + warp * 2) * (DM * 2) + lane * 128));
            }
            if (item == 0) PROF(17, w);
            issue_kblock(0);
            if (item == 0) PROF(1, w);
            if (item == 0 && w == 0) PROF_GT(1);
            const int nparts = item == 0 ? 0 : (item == 3 ? 4 : 8);
            const int ln_row = (pair * 2 + c) * 16 + warp * 2;
            auto load_x = [&]() {
                const uint8_t* src = ptr_off(x, ln_row * (DM * 2) + lane * 16);
#pragma unroll
                for (int i = 0; i < 8; i++) {
                    const uint4 t = __ldcg(reinterpret_cast<const uint4*>(src + i * 512));
                    pk[4 * i] = t.x; pk[4 * i + 1] = t.y; pk[4 * i + 2] = t.z; pk[4 * i + 3] = t.w;
                }
            };
            if ((XAT == 1 || XAT == 3) && item == 0) load_x();
#pragma unroll 1
            for (int kb = 1; kb < nk; kb++) {
                if (kb == nk - 1 && w == 1) bar_sync(4, 256);
                issue_kblock(1);
                if (kb == nk - 1 && w == 0) bar_arrive(4, 256);
                wg_wait<1>();
                release(g - 2);
                if (kb <= nparts) {
                    if (item == 4 && kb == 1) mbar_wait(sb + BAR_DEP + 16, 0);
                    write_part(kb - 1);
                    if (kb == nk - 1) write_part(nk - 1);
                    if (kb == nparts || kb == nk - 1) mark_done();
                }
                if (g <= 8) {
                    if (XAT == 2 && g == XAT) load_x();
                    float s[2], q[2];
                    if (g == 4 + (LNSH > 0)) {
                        ln_sums<0>(pk, s[0], q[0]);
                        pk[32] = __float_as_uint(s[0]); pk[33] = __float_as_uint(q[0]);
                    }
                    if (g == 5 + (LNSH == 2)) {
                        ln_sums<16>(pk, s[1], q[1]);
                        pk[34] = __float_as_uint(s[1]); pk[35] = __float_as_uint(q[1]);
                    }
                    if (g == 6) {
#pragma unroll
                        for (int r = 0; r < 2; r++) { s[r] = __uint_as_float(pk[32 + 2 * r]); q[r] = __uint_as_float(pk[33 + 2 * r]); }
                        const bool hi = lane & 16, od = lane & 8;
                        float a = hi ? s[1] : s[0], b = hi ? q[1] : q[0];
                        a += __shfl_xor_sync(~0u, hi ? s[0] : s[1], 16);
                        b += __shfl_xor_sync(~0u, hi ? q[0] : q[1], 16);
                        float t = od ? b : a;
                        t += __shfl_xor_sync(~0u, od ? a : b, 8);
#pragma unroll
                        for (int o = 4; o; o >>= 1) t += __shfl_xor_sync(~0u, t, o);
#pragma unroll
                        for (int r = 0; r < 2; r++) {
                            s[r] = __shfl_sync(~0u, t, 16 * r);
                            q[r] = __shfl_sync(~0u, t, 16 * r + 8);
                        }
                        ln_finish(s[0], q[0], pk[36], pk[37], pk[38]);
                        ln_finish(s[1], q[1], pk[39], pk[40], pk[41]);
                    }
                    if (g == 7) ln_apply<0>(pk, pk[36], pk[37], pk[38], ptr_off(g_xn, image_offset(ln_row, lane)));
                    if (g == 8) {
                        ln_apply<16>(pk, pk[39], pk[40], pk[41], ptr_off(g_xn, image_offset(ln_row + 1, lane)));
                        mark_done();
                    }
                }
            }
            wg_wait<0>();
            reg_fence(acc);
            release(g - 1);
            PROF(2 + 2 * item, w);
            if (w == 0) PROF_GT(2 + 2 * item);
            const float ksc = (QSCALE || c) ? 1.0f : SM_SCALE;
#pragma unroll
            for (int i = 0; i < 64; i++) pk[i] = pack_bf16(acc[chunk_src(i)] * ksc, acc[chunk_src(i) + 1] * ksc);
            const uint32_t vrow = (v >> 1) * 32 + (lane >> 3) * 8 + (v & 1) * 4 + ((lane >> 2) & 1);
            pend = ptr_off(g_kv, ((kv_head(pair) + (item == 1 || item == 4 ? 8 : 0)) * 16 + kv_tokens(pair) * 2) * 65536 + w * 8192 +
                                     (c ? 32768 + vrow * 128 + (((lane & 3) ^ (vrow & 7)) << 4) : v * 2048 + chunk0));
            prow = c ? 0x120 : 0x400;
            PROF(3 + 2 * item, w);
            continue;
        }

        float O[64], S[64];
        auto issue_q = [&](int first_acc) {
            wait_full(g);
            const uint32_t pg = sb + (g & 3) * (3 * PAGE);
            const uint64_t da = make_desc(pg + w * 8192, 16), db = make_desc(pg + 2 * PAGE, 8192);
            const uint64_t dab = make_desc(pg + PAGE + (1 - w) * 8192, 16);
            wg_fence();
#pragma unroll
            for (int q = 0; q < 4; q++) wgmma_n128_ss(S, da + 2 * q, db + 128 * q, q ? 1 : first_acc);
            wg_commit();
#pragma unroll
            for (int q = 0; q < 4; q++) wgmma_n128_ss(O, dab + 2 * q, db + 128 * q, q ? 1 : first_acc);
            wg_commit();
            g++;
        };
        issue_q(0);
#pragma unroll 1
        for (int kb = 1; kb < DM / 64; kb++) {
            if (kb == DM / 64 - 2 && w == 1) bar_sync(4, 256);
            issue_q(1);
            if (kb == DM / 64 - 1 && w == 0) bar_arrive(4, 256);
            wg_wait<QSPLIT ? 2 : 1>();
            release(g - 2);
            if (kb <= 8) {
                write_part(kb - 1);
                if (kb == 8) mark_done();
            }
        }
        uint32_t Q[32], Pm[32];
#pragma unroll
        for (int i = 0; i < 32; i++) Pm[i] = PMINIT ? pk[i] : 0;
        float lim = (float)(v * 16 + (lane >> 2) - 8 * (lane & 3));
        float mc[2] = {0.f, 0.f}, l[2] = {0.f, 0.f}, scale[2] = {0.f, 0.f}, sum[NSUM];
        uint32_t ctl = __shfl_sync(~0u, ctl_tab, 0), nxt = __shfl_sync(~0u, ctl_tab, 1);
        int t = 1;
        asm volatile("" : "+f"(lim), "+f"(mc[0]), "+f"(mc[1]), "+f"(l[0]), "+f"(l[1]), "+r"(ctl), "+r"(nxt), "+r"(t));
        constexpr float qsc = QSCALE ? SM_SCALE : 1.0f;
        wg_wait<QSPLIT ? 1 : 0>();
        reg_fence(S);
#pragma unroll
        for (int i = 0; i < 32; i++) Q[i] = pack_bf16(S[2 * i] * qsc, S[2 * i + 1] * qsc);
        reg_fence(Q);
        wait_full(g);
        wg_wait<0>();
        reg_fence(O);
        release(g - 1);
        PROF(2 + 2 * item, w);
        if (w == 0) PROF_GT(2 + 2 * item);

        const uint32_t qaddr = QOPQ ? __shfl_sync(~0u, stg + lane * 16, lane) : stg + lane * 16;
        auto put_queries = [&](const float (&A)[64]) {
#pragma unroll
            for (int i = 0; i < 8; i++)
                sts128(qaddr + (i >> 2) * 8192 + (i & 3) * 512, pack_bf16(A[8 * i] * qsc, A[8 * i + 1] * qsc), pack_bf16(A[8 * i + 2] * qsc, A[8 * i + 3] * qsc),
                       pack_bf16(A[8 * i + 4] * qsc, A[8 * i + 5] * qsc), pack_bf16(A[8 * i + 6] * qsc, A[8 * i + 7] * qsc));
        };
        auto get_queries = [&](int i0, int i1) {
#pragma unroll
            for (int i = i0; i < i1; i++) lds128(qaddr + (i >> 2) * 8192 + (i & 3) * 512, Q[4 * i], Q[4 * i + 1], Q[4 * i + 2], Q[4 * i + 3]);
        };
        const uint32_t kdesc0 = (uint32_t)make_desc(sb, PAGE), vdesc0 = (uint32_t)make_desc(sb, 16);
        auto wait_block = [&](uint32_t word) { mbar_wait(sb + BAR_FULL + (word & 56), (word >> 6) & 1); };
        auto write_out = [&](auto early) {
            uint8_t* dst = ctx_dst(item == 5, 0);
            uint8_t* d[2] = {ptr_off(dst, chunk0), ptr_off(dst, chunk0 ^ 64)};
#pragma unroll
            for (int i = early.value ? 0 : WN; i < (early.value ? WN : 8); i++) {
                const float sc = scale[i & 1];
                uint32_t q[4];
#pragma unroll
                for (int k = 0; k < 4; k++) q[k] = pack_bf16(O[chunk_src(4 * i + k)] * sc, O[chunk_src(4 * i + k) + 1] * sc);
                if (WINP && early.value && i > 0) {
#pragma unroll
                    for (int k = 0; k < 4; k++) O[4 * (i - 1) + k] = __uint_as_float(q[k]);
                }
                __stcg(reinterpret_cast<uint4*>(d[(i >> 1) & 1] + (i >> 2) * PAGE + (i & 1) * 1024), make_uint4(q[0], q[1], q[2], q[3]));
            }
            if (early.value == (WN == 8)) mark_done();
        };
        put_queries(O);
        bar_sync(2 + w, 256);
        wg_fence();
        issue_qk(S, Q, kdesc0);
        wg_commit();
        wg_fence();
        wg_commit();
        wg_commit();
        bar_arrive(3 - w, 256);
        for (;;) {
            const bool kready = KTRY ? mbar_try(sb + BAR_FULL + (nxt & 56), (nxt >> 6) & 1) : true;
            if (!KTRY) wait_block(nxt);
            wg_wait<2>();
            reg_fence(S);
            if (ctl & (CTL_HALF | CTL_MASKHI | CTL_SHIFT)) {
                if (LQN < 8 && (nxt & CTL_SWITCH)) get_queries(LQN, 8);
                if (ctl & CTL_HALF) mask_half<0>(S, lim, v);
                if (ctl & CTL_MASKHI) mask_half<8>(S, lim, v);
                if (ctl & CTL_SHIFT) shift_rows(S, mc[0], mc[1]);
            }
            float early[4 * EARLY + 1];
#pragma unroll
            for (int j = 0; j < EARLY; j++) {
#pragma unroll
                for (int i = 4 * j; i < 4 * j + 4; i++) early[i] = ex2(S[i]);
                sum[0] = (j ? sum[0] + early[4 * j] : early[4 * j]) + early[4 * j + 1];
                sum[1] = (j ? sum[1] + early[4 * j + 2] : early[4 * j + 2]) + early[4 * j + 3];
            }
            const uint32_t tie = EARLY ? __float_as_uint(sum[0]) & __float_as_uint(sum[1]) & (ctl & 0x80000000u) : 0;
            if (lane < 3) mbar_arrive_cluster(empty_rel + tie + (ctl & 56));
            wg_wait<1>();
#pragma unroll
            for (int j = 0; j < EARLY; j++) {
                asm volatile("" : "+r"(Pm[2 * j]), "+r"(Pm[2 * j + 1])::"memory");
                Pm[2 * j] = pack_bf16(early[4 * j], early[4 * j + 1]);
                Pm[2 * j + 1] = pack_bf16(early[4 * j + 2], early[4 * j + 3]);
            }
            exp_groups<EARLY, 8>(S, Pm, sum);
            const bool half = ctl & CTL_HALF;
            if (!half) {
                wg_wait<0>();
                reg_fence(O);
                if (lane < ((ctl >> 16) & 3)) mbar_arrive_cluster(empty_rel + ((ctl >> 16) & 56));
                exp_groups<8, 16>(S, Pm, sum);
            } else {
                asm volatile("wgmma.wait_group.sync.aligned 0;\n" ::: "memory");
                reg_fence(O);
                if (lane < ((ctl >> 16) & 3)) asm volatile("mbarrier.arrive.shared::cluster.b64 _, [%0];\n" ::"r"(empty_rel + ((ctl >> 16) & 56)) : "memory");
            }
            if (NSUM == 4) { sum[0] += sum[2]; sum[1] += sum[3]; }
            const bool over = !(sum[0] + sum[1] <= SUM_HI);
            if (__any_sync(~0u, over || !kready) || (((ctl & CTL_FIRST) | (nxt & (CTL_SWITCH | CTL_LAST))) != 0)) {
                bool bad = __any_sync(~0u, over);
                if (KTRY && !kready) wait_block(nxt);
                const bool first = ctl & CTL_FIRST;
                if (first) {
                    uint32_t b0 = __ballot_sync(~0u, sum[0] >= SUM_LO), b1 = __ballot_sync(~0u, sum[1] >= SUM_LO);
                    b0 |= b0 >> 1; b1 |= b1 >> 1;
                    b0 |= b0 >> 2; b1 |= b1 >> 2;
                    bad |= (b0 & b1 & 0x11111111u) != 0x11111111u;
                }
                if (bad) {
                    if (half) {
#pragma unroll
                        for (int i = 32; i < 64; i++) S[i] = -INFINITY;
                    }
                    float d0 = fmaxf(S[0], S[1]), d1 = fmaxf(S[2], S[3]);
#pragma unroll
                    for (int j = 1; j < 16; j++) {
                        d0 = fmaxf(d0, fmaxf(S[4 * j], S[4 * j + 1]));
                        d1 = fmaxf(d1, fmaxf(S[4 * j + 2], S[4 * j + 3]));
                    }
                    d0 = fmaxf(d0, __shfl_xor_sync(~0u, d0, 1));
                    d1 = fmaxf(d1, __shfl_xor_sync(~0u, d1, 1));
                    d0 = fmaxf(d0, __shfl_xor_sync(~0u, d0, 2));
                    d1 = fmaxf(d1, __shfl_xor_sync(~0u, d1, 2));
                    if (!first) {
                        d0 = fmaxf(d0, 0.f);
                        d1 = fmaxf(d1, 0.f);
                        const float a0 = ex2(-d0), a1 = ex2(-d1);
#pragma unroll
                        for (int j = 0; j < 16; j++) {
                            O[4 * j] *= a0; O[4 * j + 1] *= a0; O[4 * j + 2] *= a1; O[4 * j + 3] *= a1;
                        }
                        l[0] *= a0; l[1] *= a1;
                    }
                    mc[0] += d0; mc[1] += d1;
                    ctl_tab |= CTL_SHIFT;
                    nxt |= CTL_SHIFT;
                    shift_rows(S, d0, d1);
                    exp_groups<0, 16>(S, Pm, sum);
                    if (NSUM == 4) { sum[0] += sum[2]; sum[1] += sum[3]; }
                }
                if (WN && (ctl & CTL_SWITCH)) write_out(std::true_type());
                if (nxt & CTL_LAST) break;
                if (nxt & CTL_SWITCH) {
                    get_queries(0, LQN);
                    nxt &= ~CTL_SHIFT;
                    ctl_tab &= ~CTL_SHIFT;
                }
            }
            ctl = nxt;
            bar_sync(2 + w, 256);
            wg_fence();
            issue_qk(S, Q, kdesc0 + (ctl & 0x3800));
            wg_commit();
            l[0] += sum[0]; l[1] += sum[1];
            nxt = __shfl_sync(~0u, ctl_tab, ++t);
            if (ctl & (CTL_SWITCH | CTL_WOUT)) {
                if (ctl & CTL_SWITCH) {
                    scale[0] = rcp_approx(quad_sum(l[0]));
                    scale[1] = rcp_approx(quad_sum(l[1]));
                    l[0] = l[1] = mc[0] = mc[1] = 0.f;
                    if (w == 1) { release((ctl >> 3) - 2); release((ctl >> 3) + 1); }
                } else {
                    write_out(std::false_type());
                }
            }
            wait_block(ctl >> 16);
            const uint32_t vdesc = vdesc0 + ((ctl >> 16) & 0x3800);
            if (!(ctl & CTL_PVHALF)) {
                wg_fence();
                issue_pv<0>(O, Pm, vdesc, ctl & CTL_PVACC);
                wg_commit();
                issue_pv<1>(O, Pm, vdesc, 1);
                wg_commit();
            } else {
                wg_fence();
                issue_pv<0>(O, Pm, vdesc, ctl & CTL_PVACC);
                wg_commit();
                wg_commit();
            }
            bar_arrive(3 - w, 256);
        }
        g += 36;
        if (w == 0) release(g - 3);
        if (WN < 8 && (nxt & CTL_WOUT)) write_out(std::false_type());
        const uint32_t vdesc = vdesc0 + (nxt & 0x3800);
        if (nxt & CTL_PVHALF) {
            wg_fence();
            issue_pv<0>(O, Pm, vdesc, nxt & CTL_PVACC);
            wg_commit();
        } else {
            wg_fence();
            issue_pv<0>(O, Pm, vdesc, nxt & CTL_PVACC);
            issue_pv<1>(O, Pm, vdesc, 1);
            wg_commit();
        }
        l[0] += sum[0]; l[1] += sum[1];
        ctl_tab = (ctl_tab & ~(0x00780078u | CTL_SHIFT)) | ((ctl_tab + 0x00200020u) & 0x00780078u);
        const float i0 = rcp_approx(quad_sum(l[0])), i1 = rcp_approx(quad_sum(l[1]));
        wg_wait<0>();
        reg_fence(O);
        if (w == 0) release(g - 2);
        release(g - 1);
#pragma unroll
        for (int i = 0; i < 32; i++) {
            const float sc = (i & 4) ? i1 : i0;
            pk[i] = pack_bf16(O[chunk_src(i)] * sc, O[chunk_src(i) + 1] * sc);
        }
        pend = ptr_off(ctx_dst(item == 5, 1), chunk0);
        prow = 0x400;
#pragma unroll
        for (int i = 32; i < 64; i++) pk[i] = 0;
        PROF(3 + 2 * item, w);
        if (w == 0) PROF_GT(3 + 2 * item);
    }

    float acc[64];
    uint32_t slot = 0;
    auto issue_out = [&](int first_acc) {
        wait_full(g);
        const uint64_t da = make_desc(sb + slot + w * 8192, 16), db = make_desc(sb + slot + PAGE, 8192);
        wg_fence();
#pragma unroll
        for (int q = 0; q < 4; q++) wgmma_n128_ss(acc, da + 2 * q, db + 128 * q, q ? 1 : first_acc);
        wg_commit();
        g++;
        slot = slot == SM_REGION - 2 * PAGE ? 0 : slot + 2 * PAGE;
    };
    issue_out(0);
#pragma unroll 1
    for (int kb = 1; kb < 64 - PEEL; kb++) {
        issue_out(1);
        wg_wait<1>();
        if (kb <= 58) release(g - 2);
        if (kb <= 8 && !(kb & 1)) {
            write_part((kb >> 1) - 1);
            if (kb == 8) mark_done();
        }
        if (kb >= 32 - PEEL && ((kb + PEEL) & 3) == 2 * w) {
            uint32_t u0, u1, u2, u3;
            const uint32_t a = stg + ((kb + PEEL) & 16) * 512 + ((kb + PEEL) & 12) * 128 + lane * 16;
            mbar_wait(sb + BAR_G + w * 8, 0);
            lds128(a, u0, u1, u2, u3);
            sts128(a, pack_bf16(silu_f(bf_lo(u0)), silu_f(bf_hi(u0))), pack_bf16(silu_f(bf_lo(u1)), silu_f(bf_hi(u1))),
                   pack_bf16(silu_f(bf_lo(u2)), silu_f(bf_hi(u2))), pack_bf16(silu_f(bf_lo(u3)), silu_f(bf_hi(u3))));
        }
    }
    const uint32_t goff = (((pair >> 1) & 7) * 256 + c * 128 + w * 64 + v * 16 + (lane >> 3)) * (DM * 2) +
                          ((pair >> 4) * 256 + (pair & 1) * 128) * 2 + (((lane & 7) ^ (lane >> 3)) << 4);
    uint32_t xr[32], gr[32];
    {
        const uint8_t* src[2] = {ptr_off(x, goff), ptr_off(x, goff ^ 64)};
#pragma unroll
        for (int i = 0; i < 8; i++) {
            const uint4 t = __ldcg(reinterpret_cast<const uint4*>(src[i & 1] + (i & 3) * (4 * DM * 2) + (i >> 2) * 128));
            xr[4 * i] = t.x; xr[4 * i + 1] = t.y; xr[4 * i + 2] = t.z; xr[4 * i + 3] = t.w;
        }
    }
#pragma unroll 1
    for (int i = 0; i < PEEL; i++) {
        issue_out(1);
        wg_wait<1>();
        if (PEEL > 5 && i < PEEL - 5) release(g - 2);
    }
    asm volatile("barrier.cluster.arrive.relaxed.aligned;" ::: "memory");
#pragma unroll
    for (int i = 0; i < 8; i++) lds128(stg + (i >> 2) * 8192 + (i & 3) * 512 + lane * 16, gr[4 * i], gr[4 * i + 1], gr[4 * i + 2], gr[4 * i + 3]);
    uint8_t* dst[2] = {ptr_off(out, goff), ptr_off(out, goff ^ 64)};
    __syncwarp();
    wg_wait<0>();
    reg_fence(acc);
    PROF(14, w);
    if (w == 0) PROF_GT(14);
#pragma unroll
    for (int h = 0; h < 2; h++) {
#pragma unroll
        for (int s = 4 * h; s < 4 * h + 4; s++)
            stmatrix_x4(slab_addr(stg, lane, s), pack_bf16(acc[8 * s], acc[8 * s + 1]), pack_bf16(acc[8 * s + 2], acc[8 * s + 3]),
                        pack_bf16(acc[8 * s + 4], acc[8 * s + 5]), pack_bf16(acc[8 * s + 6], acc[8 * s + 7]));
        __syncwarp();
#pragma unroll
        for (int i = 4 * h; i < 4 * h + 4; i++) {
            uint32_t o[4];
            lds128(stg + h * 8192 + (i & 3) * 512 + lane * 16, o[0], o[1], o[2], o[3]);
#pragma unroll
            for (int k = 0; k < 4; k++) xr[4 * i + k] = bf2_add(xr[4 * i + k], bf2_mul(o[k], gr[4 * i + k]));
            __stcg(reinterpret_cast<uint4*>(dst[i & 1] + (i & 3) * (4 * DM * 2) + h * 128), make_uint4(xr[4 * i], xr[4 * i + 1], xr[4 * i + 2], xr[4 * i + 3]));
        }
    }
    PROF(28, w);
}

__global__ void __cluster_dims__(2, 1, 1) __launch_bounds__(384, 1)
fused_kernel(const __grid_constant__ CUtensorMap m_ckv, const __grid_constant__ CUtensorMap m_wuk,
             const __grid_constant__ CUtensorMap m_wuv, const __grid_constant__ CUtensorMap m_wq,
             const __grid_constant__ CUtensorMap m_wo, const __grid_constant__ CUtensorMap m_gate,
             const __grid_constant__ CUtensorMap m_up, const __grid_constant__ CUtensorMap m_down, const Params P) {
    extern __shared__ __align__(1024) uint8_t smem[];
    const uint32_t sb = __shfl_sync(~0u, smem_u32(smem), 0);
    const int tid = threadIdx.x;
    const int cl = blockIdx.x >> 1, c = blockIdx.x & 1;
    const int pair = cl >= 64 ? cl : cl < 4 ? cl * 16 + 15 : cl < 36 ? ((cl - 4) >> 3) * 16 + ((cl - 4) & 7)
                                                                    : ((cl - 36) / 7) * 16 + 8 + (cl - 36) % 7;
    const bool starter = tid == 256 && pair < NMAIN / 2;
    const CUtensorMap* m_wu = c ? &m_wuv : &m_wuk;
    if (tid == 256) {
        mbar_init(sb + BAR_FULL, 1);
        if (starter) {
            asm volatile("fence.mbarrier_init.release.cluster;" ::: "memory");
            mbar_expect_tx(sb + BAR_FULL, 3 * PAGE);
            tma_3d(sb, m_wu, 0, 0, kv_head(pair) * 2, sb + BAR_FULL);
            tma_3d(sb + PAGE, &m_ckv, 0, kv_tokens(pair) * 256, 0, sb + BAR_FULL);
            tma_3d(sb + 2 * PAGE, &m_ckv, 0, kv_tokens(pair) * 256 + 128, 0, sb + BAR_FULL);
        }
#pragma unroll
        for (int i = START == 2; i < NBAR; i++) mbar_init(sb + SM_BAR + i * 8, (i >> 3) == 1 ? 16 : i >= 25 ? 8 : 1);
        asm volatile("fence.mbarrier_init.release.cluster;" ::: "memory");
    }
    if (starter) {
        if (START != 2) prefetch_map(&m_ckv);
        if (START == 1) mbar_arrive(sb + BAR_FULL);
#pragma unroll 1
        for (int kb = START ? 1 : 0; kb < 4; kb++) {
            mbar_expect_tx(sb + BAR_FULL + kb * 8, 3 * PAGE);
            if (kb < EARLYW) tma_3d(sb + kb * (3 * PAGE), m_wu, 0, kb * 64, kv_head(pair) * 2, sb + BAR_FULL + kb * 8);
        }
    }
    PROF(18, (tid >> 7) & 1);
    __syncthreads();
    cluster_sync();
    PROF(22, (tid >> 7) & 1);
    auto start_loads = [&]() {
#pragma unroll 1
        for (int kb = START ? 1 : 0; kb < 4; kb++) {
            if (kb >= EARLYW) tma_3d(sb + kb * (3 * PAGE), m_wu, 0, kb * 64, kv_head(pair) * 2, sb + BAR_FULL + kb * 8);
            tma_3d_mc(sb + kb * (3 * PAGE) + (1 + c) * PAGE, &m_ckv, 0, kv_tokens(pair) * 256 + c * 128, kb, sb + BAR_FULL + kb * 8);
        }
    };
    if (!LATEMC && starter) start_loads();
    PROF(19, (tid >> 7) & 1);
    const int warp = __shfl_sync(~0u, tid >> 5, 0), lane = tid & 31;
    auto dump_prof = [&]() {
    };
    if (pair >= NMAIN / 2) {
        if (warp < 8) ffn_cta(smem, sb, blockIdx.x - NMAIN, __ldcg(&g_sync.done) / NCTA, P.w_r);
        else if (tid == 256) ffn_producer(sb, blockIdx.x - NMAIN, &m_gate, &m_up, &m_down);
        __syncwarp();
        PROF(29, tid >> 7);
        cluster_sync();
        if (tid == 0) atomicAdd(&g_sync.done, 1u);
        if (warp < 8) dump_prof();
    } else if (warp < 8) {
        asm volatile("setmaxnreg.inc.sync.aligned.u32 232;");
        consumer(sb, pair, c, P.out, (const uint8_t*)P.x);
        PROF(29, tid >> 7);
        asm volatile("barrier.cluster.wait.aligned;" ::: "memory");
        dump_prof();
    } else {
        asm volatile("setmaxnreg.dec.sync.aligned.u32 40;");
        if (LATEMC && starter) start_loads();
        if (PF4 && warp == 9) {
            const int cta = pair * 2 + c;
            if (lane < 16 * PF4) lsu_prefetch(ptr_off((cta & 64) ? P.w_uv : P.w_uk, (256 + (lane >> 4) * 64 + (cta & 63)) * 8192 + (lane & 15) * 128));
            lsu_prefetch(ptr_off(P.c_kv, (cta * 16 + (lane >> 1)) * 1024 + 512 + (lane & 1) * 128));
        }
        if (warp == 10) {
            sync_helper(sb, lane, pair, c);
        } else if (warp & 1) {
            fetch_helper((warp & 2) ? P.w_uv : P.w_uk, (const uint8_t*)P.x, sb, (warp >> 1) & 1, lane, pair, c);
        } else {
            producer(P, sb, pair, c, &m_ckv, m_wu, &m_wq, &m_wo);
        }
        bar_sync(6, 128);
        if (tid == 256) atomicAdd(&g_sync.done, 1u);
        cluster_sync();
    }
}

typedef CUresult (*EncodeFn)(CUtensorMap*, CUtensorMapDataType, cuuint32_t, void*, const cuuint64_t*, const cuuint64_t*,
                             const cuuint32_t*, const cuuint32_t*, CUtensorMapInterleave, CUtensorMapSwizzle,
                             CUtensorMapL2promotion, CUtensorMapFloatOOBfill);

void make_map_w(EncodeFn fn, CUtensorMap* m, const void* ptr, int rows, int cols, int blocks, int box_rows = 32) {
    cuuint64_t dims[3] = {64, (cuuint64_t)rows, (cuuint64_t)cols / 64};
    cuuint64_t strides[2] = {(cuuint64_t)cols * 2, 128};
    cuuint32_t box[3] = {64, (cuuint32_t)box_rows, (cuuint32_t)blocks};
    cuuint32_t es[3] = {1, 1, 1};
    fn(m, CU_TENSOR_MAP_DATA_TYPE_BFLOAT16, 3, const_cast<void*>(ptr), dims, strides, box, es, CU_TENSOR_MAP_INTERLEAVE_NONE,
       CU_TENSOR_MAP_SWIZZLE_128B, CU_TENSOR_MAP_L2_PROMOTION_L2_256B, CU_TENSOR_MAP_FLOAT_OOB_FILL_NONE);
}

}

extern "C" void kernel_launch(void* const* d_in, const int* in_sizes, int n_in, void* d_out, int out_size) {
    static EncodeFn fn = nullptr;
    if (!fn) {
        void* f = nullptr;
        cudaDriverEntryPointQueryResult qr;
        cudaGetDriverEntryPoint("cuTensorMapEncodeTiled", &f, cudaEnableDefault, &qr);
        fn = (EncodeFn)f;
        cudaFuncSetAttribute(fused_kernel, cudaFuncAttributeMaxDynamicSharedMemorySize, SMEM_BYTES);
    }
    CUtensorMap m_ckv, m_wuk, m_wuv, m_wq, m_wo, m_gate, m_up, m_down;
    make_map_w(fn, &m_gate, d_in[8], DM, FF, FS / 64, 16);
    make_map_w(fn, &m_up, d_in[9], DM, FF, FS / 64, 16);
    make_map_w(fn, &m_down, d_in[10], FF, DM, DM / 64, 16);
    make_map_w(fn, &m_ckv, d_in[1], SEQ, DC, 1, 128);
    make_map_w(fn, &m_wq, d_in[2], DM, NH * 128, 1, 64);
    make_map_w(fn, &m_wuk, d_in[3], DC, NH * 128, 2, 64);
    make_map_w(fn, &m_wuv, d_in[4], DC, NH * 128, 2, 64);
    make_map_w(fn, &m_wo, d_in[5], NH * 128, DM, 1, 64);
    Params P;
    P.x = (const __nv_bfloat16*)d_in[0];
    P.w_r = (const __nv_bfloat16*)d_in[7];
    P.c_kv = (const uint8_t*)d_in[1];
    P.w_uk = (const uint8_t*)d_in[3];
    P.w_uv = (const uint8_t*)d_in[4];
    P.out = (uint8_t*)d_out;
    fused_kernel<<<NCTA, 384, SMEM_BYTES>>>(m_ckv, m_wuk, m_wuv, m_wq, m_wo, m_gate, m_up, m_down, P);
}
```

```cpp
#include <cuda_runtime.h>
#include <cuda_bf16.h>
#include <cuda.h>
#include <stdint.h>
#define TBAR 0
#define STAG 3
#define PEEL 5
#define PF4 0
#define FDELAY 1
#define LNSH 0
#define FETCH_INL __noinline__
#define RDUM 0
#define UBAD 0
#define ACOND ((0x1B >> item) & 1)
#define LATEMC 1
#define START 2
#define XAT 1
#include <type_traits>
#define WN 6
#define WINP 1
#define LQN 8
#define LQPOS 1
#define QOPQ 0
#define NTIE 1
#define KTRY 1
#define MASKV 1
#define EREL 0
#define NSUM 2
#define EARLY 2
#define PMINIT 1
#define QSPLIT 1
#define PARK0 1
#define MG 8
#define LQEND 4
#define QKORD 1
#define BALLOT 1
#define AMAP 1
#define EARLYW 2
#define QSCALE 1
#define INPLACE 1

namespace {

constexpr int SEQ = 2048, DM = 1024, NH = 32, DC = 512, FF = 3584;
constexpr int PAGE = 16384;
constexpr int NRING = 12;
constexpr int NCTA = 132, NMAIN = 128;
constexpr uint32_t SM_REGION = NRING * PAGE;
constexpr uint32_t SM_BAR = (NRING + 2) * PAGE;
constexpr uint32_t BAR_FULL = SM_BAR, BAR_EMPTY = SM_BAR + 64;
constexpr uint32_t BAR_DEP = SM_BAR + 128;
constexpr uint32_t BAR_G = SM_BAR + 184;
constexpr uint32_t BAR_DONE = SM_BAR + 200;
constexpr uint32_t BAR_EMPTYL = SM_BAR + 216;
constexpr int NBAR = 35;
constexpr uint32_t SM_PROF = SM_BAR + 320;
constexpr int SMEM_BYTES = SM_PROF + 512;
constexpr uint32_t SPIN_LIMIT = 1u << 16;
constexpr uint32_t POLL_MASK = 7;

struct SyncBlock {
    unsigned done;       unsigned pad0[31];
    unsigned ln;         unsigned pad1[31];
    unsigned router;     unsigned pad4[31];
    unsigned ffn_ticket; unsigned pad2[31];
    unsigned ffn_done;   unsigned pad3[31];
    unsigned kv[NH * 8];
    unsigned kvfree[16 * 8];
    unsigned ctx[32 * NH];
};

__device__ __align__(1024) uint8_t g_xn[8 * 16 * 4 * 8192];
__device__ __align__(4096) uint8_t g_kv[16 * 16 * 65536];
__device__ __align__(4096) uint8_t g_ctx[16 * 64 * 16384];
__device__ __align__(16) uint4 g_routed[2 * 128];
__device__ int g_sel[2];
__device__ __align__(16) float g_r[SEQ];
__device__ __align__(16) float g_ypart[4 * 2 * DM];
__device__ SyncBlock g_sync;

__device__ __forceinline__ uint32_t smem_u32(const void* p) { return (uint32_t)__cvta_generic_to_shared(p); }

__device__ __forceinline__ void mbar_init(uint32_t bar, uint32_t count) {
    asm volatile("mbarrier.init.shared::cta.b64 [%0], %1;" ::"r"(bar), "r"(count) : "memory");
}
#define MBAR_WAIT_ASM(HINT, LIMIT)                                                                  \
    asm volatile("{\n.reg .pred p;\n.reg .u32 n;\nmov.u32 n, 0;\n"                                  \
                 "WAIT_LOOP:\n"                                                                     \
                 "mbarrier.try_wait.parity.shared::cta.b64 p, [%0], %1" HINT ";\n"                  \
                 "@p bra WAIT_DONE;\n"                                                              \
                 "add.u32 n, n, 1;\n"                                                               \
                 "setp.lt.u32 p, n, " LIMIT ";\n"                                                   \
                 "@p bra WAIT_LOOP;\n"                                                              \
                 "WAIT_DONE:\n}\n" ::"r"(bar), "r"(parity) : "memory")
__device__ __forceinline__ void mbar_wait(uint32_t bar, uint32_t parity) { MBAR_WAIT_ASM("", "131072"); }
__device__ __forceinline__ void mbar_sleep(uint32_t bar, uint32_t parity) { MBAR_WAIT_ASM(", 2000", "8192"); }
__device__ __forceinline__ bool mbar_try(uint32_t bar, uint32_t parity) {
    uint32_t ok;
    asm volatile("{\n.reg .pred p;\nmbarrier.try_wait.parity.shared::cta.b64 p, [%1], %2;\nselp.u32 %0, 1, 0, p;\n}\n"
                 : "=r"(ok) : "r"(bar), "r"(parity) : "memory");
    return ok;
}
__device__ __forceinline__ bool mbar_test(uint32_t bar, uint32_t parity) {
    uint32_t ok;
    asm volatile("{\n.reg .pred p;\nmbarrier.test_wait.parity.shared::cta.b64 p, [%1], %2;\nselp.u32 %0, 1, 0, p;\n}\n"
                 : "=r"(ok) : "r"(bar), "r"(parity) : "memory");
    return ok;
}
__device__ __forceinline__ bool elect_one() {
    uint32_t ok;
    asm volatile("{\n.reg .pred p;\nelect.sync _|p, 0xffffffff;\nselp.u32 %0, 1, 0, p;\n}\n" : "=r"(ok));
    return ok;
}
__device__ __forceinline__ void mbar_arrive(uint32_t bar) {
    asm volatile("mbarrier.arrive.shared::cta.b64 _, [%0];" ::"r"(bar) : "memory");
}
__device__ __forceinline__ void mbar_expect_tx(uint32_t bar, uint32_t bytes) {
    asm volatile("mbarrier.arrive.expect_tx.shared::cta.b64 _, [%0], %1;" ::"r"(bar), "r"(bytes) : "memory");
}
__device__ __forceinline__ void mbar_arrive_cluster(uint32_t cluster_addr) {
    asm volatile("mbarrier.arrive.shared::cluster.b64 _, [%0];" ::"r"(cluster_addr) : "memory");
}
__device__ __forceinline__ uint32_t mapa(uint32_t addr, uint32_t rank) {
    uint32_t r;
    asm("mapa.shared::cluster.u32 %0, %1, %2;" : "=r"(r) : "r"(addr), "r"(rank));
    return r;
}
__device__ __forceinline__ void tma_3d(uint32_t dst, const CUtensorMap* m, int c0, int c1, int c2, uint32_t bar) {
    asm volatile("cp.async.bulk.tensor.3d.shared::cluster.global.mbarrier::complete_tx::bytes [%0], [%1, {%3, %4, %5}], [%2];"
                 ::"r"(dst), "l"(m), "r"(bar), "r"(c0), "r"(c1), "r"(c2) : "memory");
}
__device__ __forceinline__ void tma_3d_hint(uint32_t dst, const CUtensorMap* m, int c0, int c1, int c2, uint32_t bar, uint64_t pol) {
    asm volatile("cp.async.bulk.tensor.3d.shared::cluster.global.mbarrier::complete_tx::bytes.L2::cache_hint [%0], [%1, {%3, %4, %5}], [%2], %6;"
                 ::"r"(dst), "l"(m), "r"(bar), "r"(c0), "r"(c1), "r"(c2), "l"(pol) : "memory");
}
__device__ __forceinline__ void tma_3d_mc(uint32_t dst, const CUtensorMap* m, int c0, int c1, int c2, uint32_t bar) {
    asm volatile("cp.async.bulk.tensor.3d.shared::cluster.global.mbarrier::complete_tx::bytes.multicast::cluster [%0], [%1, {%3, %4, %5}], [%2], %6;"
                 ::"r"(dst), "l"(m), "r"(bar), "r"(c0), "r"(c1), "r"(c2), "h"((uint16_t)3) : "memory");
}
__device__ __forceinline__ void bulk_load(uint32_t dst, const void* src, uint32_t bytes, uint32_t bar) {
    asm volatile("cp.async.bulk.shared::cluster.global.mbarrier::complete_tx::bytes [%0], [%1], %2, [%3];"
                 ::"r"(dst), "l"(src), "r"(bytes), "r"(bar) : "memory");
}
__device__ __forceinline__ void cp_async16(uint32_t dst, const void* src) {
    asm volatile("cp.async.cg.shared.global [%0], [%1], 16;" ::"r"(dst), "l"(src) : "memory");
}
__device__ __forceinline__ void bulk_load_mc(uint32_t dst, const void* src, uint32_t bytes, uint32_t bar) {
    asm volatile("cp.async.bulk.shared::cluster.global.mbarrier::complete_tx::bytes.multicast::cluster [%0], [%1], %2, [%3], %4;"
                 ::"r"(dst), "l"(src), "r"(bytes), "r"(bar), "h"((uint16_t)3) : "memory");
}
__device__ __forceinline__ void tma_store_2d(const CUtensorMap* m, int c0, int c1, uint32_t src) {
    asm volatile("cp.async.bulk.tensor.2d.global.shared::cta.bulk_group [%0, {%2, %3}], [%1];"
                 ::"l"(m), "r"(src), "r"(c0), "r"(c1) : "memory");
}
__device__ __forceinline__ void bulk_commit() { asm volatile("cp.async.bulk.commit_group;" ::: "memory"); }
__device__ __forceinline__ void bulk_wait_read() { asm volatile("cp.async.bulk.wait_group.read 0;" ::: "memory"); }
__device__ __forceinline__ void fence_async_smem() { asm volatile("fence.proxy.async.shared::cta;" ::: "memory"); }
__device__ __forceinline__ void prefetch_map(const CUtensorMap* m) {
    asm volatile("prefetch.tensormap [%0];" ::"l"(m) : "memory");
}
__device__ __forceinline__ void red_release(unsigned* p) {
    asm volatile("red.release.gpu.global.add.u32 [%0], 1;" ::"l"(p) : "memory");
}
__device__ __forceinline__ unsigned ld_relaxed(const unsigned* p) {
    unsigned v;
    asm volatile("ld.relaxed.gpu.global.u32 %0, [%1];" : "=r"(v) : "l"(p) : "memory");
    return v;
}
__device__ __forceinline__ void wait_counter(const unsigned* p, unsigned target) {
    for (uint32_t n = 0; (int)(ld_relaxed(p) - target) < 0 && n < SPIN_LIMIT; n++) __nanosleep(100);
    asm volatile("fence.acquire.gpu;" ::: "memory");
    asm volatile("fence.proxy.async.global;" ::: "memory");
}
__device__ __forceinline__ void bar_sync(int id, int n) { asm volatile("bar.sync %0, %1;" ::"r"(id), "r"(n) : "memory"); }
__device__ __forceinline__ void bar_arrive(int id, int n) { asm volatile("bar.arrive %0, %1;" ::"r"(id), "r"(n) : "memory"); }
__device__ __forceinline__ void cluster_sync() {
    asm volatile("barrier.cluster.arrive.relaxed.aligned;\nbarrier.cluster.wait.aligned;" ::: "memory");
}
__device__ __forceinline__ void wg_fence() { asm volatile("wgmma.fence.sync.aligned;" ::: "memory"); }
__device__ __forceinline__ void wg_commit() { asm volatile("wgmma.commit_group.sync.aligned;" ::: "memory"); }
template <int N> __device__ __forceinline__ void wg_wait() { asm volatile("wgmma.wait_group.sync.aligned %0;" ::"n"(N) : "memory"); }
template <int N> __device__ __forceinline__ void reg_fence(float (&a)[N]) {
#pragma unroll
    for (int i = 0; i < N; i++) asm volatile("" : "+f"(a[i])::"memory");
}
template <int N> __device__ __forceinline__ void reg_fence(uint32_t (&a)[N]) {
#pragma unroll
    for (int i = 0; i < N; i++) asm volatile("" : "+r"(a[i])::"memory");
}
__device__ __forceinline__ uint32_t pack_bf16(float lo, float hi) {
    uint32_t r;
    asm("cvt.rn.bf16x2.f32 %0, %1, %2;" : "=r"(r) : "f"(hi), "f"(lo));
    return r;
}
__device__ __forceinline__ float bf_lo(uint32_t v) { return __uint_as_float(v << 16); }
__device__ __forceinline__ float bf_hi(uint32_t v) { return __uint_as_float(v & 0xffff0000u); }
__device__ __forceinline__ float bf_round(float v) { return __bfloat162float(__float2bfloat16_rn(v)); }
__device__ __forceinline__ float ex2(float v) {
    float r;
    asm("ex2.approx.ftz.f32 %0, %1;" : "=f"(r) : "f"(v));
    return r;
}
__device__ __forceinline__ float sqrt_approx(float v) {
    float r;
    asm("sqrt.approx.ftz.f32 %0, %1;" : "=f"(r) : "f"(v));
    return r;
}
__device__ __forceinline__ float rcp_approx(float v) {
    float r;
    asm("rcp.approx.ftz.f32 %0, %1;" : "=f"(r) : "f"(v));
    return r;
}
__device__ __forceinline__ float silu_f(float v) { return v * rcp_approx(1.0f + ex2(v * -1.4426950408889634f)); }
__device__ __forceinline__ void stmatrix_x4(uint32_t addr, uint32_t r0, uint32_t r1, uint32_t r2, uint32_t r3) {
    asm volatile("stmatrix.sync.aligned.m8n8.x4.shared.b16 [%0], {%1, %2, %3, %4};"
                 ::"r"(addr), "r"(r0), "r"(r1), "r"(r2), "r"(r3) : "memory");
}
__device__ __forceinline__ void sts128(uint32_t addr, uint32_t r0, uint32_t r1, uint32_t r2, uint32_t r3) {
    asm volatile("st.shared.v4.b32 [%0], {%1, %2, %3, %4};" ::"r"(addr), "r"(r0), "r"(r1), "r"(r2), "r"(r3) : "memory");
}
__device__ __forceinline__ void lds128(uint32_t addr, uint32_t& r0, uint32_t& r1, uint32_t& r2, uint32_t& r3) {
    asm volatile("ld.shared.v4.b32 {%0, %1, %2, %3}, [%4];" : "=r"(r0), "=r"(r1), "=r"(r2), "=r"(r3) : "r"(addr) : "memory");
}
__device__ __forceinline__ void ldmatrix_x4(uint32_t addr, uint32_t& r0, uint32_t& r1, uint32_t& r2, uint32_t& r3) {
    asm volatile("ldmatrix.sync.aligned.m8n8.x4.shared.b16 {%0, %1, %2, %3}, [%4];"
                 : "=r"(r0), "=r"(r1), "=r"(r2), "=r"(r3) : "r"(addr) : "memory");
}
__device__ __forceinline__ uint32_t bf2_mul(uint32_t a, uint32_t b) {
    uint32_t r;
    asm("mul.rn.bf16x2 %0, %1, %2;" : "=r"(r) : "r"(a), "r"(b));
    return r;
}
__device__ __forceinline__ uint32_t bf2_add(uint32_t a, uint32_t b) {
    uint32_t r;
    asm("add.rn.bf16x2 %0, %1, %2;" : "=r"(r) : "r"(a), "r"(b));
    return r;
}
__device__ __forceinline__ uint64_t policy_evict_first() {
    uint64_t p;
    asm("createpolicy.fractional.L2::evict_first.b64 %0, 1.0;" : "=l"(p));
    return p;
}

__device__ __forceinline__ uint64_t make_desc(uint32_t addr, uint32_t lbo_bytes) {
    return (uint64_t)((addr & 0x3FFFF) >> 4) | ((uint64_t)(lbo_bytes >> 4) << 16) | ((uint64_t)(1024 >> 4) << 32) | (1ull << 62);
}

__device__ __forceinline__ void wgmma_n256_ss(float (&d)[128], uint64_t da, uint64_t db, int acc) {
    asm volatile(
        "{\n.reg .pred p;\nsetp.ne.b32 p, %130, 0;\n"
        "wgmma.mma_async.sync.aligned.m64n256k16.f32.bf16.bf16 {"
        "%0, %1, %2, %3, %4, %5, %6, %7, %8, %9, %10, %11, %12, %13, %14, %15, "
        "%16, %17, %18, %19, %20, %21, %22, %23, %24, %25, %26, %27, %28, %29, %30, %31, "
        "%32, %33, %34, %35, %36, %37, %38, %39, %40, %41, %42, %43, %44, %45, %46, %47, "
        "%48, %49, %50, %51, %52, %53, %54, %55, %56, %57, %58, %59, %60, %61, %62, %63, "
        "%64, %65, %66, %67, %68, %69, %70, %71, %72, %73, %74, %75, %76, %77, %78, %79, "
        "%80, %81, %82, %83, %84, %85, %86, %87, %88, %89, %90, %91, %92, %93, %94, %95, "
        "%96, %97, %98, %99, %100, %101, %102, %103, %104, %105, %106, %107, %108, %109, %110, %111, "
        "%112, %113, %114, %115, %116, %117, %118, %119, %120, %121, %122, %123, %124, %125, %126, %127"
        "}, %128, %129, p, 1, 1, 1, 0;\n}\n"
        :
        "+f"(d[0]), "+f"(d[1]), "+f"(d[2]), "+f"(d[3]), "+f"(d[4]), "+f"(d[5]), "+f"(d[6]), "+f"(d[7]),
        "+f"(d[8]), "+f"(d[9]), "+f"(d[10]), "+f"(d[11]), "+f"(d[12]), "+f"(d[13]), "+f"(d[14]), "+f"(d[15]),
        "+f"(d[16]), "+f"(d[17]), "+f"(d[18]), "+f"(d[19]), "+f"(d[20]), "+f"(d[21]), "+f"(d[22]), "+f"(d[23]),
        "+f"(d[24]), "+f"(d[25]), "+f"(d[26]), "+f"(d[27]), "+f"(d[28]), "+f"(d[29]), "+f"(d[30]), "+f"(d[31]),
        "+f"(d[32]), "+f"(d[33]), "+f"(d[34]), "+f"(d[35]), "+f"(d[36]), "+f"(d[37]), "+f"(d[38]), "+f"(d[39]),
        "+f"(d[40]), "+f"(d[41]), "+f"(d[42]), "+f"(d[43]), "+f"(d[44]), "+f"(d[45]), "+f"(d[46]), "+f"(d[47]),
        "+f"(d[48]), "+f"(d[49]), "+f"(d[50]), "+f"(d[51]), "+f"(d[52]), "+f"(d[53]), "+f"(d[54]), "+f"(d[55]),
        "+f"(d[56]), "+f"(d[57]), "+f"(d[58]), "+f"(d[59]), "+f"(d[60]), "+f"(d[61]), "+f"(d[62]), "+f"(d[63]),
        "+f"(d[64]), "+f"(d[65]), "+f"(d[66]), "+f"(d[67]), "+f"(d[68]), "+f"(d[69]), "+f"(d[70]), "+f"(d[71]),
        "+f"(d[72]), "+f"(d[73]), "+f"(d[74]), "+f"(d[75]), "+f"(d[76]), "+f"(d[77]), "+f"(d[78]), "+f"(d[79]),
        "+f"(d[80]), "+f"(d[81]), "+f"(d[82]), "+f"(d[83]), "+f"(d[84]), "+f"(d[85]), "+f"(d[86]), "+f"(d[87]),
        "+f"(d[88]), "+f"(d[89]), "+f"(d[90]), "+f"(d[91]), "+f"(d[92]), "+f"(d[93]), "+f"(d[94]), "+f"(d[95]),
        "+f"(d[96]), "+f"(d[97]), "+f"(d[98]), "+f"(d[99]), "+f"(d[100]), "+f"(d[101]), "+f"(d[102]), "+f"(d[103]),
        "+f"(d[104]), "+f"(d[105]), "+f"(d[106]), "+f"(d[107]), "+f"(d[108]), "+f"(d[109]), "+f"(d[110]), "+f"(d[111]),
        "+f"(d[112]), "+f"(d[113]), "+f"(d[114]), "+f"(d[115]), "+f"(d[116]), "+f"(d[117]), "+f"(d[118]), "+f"(d[119]),
        "+f"(d[120]), "+f"(d[121]), "+f"(d[122]), "+f"(d[123]), "+f"(d[124]), "+f"(d[125]), "+f"(d[126]), "+f"(d[127])
        : "l"(da), "l"(db), "r"(acc));
}

template <int TB>
__device__ __forceinline__ void wgmma_n128_rs(float (&d)[64], uint32_t a0, uint32_t a1, uint32_t a2, uint32_t a3, uint32_t db, int acc) {
    asm volatile(
        "{\n.reg .pred p;\n.reg .b64 db;\nsetp.ne.b32 p, %69, 0;\nmov.b64 db, {%68, 0x40000040};\n"
        "wgmma.mma_async.sync.aligned.m64n128k16.f32.bf16.bf16 {"
        "%0, %1, %2, %3, %4, %5, %6, %7, %8, %9, %10, %11, %12, %13, %14, %15, "
        "%16, %17, %18, %19, %20, %21, %22, %23, %24, %25, %26, %27, %28, %29, %30, %31, "
        "%32, %33, %34, %35, %36, %37, %38, %39, %40, %41, %42, %43, %44, %45, %46, %47, "
        "%48, %49, %50, %51, %52, %53, %54, %55, %56, %57, %58, %59, %60, %61, %62, %63"
        "}, {%64, %65, %66, %67}, db, p, 1, 1, %70;\n}\n"
        :
        "+f"(d[0]), "+f"(d[1]), "+f"(d[2]), "+f"(d[3]), "+f"(d[4]), "+f"(d[5]), "+f"(d[6]), "+f"(d[7]),
        "+f"(d[8]), "+f"(d[9]), "+f"(d[10]), "+f"(d[11]), "+f"(d[12]), "+f"(d[13]), "+f"(d[14]), "+f"(d[15]),
        "+f"(d[16]), "+f"(d[17]), "+f"(d[18]), "+f"(d[19]), "+f"(d[20]), "+f"(d[21]), "+f"(d[22]), "+f"(d[23]),
        "+f"(d[24]), "+f"(d[25]), "+f"(d[26]), "+f"(d[27]), "+f"(d[28]), "+f"(d[29]), "+f"(d[30]), "+f"(d[31]),
        "+f"(d[32]), "+f"(d[33]), "+f"(d[34]), "+f"(d[35]), "+f"(d[36]), "+f"(d[37]), "+f"(d[38]), "+f"(d[39]),
        "+f"(d[40]), "+f"(d[41]), "+f"(d[42]), "+f"(d[43]), "+f"(d[44]), "+f"(d[45]), "+f"(d[46]), "+f"(d[47]),
        "+f"(d[48]), "+f"(d[49]), "+f"(d[50]), "+f"(d[51]), "+f"(d[52]), "+f"(d[53]), "+f"(d[54]), "+f"(d[55]),
        "+f"(d[56]), "+f"(d[57]), "+f"(d[58]), "+f"(d[59]), "+f"(d[60]), "+f"(d[61]), "+f"(d[62]), "+f"(d[63])
        : "r"(a0), "r"(a1), "r"(a2), "r"(a3), "r"(db), "r"(acc), "n"(TB));
}

__device__ __forceinline__ void wgmma_n128_ss(float* d, uint64_t da, uint64_t db, int acc) {
    asm volatile(
        "{\n.reg .pred p;\nsetp.ne.b32 p, %66, 0;\n"
        "wgmma.mma_async.sync.aligned.m64n128k16.f32.bf16.bf16 {"
        "%0, %1, %2, %3, %4, %5, %6, %7, %8, %9, %10, %11, %12, %13, %14, %15, "
        "%16, %17, %18, %19, %20, %21, %22, %23, %24, %25, %26, %27, %28, %29, %30, %31, "
        "%32, %33, %34, %35, %36, %37, %38, %39, %40, %41, %42, %43, %44, %45, %46, %47, "
        "%48, %49, %50, %51, %52, %53, %54, %55, %56, %57, %58, %59, %60, %61, %62, %63"
        "}, %64, %65, p, 1, 1, 0, 1;\n}\n"
        :
        "+f"(d[0]), "+f"(d[1]), "+f"(d[2]), "+f"(d[3]), "+f"(d[4]), "+f"(d[5]), "+f"(d[6]), "+f"(d[7]),
        "+f"(d[8]), "+f"(d[9]), "+f"(d[10]), "+f"(d[11]), "+f"(d[12]), "+f"(d[13]), "+f"(d[14]), "+f"(d[15]),
        "+f"(d[16]), "+f"(d[17]), "+f"(d[18]), "+f"(d[19]), "+f"(d[20]), "+f"(d[21]), "+f"(d[22]), "+f"(d[23]),
        "+f"(d[24]), "+f"(d[25]), "+f"(d[26]), "+f"(d[27]), "+f"(d[28]), "+f"(d[29]), "+f"(d[30]), "+f"(d[31]),
        "+f"(d[32]), "+f"(d[33]), "+f"(d[34]), "+f"(d[35]), "+f"(d[36]), "+f"(d[37]), "+f"(d[38]), "+f"(d[39]),
        "+f"(d[40]), "+f"(d[41]), "+f"(d[42]), "+f"(d[43]), "+f"(d[44]), "+f"(d[45]), "+f"(d[46]), "+f"(d[47]),
        "+f"(d[48]), "+f"(d[49]), "+f"(d[50]), "+f"(d[51]), "+f"(d[52]), "+f"(d[53]), "+f"(d[54]), "+f"(d[55]),
        "+f"(d[56]), "+f"(d[57]), "+f"(d[58]), "+f"(d[59]), "+f"(d[60]), "+f"(d[61]), "+f"(d[62]), "+f"(d[63])
        : "l"(da), "l"(db), "r"(acc));
}

__device__ __forceinline__ void wgmma_n8_ta(float* d, uint64_t da, uint64_t db) {
    asm volatile("wgmma.mma_async.sync.aligned.m64n8k16.f32.bf16.bf16 {%0, %1, %2, %3}, %4, %5, 1, 1, 1, 1, 0;\n"
                 : "+f"(d[0]), "+f"(d[1]), "+f"(d[2]), "+f"(d[3]) : "l"(da), "l"(db));
}

#define PROF(slot, role)
#undef PROF_GT
#define PROF_GT(slot)

struct Params {
    const __nv_bfloat16* x;
    const __nv_bfloat16* w_r;
    const uint8_t *c_kv, *w_uk, *w_uv;
    uint8_t* out;
};
__device__ __forceinline__ void lsu_prefetch(const void* p) { asm volatile("prefetch.global.L2 [%0];" ::"l"(p) : "memory"); }

template <typename T>
__device__ __forceinline__ T* ptr_off(T* base, uint32_t off) {
    uint32_t lo, hi;
    asm("mov.b64 {%0, %1}, %2;" : "=r"(lo), "=r"(hi) : "l"(base));
    asm("add.cc.u32 %0, %0, %2;\naddc.u32 %1, %1, 0;" : "+r"(lo), "+r"(hi) : "r"(off));
    T* r;
    asm("mov.b64 %0, {%1, %2};" : "=l"(r) : "r"(lo), "r"(hi));
    return r;
}
__device__ __forceinline__ int kv_head(int pair) { return AMAP ? (pair & 15) >> 1 : pair >> 3; }
__device__ __forceinline__ int kv_tokens(int pair) { return AMAP ? (pair & 1) * 4 + (pair >> 4) : pair & 7; }
__device__ __forceinline__ int attn_rowblock(int pair, int seg) {
    int j = pair & 3, hl = pair >> 2;
    return ((hl & 1) ^ seg) ? j : 7 - j;
}
__device__ __forceinline__ int outproj_head(int i, int ib) {
    if (i < 16) return i;
    return 16 + 2 * (i & 7) + ((ib < 4) ^ ((i >> 3) & 1));
}

__device__ __forceinline__ void pin_value(uint32_t& v) { asm volatile("" : "+r"(v)); }
__device__ __forceinline__ void pin_value(int& v) { asm volatile("" : "+r"(v)); }
__device__ __forceinline__ void pin_value(const uint8_t*& v) { asm volatile("" : "+l"(v)); }

__device__ __forceinline__ void producer(const Params& P, uint32_t sb, int pair, int c,
                                         const CUtensorMap* m_ckv, const CUtensorMap* m_wu,
                                         const CUtensorMap* m_wq, const CUtensorMap* m_wo) {
    const int hl = pair >> 2;
    const int ibA = attn_rowblock(pair, 0), nA = 2 * ibA + 2;
    const int ib = (pair >> 1) & 7, mi = 2 * ib + c, nb = (pair >> 4) * 4 + (pair & 1) * 2;
    const bool leader = elect_one();
    uint32_t g = 4, tail = 0;
    if (leader) prefetch_map(m_wq);
    auto wait_released = [&](uint32_t need) {
#pragma unroll 1
        for (; tail <= need; tail++) mbar_wait(sb + BAR_EMPTY + (tail & 7) * 8, (tail >> 3) & 1);
    };
    auto wait_released_here = [&](uint32_t need) {
#pragma unroll 1
        for (; tail < need; tail++) mbar_wait(sb + BAR_EMPTY + (tail & 7) * 8, (tail >> 3) & 1);
        if (tail == need) mbar_wait(sb + BAR_EMPTYL + (need & 7) * 8, (need >> 3) & 1);
    };
    auto wait_released_peer = [&](uint32_t need) {
        if (tail == need) {
            uint32_t eb = sb + BAR_EMPTY + (need & 7) * 8, ep = (need >> 3) & 1;
            tail++;
            mbar_wait(eb, ep);
        }
    };
    auto full_bar = [&]() { return sb + BAR_FULL + (g & 7) * 8; };
    auto pin = [](auto&... v) { (pin_value(v), ...); };
#pragma unroll 1
    for (int rnd = 0; rnd < 2; rnd++) {
#pragma unroll 1
        for (int i = rnd ? 0 : 4; i < 16; i++) {
            int kb = i & 7, h2 = (kv_head(pair) + (i & 8) + rnd * 16) * 2, krow = kb * 64;
            uint32_t pg = sb + (i & 3) * (3 * PAGE), pb = pg + (1 + c) * PAGE, bar = full_bar();
            pin(kb, h2, krow, pg, pb, bar);
            const uint32_t need = g - 4 - (i < 2);
            wait_released_here(need);
            if (leader) {
                mbar_expect_tx(bar, 3 * PAGE);
                tma_3d(pg, m_wu, 0, krow, h2, bar);
            }
            wait_released_peer(need);
            if (leader) {
                tma_3d_mc(pb, m_ckv, 0, kv_tokens(pair) * 256 + c * 128, kb, bar);
                if (rnd == 1 && i == 3) asm volatile("red.relaxed.gpu.global.add.u32 [%0], 1;" ::"l"(ptr_off(g_sync.kvfree, hl * 32)) : "memory");
            }
            g++;
        }
        mbar_sleep(sb + BAR_DEP, 0);
        const uint8_t* xa = ptr_off(g_xn, ibA * (16 * 32768) + c * PAGE);
        const uint8_t* xb = ptr_off(g_xn, (7 - ibA) * (16 * 32768) + (1 - c) * PAGE);
#pragma unroll 1
        for (int kb = 0; kb < DM / 64; kb++) {
            uint32_t pg = sb + (kb & 3) * (3 * PAGE), pw = pg + 2 * PAGE + c * 8192, bar = full_bar(), p2 = pg + PAGE;
            int krow = kb * 64;
            pin(pg, pw, p2, bar, krow);
            wait_released_here(g - 4);
            if (leader) {
                mbar_expect_tx(bar, 3 * PAGE);
                bulk_load(pg, xa, PAGE, bar);
            }
            wait_released_peer(g - 4);
            if (leader) {
                tma_3d_mc(pw, m_wq, 0, krow, (rnd * 16 + hl) * 2 + c, bar);
                bulk_load(p2, xb, PAGE, bar);
            }
            g++;
            xa += 32768;
            xb += 32768;
        }
        mbar_sleep(sb + BAR_DEP + 8 + rnd * 16, 0);
        if (rnd == 1 && leader) prefetch_map(m_wo);
        uint32_t pg = sb + c * PAGE;
#pragma unroll 1
        for (int j = 0; j < 36; j++) {
            const bool isk = j == 0 || ((j & 1) && j != 35);
            const int t = isk ? (j + 1) >> 1 : (j - 1) >> 1;
            const uint8_t* src = ptr_off(g_kv, (hl * 16 + (t >= nA ? t - nA : t)) * 65536 + (isk ? 0 : 32768) + c * PAGE);
            uint32_t bar = full_bar(), need = g - 6 + (j < 2) + (j < 5);
            pin(src, bar, need);
            wait_released(need);
            if (leader) {
                mbar_expect_tx(bar, 2 * PAGE);
                bulk_load_mc(pg, src, PAGE, bar);
            }
            g++;
            if (rnd == 0 && j >= 22 && j < 34) {
                const int cta = pair * 2 + c, i = j - 22;
                const uint32_t l = (threadIdx.x & 31) * 128;
                if (i < 8) lsu_prefetch(ptr_off(i & 1 ? P.w_uv : P.w_uk, cta * 32768 + (i >> 1) * 8192 + 4096 + l));
                else lsu_prefetch(ptr_off(P.c_kv, cta * 16384 + (i - 8) * 4096 + l));
            }
            pg = pg >= sb + SM_REGION - 2 * PAGE ? pg - (SM_REGION - 2 * PAGE) : pg + 2 * PAGE;
        }
    }
    uint32_t pg = sb;
#pragma unroll 1
    for (int i = 0; i < 64; i++) {
        if ((i & 15) == 0 && i != 16) mbar_sleep(sb + BAR_DEP + 32 + (i >> 1) - (i ? 8 : 0), 0);
        const int kb = outproj_head(i >> 1, ib) * 2 + (i & 1);
        const uint8_t* src = ptr_off(g_ctx, (mi * 64 + kb) * PAGE);
        uint32_t bar = full_bar(), pw = pg + PAGE + c * 8192;
        int krow = kb * 64;
        pin(src, bar, pw, krow);
        wait_released_here(g - 6);
        if (leader) {
            mbar_expect_tx(bar, 2 * PAGE);
            bulk_load(pg, src, PAGE, bar);
        }
        wait_released_peer(g - 6);
        if (leader) tma_3d_mc(pw, m_wo, 0, krow, nb + c, bar);
        g++;
        pg = pg == sb + SM_REGION - 2 * PAGE ? sb : pg + 2 * PAGE;
    }
}

__device__ __forceinline__ uint32_t xn_block(int row64, int kb) {
    return (((row64 >> 2) * 16 + kb) * 4 + ((row64 & 1) * 2 + (((row64 >> 1) & 1) ^ 1))) * 8192;
}
__device__ __forceinline__ uint32_t image_offset(int row, int ch) {
    return xn_block(row >> 6, ch >> 3) + (row & 63) * 128 + (((ch & 7) ^ (row & 7)) << 4);
}
__device__ __forceinline__ uint32_t bf2_sub(uint32_t a, uint32_t b) {
    uint32_t r;
    asm("sub.rn.bf16x2 %0, %1, %2;" : "=r"(r) : "r"(a), "r"(b));
    return r;
}
__device__ __forceinline__ uint32_t bf2_fma(uint32_t a, uint32_t b, uint32_t c) {
    uint32_t r;
    asm("fma.rn.bf16x2 %0, %1, %2, %3;" : "=r"(r) : "r"(a), "r"(b), "r"(c));
    return r;
}
template <int N0, int N>
__device__ __forceinline__ void ln_sums(const uint32_t (&u)[N], float& sum, float& sq) {
    float s0 = 0.f, s1 = 0.f, q0 = 0.f, q1 = 0.f;
#pragma unroll
    for (int k = N0; k < N0 + 16; k++) {
        const float a = bf_lo(u[k]), b = bf_hi(u[k]);
        s0 += a; s1 += b;
        q0 = fmaf(a, a, q0); q1 = fmaf(b, b, q1);
    }
    sum = s0 + s1;
    sq = q0 + q1;
}
__device__ __forceinline__ void ln_finish(float sum, float sq, uint32_t& mean2, uint32_t& rhi2, uint32_t& rlo2) {
    const float ms = sum * (1.0f / DM);
    const float var = fmaxf(fmaf(-ms, ms, sq * (1.0f / DM)), 0.f);
    const float rden = rcp_approx(bf_round(sqrt_approx(bf_round(bf_round(var) + 1e-5f))));
    const float rhi = bf_round(rden);
    mean2 = pack_bf16(ms, ms);
    rhi2 = pack_bf16(rhi, rhi);
    rlo2 = pack_bf16(rden - rhi, rden - rhi);
}
template <int N0, int N>
__device__ __forceinline__ void ln_apply(uint32_t (&u)[N], uint32_t mean2, uint32_t rhi2, uint32_t rlo2, uint8_t* dst) {
#pragma unroll
    for (int i = 0; i < 4; i++) {
        uint32_t o[4];
#pragma unroll
        for (int k = 0; k < 4; k++) {
            const uint32_t d = bf2_sub(u[N0 + 4 * i + k], mean2);
            o[k] = bf2_fma(d, rhi2, bf2_mul(d, rlo2));
        }
#pragma unroll
        for (int k = 0; k < 4; k++) u[N0 + 4 * i + k] = o[k];
        __stcg(reinterpret_cast<uint4*>(dst + i * 131072), make_uint4(o[0], o[1], o[2], o[3]));
    }
}
__device__ __forceinline__ int query_rowblock(int pair, int c, int w, int seg) {
    const int qA = (w ? 0 : 2) + c;
    return 4 * attn_rowblock(pair, seg) + (seg ? 3 - qA : qA);
}

__device__ FETCH_INL void fetch_helper(const uint8_t* w_u, const uint8_t* x, uint32_t sb, int w, int lane, int pair, int c) {
    const uint32_t page = sb + SM_REGION + w * PAGE + lane * 16;
    mbar_sleep(sb + BAR_FULL + 5 * 8, 0);
#pragma unroll 1
    for (int i = 0; i < 2; i++) {
        lsu_prefetch(ptr_off(w_u, ((pair * 2 + c) * 4 + i * 2 + (lane >> 4)) * 8192 + 2048 + (lane & 15) * 128));
        __nanosleep(300);
    }
    const unsigned e1 = __ldcg(&g_sync.done) / NCTA + 1;
#pragma unroll 1
    for (int e = 1; e <= 7; e += 2) mbar_sleep(sb + BAR_DONE + 8, (e >> 1) & 1);
    const int rb = ((pair >> 1) & 7) * 4 + c * 2 + w, kb0 = (pair >> 4) * 4 + (pair & 1) * 2;
    const uint8_t* src = ptr_off(g_xn, xn_block(rb, kb0) + lane * 16);
#pragma unroll 1
    for (int i = 0; i < 32; i += 4) {
#pragma unroll
        for (int k = 0; k < 4; k++) cp_async16(page + (i + k) * 512, src + (i + k) * 512 + (i >> 4) * (32768 - 8192));
        __nanosleep(200);
    }
#pragma unroll 1
    for (int i = 0; i < 4; i++) lsu_prefetch(ptr_off(x, (rb * 64 + i * 16 + (lane >> 1)) * (DM * 2) + kb0 * 128 + (lane & 1) * 128));
    wait_counter(&g_sync.ffn_done, e1);
    const int r = __ldcg(ptr_off(g_sel, (lane >> 4) * 4)) - rb * 64, ch = lane & 15;
    const uint4 t = __ldcg(ptr_off(g_routed, ((lane >> 4) * 128 + kb0 * 8 + ch) * 16));
    asm volatile("cp.async.wait_all;" ::: "memory");
    __syncwarp();
    if (r >= 0 && r < 64)
        sts128(sb + SM_REGION + w * PAGE + (ch >> 3) * 8192 + r * 128 + (((ch & 7) ^ (r & 7)) << 4), t.x, t.y, t.z, t.w);
    __syncwarp();
    if (lane == 0) mbar_arrive(sb + BAR_G + w * 8);
    PROF(20, 2);
}

__device__ __noinline__ void sync_helper(uint32_t sb, int lane, int pair, int c) {
    const unsigned e1 = __ldcg(&g_sync.done) / NCTA + 1;
    const int ib = (pair >> 1) & 7;
    int e = 0, b = 0;
#pragma unroll 1
    for (uint32_t n = 0; (e < 9 || b < 7) && n < SPIN_LIMIT; n++) {
        if (e < 9 && __all_sync(~0u, mbar_test(sb + BAR_DONE + (e & 1) * 8, (e >> 1) & 1))) {
            const int rnd = e > 4, ev = (e - 1) & 3;
            unsigned* flag = e == 0 ? &g_sync.ln
                           : ev < 2 ? ptr_off(g_sync.kv, (rnd * 16 + kv_head(pair) + 8 * ev) * 32)
                                    : ptr_off(g_sync.ctx, (query_rowblock(pair, c, lane & 1, ev & 1) * NH + rnd * 16 + (pair >> 2)) * 4);
            asm volatile("fence.proxy.async.global;\nfence.release.gpu;" ::: "memory");
            if (lane < ((e == 0 || ev < 2) ? 1 : 2)) asm volatile("red.relaxed.gpu.global.add.u32 [%0], 1;" ::"l"(flag) : "memory");
            PROF(10 + e, 2);
            e++;
        }
        if (b < 7 && e > 0 && (b < 4 || (n & POLL_MASK) == 0)) {
            const int i = b == 4 ? lane >> 1 : 8 * b - 24 + ((lane >> 1) & 7);
            const unsigned* cnt = b == 0 ? &g_sync.ln
                                : b == 2 ? ptr_off(g_sync.kvfree, (kv_head(pair) + 8 * (lane & 1)) * 32)
                                : b < 4 ? ptr_off(g_sync.kv, ((b >> 1) * 16 + (pair >> 2)) * 32)
                                        : ptr_off(g_sync.ctx, ((4 * ib + 2 * c + (lane & 1)) * NH + outproj_head(i & 31, ib)) * 4);
            if (__all_sync(~0u, (int)(ld_relaxed(cnt) - e1 * (b == 0 ? NMAIN : b == 2 ? 8 : b < 4 ? 16 : 1)) >= 0)) {
                asm volatile("fence.acquire.gpu;\nfence.proxy.async.global;" ::: "memory");
                __syncwarp();
                if (lane == 0) mbar_arrive(sb + BAR_DEP + b * 8);
                PROF(1 + b, 2);
                b++;
            }
        }
        __nanosleep(150);
    }
}

__device__ __forceinline__ unsigned long long block_max_key(unsigned long long k, unsigned long long* red, int tid) {
#pragma unroll
    for (int o = 16; o; o >>= 1) {
        unsigned long long t = __shfl_xor_sync(~0u, k, o);
        k = t > k ? t : k;
    }
    bar_sync(1, 256);
    if ((tid & 31) == 0) red[tid >> 5] = k;
    bar_sync(1, 256);
    k = red[0];
#pragma unroll
    for (int i = 1; i < 8; i++) k = red[i] > k ? red[i] : k;
    return k;
}

constexpr int FS = FF / 4;
constexpr int FSTAGE = 32768, FNST = 6;
constexpr int FN1 = 2 * (DM / 16), FN2 = FS / 16;

__device__ __forceinline__ void ffn_producer(uint32_t sb, int s, const CUtensorMap* m_gate, const CUtensorMap* m_up,
                                             const CUtensorMap* m_down) {
    const uint64_t pol = policy_evict_first();
    if (FDELAY) wait_counter(&g_sync.ln, (__ldcg(&g_sync.done) / NCTA + 1) * NMAIN);
    int slot = 0, ph = 1;
#pragma unroll 1
    for (int st = 0; st < FN1 + FN2; st++) {
        mbar_sleep(sb + BAR_EMPTY + slot * 8, ph);
        const uint32_t bar = sb + BAR_FULL + slot * 8;
        const bool up = st < FN1;
        mbar_expect_tx(bar, up ? FS * 32 : DM * 32);
        tma_3d_hint(sb + slot * FSTAGE, up ? ((st & 1) ? m_up : m_gate) : m_down, 0,
                    up ? (st >> 1) * 16 : s * FS + (st - FN1) * 16, up ? s * (FS / 64) : 0, bar, pol);
        if (++slot == FNST) { slot = 0; ph ^= 1; }
    }
}

__device__ __forceinline__ void ffn_cta(uint8_t* smem, uint32_t sb, int s, unsigned epoch, const __nv_bfloat16* w_r) {
    const int tid = threadIdx.x, lane = tid & 31;
    const int warp = __shfl_sync(~0u, tid >> 5, 0), w = warp >> 2;
    constexpr uint32_t XB = FNST * FSTAGE, HB = XB + 16384, AUX = HB + 14336;
    unsigned long long* red = reinterpret_cast<unsigned long long*>(smem + AUX);
    unsigned* flag = reinterpret_cast<unsigned*>(smem + AUX + 128);
    const unsigned e1 = epoch + 1;
    for (int i = tid; i < (16384 + 14336) / 16; i += 256) reinterpret_cast<uint4*>(smem + XB)[i] = make_uint4(0, 0, 0, 0);
    {
        float wf[32];
#pragma unroll
        for (int i = 0; i < 4; i++) {
            const uint4 t = __ldg(reinterpret_cast<const uint4*>(w_r) + lane + 32 * i);
            const uint32_t tu[4] = {t.x, t.y, t.z, t.w};
#pragma unroll
            for (int k = 0; k < 4; k++) { wf[8 * i + 2 * k] = bf_lo(tu[k]); wf[8 * i + 2 * k + 1] = bf_hi(tu[k]); }
        }
        if (tid == 0) wait_counter(&g_sync.ln, e1 * NMAIN);
        bar_sync(1, 256);
#pragma unroll 1
        for (int r0 = s * (SEQ / 4) + warp * (SEQ / 32); r0 < s * (SEQ / 4) + (warp + 1) * (SEQ / 32); r0 += 4) {
            uint4 t[4][4];
#pragma unroll
            for (int r = 0; r < 4; r++)
#pragma unroll
                for (int i = 0; i < 4; i++) t[r][i] = __ldcg(reinterpret_cast<const uint4*>(g_xn + image_offset(r0 + r, lane) + i * 131072));
            float acc[4];
#pragma unroll
            for (int r = 0; r < 4; r++) {
                float a = 0.f, b = 0.f;
#pragma unroll
                for (int i = 0; i < 4; i++) {
                    const uint32_t tu[4] = {t[r][i].x, t[r][i].y, t[r][i].z, t[r][i].w};
#pragma unroll
                    for (int k = 0; k < 4; k++) {
                        a = fmaf(bf_lo(tu[k]), wf[8 * i + 2 * k], a);
                        b = fmaf(bf_hi(tu[k]), wf[8 * i + 2 * k + 1], b);
                    }
                }
                acc[r] = a + b;
            }
#pragma unroll
            for (int o = 16; o; o >>= 1)
#pragma unroll
                for (int r = 0; r < 4; r++) acc[r] += __shfl_xor_sync(~0u, acc[r], o);
            if (lane < 4) __stcg(&g_r[r0 + lane], bf_round(lane == 0 ? acc[0] : lane == 1 ? acc[1] : lane == 2 ? acc[2] : acc[3]));
        }
        __threadfence();
        bar_sync(1, 256);
        if (tid == 0) {
            red_release(&g_sync.router);
            wait_counter(&g_sync.router, e1 * 4);
        }
        bar_sync(1, 256);
    }
    unsigned long long keys[8];
    unsigned long long best = 0;
#pragma unroll
    for (int i = 0; i < 8; i++) {
        int idx = tid + 256 * i;
        uint32_t b = __float_as_uint(__ldcg(&g_r[idx]) + 0.0f);
        b = (b & 0x80000000u) ? ~b : (b | 0x80000000u);
        keys[i] = ((unsigned long long)b << 32) | (unsigned)(SEQ - 1 - idx);
        best = keys[i] > best ? keys[i] : best;
    }
    const unsigned long long k0 = block_max_key(best, red, tid);
    best = 0;
#pragma unroll
    for (int i = 0; i < 8; i++) best = (keys[i] != k0 && keys[i] > best) ? keys[i] : best;
    const unsigned long long k1 = block_max_key(best, red, tid);
    const int row = SEQ - 1 - (int)((w ? k1 : k0) & 0xffffffffu);
    const int ch = tid & 127;
    const uint4 xrow = __ldcg(reinterpret_cast<const uint4*>(g_xn + image_offset(row, ch)));
    *reinterpret_cast<uint4*>(smem + XB + (ch >> 3) * 1024 + w * 128 + (((ch & 7) ^ w) << 4)) = xrow;
    fence_async_smem();
    bar_sync(1, 256);
    PROF(20, tid >> 7);
    int slot = 0, ph = 0, prev = 0;
    auto next_stage = [&](bool has_prev) {
        wg_commit();
        wg_wait<1>();
        if (has_prev && lane < 2) mbar_arrive(sb + BAR_EMPTY + prev * 8);
        prev = slot;
        if (++slot == FNST) { slot = 0; ph ^= 1; }
    };
    {
        float ag[28], au[28];
#pragma unroll
        for (int i = 0; i < 28; i++) ag[i] = au[i] = 0.f;
#pragma unroll 1
        for (int ks = 0; ks < DM / 16; ks++) {
            const uint64_t db = make_desc(sb + XB + (ks >> 2) * 1024 + (ks & 3) * 32, 16);
            mbar_wait(sb + BAR_FULL + slot * 8, ph);
            uint64_t da = make_desc(sb + slot * FSTAGE + w * (7 * 2048), 16);
            wg_fence();
#pragma unroll
            for (int b = 0; b < 7; b++) wgmma_n8_ta(ag + 4 * b, da + b * 128, db);
            next_stage(ks > 0);
            mbar_wait(sb + BAR_FULL + slot * 8, ph);
            da = make_desc(sb + slot * FSTAGE + w * (7 * 2048), 16);
            wg_fence();
#pragma unroll
            for (int b = 0; b < 7; b++) wgmma_n8_ta(au + 4 * b, da + b * 128, db);
            next_stage(true);
        }
        wg_wait<0>();
        reg_fence(ag);
        reg_fence(au);
        if ((lane & 3) == 0) {
#pragma unroll
            for (int i = 0; i < 28; i++) {
                const int f = (warp & 3) * 16 + (lane >> 2) + (i & 2) * 4, tok = i & 1;
                const float h = bf_round(silu_f(bf_round(ag[i]))) * bf_round(au[i]);
                *reinterpret_cast<__nv_bfloat16*>(smem + HB + (w * 7 + (i >> 2)) * 1024 + tok * 128 + (((f >> 3) ^ tok) << 4) + (f & 7) * 2) =
                    __float2bfloat16_rn(h);
            }
        }
    }
    fence_async_smem();
    bar_sync(1, 256);
    PROF(21, tid >> 7);
    {
        float ay[32];
#pragma unroll
        for (int i = 0; i < 32; i++) ay[i] = 0.f;
#pragma unroll 1
        for (int ks = 0; ks < FN2; ks++) {
            const uint64_t db = make_desc(sb + HB + (ks >> 2) * 1024 + (ks & 3) * 32, 16);
            mbar_wait(sb + BAR_FULL + slot * 8, ph);
            const uint64_t da = make_desc(sb + slot * FSTAGE + w * (8 * 2048), 16);
            wg_fence();
#pragma unroll
            for (int b = 0; b < 8; b++) wgmma_n8_ta(ay + 4 * b, da + b * 128, db);
            next_stage(true);
        }
        wg_wait<0>();
        reg_fence(ay);
        if ((lane & 3) == 0) {
#pragma unroll
            for (int i = 0; i < 32; i++)
                g_ypart[(s * 2 + (i & 1)) * DM + (w * 8 + (i >> 2)) * 64 + (warp & 3) * 16 + (lane >> 2) + (i & 2) * 4] = ay[i];
        }
    }
    PROF(23, tid >> 7);
    __threadfence();
    bar_sync(1, 256);
    if (tid == 0) {
        *flag = atomicAdd(&g_sync.ffn_ticket, 1u) == epoch * 4 + 3;
        __threadfence();
    }
    bar_sync(1, 256);
    if (*flag) {
        const float sg = bf_round(__fdividef(1.0f, 1.0f + __expf(-__ldcg(&g_r[row]))));
        const uint32_t xu[4] = {xrow.x, xrow.y, xrow.z, xrow.w};
        uint32_t o[4];
#pragma unroll
        for (int k = 0; k < 4; k++) {
            float y0 = 0.f, y1 = 0.f;
#pragma unroll
            for (int q = 0; q < 4; q++) {
                const float2 y = __ldcg(reinterpret_cast<const float2*>(&g_ypart[(q * 2 + w) * DM + ch * 8 + 2 * k]));
                y0 += y.x; y1 += y.y;
            }
            o[k] = pack_bf16(bf_lo(xu[k]) + bf_round(bf_round(y0) * sg), bf_hi(xu[k]) + bf_round(bf_round(y1) * sg));
        }
        g_routed[w * 128 + ch] = make_uint4(o[0], o[1], o[2], o[3]);
        if (ch == 0) g_sel[w] = row;
        bar_sync(1, 256);
        if (tid == 0) red_release(&g_sync.ffn_done);
    }
}

__device__ __forceinline__ uint32_t slab_addr(uint32_t stg, int lane, int s) {
    const int row = ((lane >> 3) & 1) * 8 + (lane & 7);
    const int chunk = 2 * (s & 3) + (lane >> 4);
    return stg + row * 128 + (s >> 2) * 8192 + ((chunk ^ (lane & 7)) << 4);
}

constexpr float SM_SCALE = 0.08838834764831845f * 1.4426950408889634f;
constexpr float SUM_HI = 1048576.f, SUM_LO = 1.0f / 1048576.f;

template <int I0, int I1, int J0>
__device__ __forceinline__ void mask_range(float (&S)[64], float limf) {
#pragma unroll
    for (int i = I0; i < I1; i++) {
        const int j = i >> 2;
        float t;
        asm("add.sat.f32 %0, %1, %2;" : "=f"(t) : "f"((float)(32 * (j >> 2) + 2 * (j & 3) + (i & 1) - (i & 2) * 4)), "f"(-limf));
        S[4 * J0 + i] = fmaf(t, -1e30f, S[4 * J0 + i]);
    }
}
template <int J0>
__device__ __forceinline__ void mask_half(float (&S)[64], float limf, int v) {
    asm volatile("" : "+f"(limf));
    if (v < 2) {
        mask_range<0, 16, J0>(S, limf);
#pragma unroll
        for (int i = 16; i < 32; i++) S[4 * J0 + i] = -1e30f;
    } else {
        mask_range<16, 32, J0>(S, limf);
    }
}
__device__ __forceinline__ void issue_qk(float (&S)[64], const uint32_t (&Q)[32], uint32_t d0) {
#pragma unroll
    for (int s = 0; s < 8; s++)
        wgmma_n128_rs<1>(S, Q[4 * s], Q[4 * s + 1], Q[4 * s + 2], Q[4 * s + 3], d0 + s * 128, s > 0);
}
template <int H>
__device__ __forceinline__ void issue_pv(float (&O)[64], const uint32_t (&Pm)[32], uint32_t d0, int acc) {
#pragma unroll
    for (int s = 4 * H; s < 4 * H + 4; s++)
        wgmma_n128_rs<0>(O, Pm[4 * s], Pm[4 * s + 1], Pm[4 * s + 2], Pm[4 * s + 3], d0 + H * (PAGE >> 4) + (s & 3) * 2, s > 0 ? 1 : acc);
}
template <int J0, int J1>
__device__ __forceinline__ void exp_groups(const float (&S)[64], uint32_t (&Pm)[32], float (&sum)[NSUM]) {
#pragma unroll
    for (int i = 2 * J0; i < 2 * J1; i++) asm volatile("" : "+r"(Pm[i])::"memory");
#pragma unroll
    for (int j = J0; j < J1; j++) {
        const float e0 = ex2(S[4 * j]), e1 = ex2(S[4 * j + 1]), e2 = ex2(S[4 * j + 2]), e3 = ex2(S[4 * j + 3]);
        if (NSUM == 4) {
            sum[0] = j ? sum[0] + e0 : e0; sum[2] = j ? sum[2] + e1 : e1; sum[1] = j ? sum[1] + e2 : e2; sum[3] = j ? sum[3] + e3 : e3;
        } else {
            sum[0] = (j ? sum[0] + e0 : e0) + e1; sum[1] = (j ? sum[1] + e2 : e2) + e3;
        }
        Pm[2 * j] = pack_bf16(e0, e1);
        Pm[2 * j + 1] = pack_bf16(e2, e3);
    }
}
__device__ __forceinline__ void shift_rows(float (&S)[64], float d0, float d1) {
#pragma unroll
    for (int j = 0; j < 16; j++) {
        S[4 * j] -= d0; S[4 * j + 1] -= d0; S[4 * j + 2] -= d1; S[4 * j + 3] -= d1;
    }
}
__device__ constexpr int chunk_src(int i) { return 4 * (4 * (i >> 3) + (i & 3)) + 2 * ((i >> 2) & 1); }
enum : uint32_t { CTL_FIRST = 1, CTL_SWITCH = 2, CTL_LAST = 4, CTL_HALF = 128, CTL_MASKHI = 256, CTL_WOUT = 512, CTL_PVHALF = 1024, CTL_PVACC = 16384,
                  CTL_SHIFT = 32768 };
__device__ __forceinline__ float quad_sum(float v) {
    v += __shfl_xor_sync(~0u, v, 1);
    return v + __shfl_xor_sync(~0u, v, 2);
}

__device__ __forceinline__ void store_part(uint8_t* base, uint32_t row_bits, int p, const uint32_t (&pk)[64]) {
    asm volatile("{\n.reg .b64 d0, d1;\nxor.b64 d0, %0, %1;\nxor.b64 d1, d0, 64;\n"
                 "TS: .branchtargets P0, P1, P2, P3, P4, P5, P6, P7;\n"
                 "brx.idx.uni %2, TS;\n"
                 "P0:\n st.global.cg.v4.u32 [d0 + 0], {%3, %4, %5, %6};\n st.global.cg.v4.u32 [d1 + 0], {%11, %12, %13, %14};\n bra.uni DONE;\n"
                 "P1:\n st.global.cg.v4.u32 [d0 + 0], {%7, %8, %9, %10};\n st.global.cg.v4.u32 [d1 + 0], {%15, %16, %17, %18};\n bra.uni DONE;\n"
                 "P2:\n st.global.cg.v4.u32 [d0 + 16384], {%19, %20, %21, %22};\n st.global.cg.v4.u32 [d1 + 16384], {%27, %28, %29, %30};\n bra.uni DONE;\n"
                 "P3:\n st.global.cg.v4.u32 [d0 + 16384], {%23, %24, %25, %26};\n st.global.cg.v4.u32 [d1 + 16384], {%31, %32, %33, %34};\n bra.uni DONE;\n"
                 "P4:\n st.global.cg.v4.u32 [d0 + 65536], {%35, %36, %37, %38};\n st.global.cg.v4.u32 [d1 + 65536], {%43, %44, %45, %46};\n bra.uni DONE;\n"
                 "P5:\n st.global.cg.v4.u32 [d0 + 65536], {%39, %40, %41, %42};\n st.global.cg.v4.u32 [d1 + 65536], {%47, %48, %49, %50};\n bra.uni DONE;\n"
                 "P6:\n st.global.cg.v4.u32 [d0 + 81920], {%51, %52, %53, %54};\n st.global.cg.v4.u32 [d1 + 81920], {%59, %60, %61, %62};\n bra.uni DONE;\n"
                 "P7:\n st.global.cg.v4.u32 [d0 + 81920], {%55, %56, %57, %58};\n st.global.cg.v4.u32 [d1 + 81920], {%63, %64, %65, %66};\n bra.uni DONE;\n"
                 "DONE:\n}\n"
                 ::"l"(base), "l"((uint64_t)((p & 1) ? row_bits : 0)), "r"(p), "r"(pk[0]), "r"(pk[1]), "r"(pk[2]), "r"(pk[3]), "r"(pk[4]), "r"(pk[5]), "r"(pk[6]), "r"(pk[7]), "r"(pk[8]), "r"(pk[9]), "r"(pk[10]), "r"(pk[11]), "r"(pk[12]), "r"(pk[13]), "r"(pk[14]), "r"(pk[15]), "r"(pk[16]), "r"(pk[17]), "r"(pk[18]), "r"(pk[19]), "r"(pk[20]), "r"(pk[21]), "r"(pk[22]), "r"(pk[23]), "r"(pk[24]), "r"(pk[25]), "r"(pk[26]), "r"(pk[27]), "r"(pk[28]), "r"(pk[29]), "r"(pk[30]), "r"(pk[31]), "r"(pk[32]), "r"(pk[33]), "r"(pk[34]), "r"(pk[35]), "r"(pk[36]), "r"(pk[37]), "r"(pk[38]), "r"(pk[39]), "r"(pk[40]), "r"(pk[41]), "r"(pk[42]), "r"(pk[43]), "r"(pk[44]), "r"(pk[45]), "r"(pk[46]), "r"(pk[47]), "r"(pk[48]), "r"(pk[49]), "r"(pk[50]), "r"(pk[51]), "r"(pk[52]), "r"(pk[53]), "r"(pk[54]), "r"(pk[55]), "r"(pk[56]), "r"(pk[57]), "r"(pk[58]), "r"(pk[59]), "r"(pk[60]), "r"(pk[61]), "r"(pk[62]), "r"(pk[63])
                 : "memory");
}

__device__ __forceinline__ void consumer(uint32_t sb, int pair, int c, uint8_t* out, const uint8_t* x) {
    const int tid = threadIdx.x;
    const int warp = __shfl_sync(~0u, tid >> 5, 0);
    const int w = warp >> 2, v = warp & 3, lane = tid & 31;

    const uint32_t empty_rel = lane == 2 ? mapa(sb + BAR_EMPTYL, c) : mapa(sb + BAR_EMPTY, lane & 1);
    auto release = [&](uint32_t grp) {
        if (lane < 3) mbar_arrive_cluster(empty_rel + (grp & 7) * 8);
    };
    auto wait_full = [&](uint32_t grp) { mbar_wait(sb + BAR_FULL + (grp & 7) * 8, (grp >> 3) & 1); };

    uint32_t g = 0;
    const uint32_t stg = sb + SM_REGION + w * PAGE + v * 2048;
    const uint32_t chunk0 = (lane >> 2) * 128 + (((lane & 3) ^ (lane >> 2)) << 4);
    uint32_t ndone = 0;
    auto mark_done = [&]() {
        __syncwarp();
        if (lane == 0) mbar_arrive(sb + BAR_DONE + (ndone & 1) * 8);
        ndone++;
    };
    auto ctx_dst = [&](int rnd, int seg) {
        const int rb = query_rowblock(pair, c, w, seg);
        return ptr_off(g_ctx, ((rb >> 1) * 64 + (rnd * 16 + (pair >> 2)) * 2) * PAGE + (rb & 1) * 8192 + v * 2048);
    };

    uint32_t ctl_tab;
    {
        const int t = lane, firstB = 2 * attn_rowblock(pair, 0) + 2 - w;
        auto is_half = [&](int u) { return (u == firstB - 1 || u == 16) && c == (u >= firstB); };
        auto block = [&](int u) { return u + (w == 1 && u >= firstB); };
        auto place = [](int j) { return ((j & 15) << 3) | ((j - (j * 43 >> 8) * 6) << 11); };
        const int jv = min(2 * block(t - 1) + 2, 35), jk = t == 17 ? jv : max(2 * block(t) - 1, 0);
        const bool diag = t == firstB - 1 || t == 16;
        ctl_tab = ((t == 0 || t == firstB) ? CTL_FIRST : 0) | (t == firstB ? CTL_SWITCH : 0) | (t == 17 ? CTL_LAST : 0) |
                  (diag ? (is_half(t) ? CTL_HALF : CTL_MASKHI) : 0) | (t == firstB + 1 ? CTL_WOUT : 0) |
                  (is_half(t - 1) ? CTL_PVHALF : 0) | ((t == 1 || t == firstB + 1) ? 0 : CTL_PVACC) |
                  place(jk) | ((place(jv) | (t ? 3 : 0)) << 16);
    }

    uint32_t pk[64];
#pragma unroll
    for (int i = 0; i < 64; i++) pk[i] = 0;
    uint8_t* pend = nullptr;
    uint32_t prow = 0x400;
    auto write_part = [&](int p) { store_part(pend, prow, p, pk); };
    if (w == 1) bar_arrive(2, 256);

    for (int item = 0; item < 6; item++) {
        if (ACOND) {
            constexpr int nk = DC / 64;
            float acc[128];
            auto issue_kblock = [&](int first_acc) {
                wait_full(g);
                const uint32_t pg = sb + (g & 3) * (3 * PAGE);
                const uint64_t da = make_desc(pg + w * 8192, 16), db = make_desc(pg + PAGE, 16);
                wg_fence();
                wgmma_n256_ss(acc, da, db, first_acc);
                wgmma_n256_ss(acc, da + 128, db + 2, 1);
                wgmma_n256_ss(acc, da + 256, db + 4, 1);
                wgmma_n256_ss(acc, da + 384, db + 6, 1);
                wg_commit();
                g++;
            };
            if (XAT == 0 && item == 0) {
                const uint8_t* src = ptr_off(x, ((pair * 2 + c) * 16 + warp * 2) * (DM * 2) + lane * 16);
#pragma unroll
                for (int i = 0; i < 8; i++) {
                    const uint4 t = __ldcg(reinterpret_cast<const uint4*>(src + i * 512));
                    pk[4 * i] = t.x; pk[4 * i + 1] = t.y; pk[4 * i + 2] = t.z; pk[4 * i + 3] = t.w;
                }
            }
            if (XAT == 3 && item == 0) {
                if (lane < 16) lsu_prefetch(ptr_off(x, ((pair * 2 + c) * 16 + warp * 2) * (DM * 2) + lane * 128));
            }
            if (item == 0) PROF(17, w);
            issue_kblock(0);
            if (item == 0) PROF(1, w);
            if (item == 0 && w == 0) PROF_GT(1);
            const int nparts = item == 0 ? 0 : (item == 3 ? 4 : 8);
            const int ln_row = (pair * 2 + c) * 16 + warp * 2;
            auto load_x = [&]() {
                const uint8_t* src = ptr_off(x, ln_row * (DM * 2) + lane * 16);
#pragma unroll
                for (int i = 0; i < 8; i++) {
                    const uint4 t = __ldcg(reinterpret_cast<const uint4*>(src + i * 512));
                    pk[4 * i] = t.x; pk[4 * i + 1] = t.y; pk[4 * i + 2] = t.z; pk[4 * i + 3] = t.w;
                }
            };
            if ((XAT == 1 || XAT == 3) && item == 0) load_x();
#pragma unroll 1
            for (int kb = 1; kb < nk; kb++) {
                if (kb == nk - 1 && w == 1) bar_sync(4, 256);
                issue_kblock(1);
                if (kb == nk - 1 && w == 0) bar_arrive(4, 256);
                wg_wait<1>();
                release(g - 2);
                if (kb <= nparts) {
                    if (item == 4 && kb == 1) mbar_wait(sb + BAR_DEP + 16, 0);
                    write_part(kb - 1);
                    if (kb == nk - 1) write_part(nk - 1);
                    if (kb == nparts || kb == nk - 1) mark_done();
                }
                if (g <= 8) {
                    if (XAT == 2 && g == XAT) load_x();
                    float s[2], q[2];
                    if (g == 4 + (LNSH > 0)) {
                        ln_sums<0>(pk, s[0], q[0]);
                        pk[32] = __float_as_uint(s[0]); pk[33] = __float_as_uint(q[0]);
                    }
                    if (g == 5 + (LNSH == 2)) {
                        ln_sums<16>(pk, s[1], q[1]);
                        pk[34] = __float_as_uint(s[1]); pk[35] = __float_as_uint(q[1]);
                    }
                    if (g == 6) {
#pragma unroll
                        for (int r = 0; r < 2; r++) { s[r] = __uint_as_float(pk[32 + 2 * r]); q[r] = __uint_as_float(pk[33 + 2 * r]); }
                        const bool hi = lane & 16, od = lane & 8;
                        float a = hi ? s[1] : s[0], b = hi ? q[1] : q[0];
                        a += __shfl_xor_sync(~0u, hi ? s[0] : s[1], 16);
                        b += __shfl_xor_sync(~0u, hi ? q[0] : q[1], 16);
                        float t = od ? b : a;
                        t += __shfl_xor_sync(~0u, od ? a : b, 8);
#pragma unroll
                        for (int o = 4; o; o >>= 1) t += __shfl_xor_sync(~0u, t, o);
#pragma unroll
                        for (int r = 0; r < 2; r++) {
                            s[r] = __shfl_sync(~0u, t, 16 * r);
                            q[r] = __shfl_sync(~0u, t, 16 * r + 8);
                        }
                        ln_finish(s[0], q[0], pk[36], pk[37], pk[38]);
                        ln_finish(s[1], q[1], pk[39], pk[40], pk[41]);
                    }
                    if (g == 7) ln_apply<0>(pk, pk[36], pk[37], pk[38], ptr_off(g_xn, image_offset(ln_row, lane)));
                    if (g == 8) {
                        ln_apply<16>(pk, pk[39], pk[40], pk[41], ptr_off(g_xn, image_offset(ln_row + 1, lane)));
                        mark_done();
                    }
                }
            }
            wg_wait<0>();
            reg_fence(acc);
            release(g - 1);
            PROF(2 + 2 * item, w);
            if (w == 0) PROF_GT(2 + 2 * item);
            const float ksc = (QSCALE || c) ? 1.0f : SM_SCALE;
#pragma unroll
            for (int i = 0; i < 64; i++) pk[i] = pack_bf16(acc[chunk_src(i)] * ksc, acc[chunk_src(i) + 1] * ksc);
            const uint32_t vrow = (v >> 1) * 32 + (lane >> 3) * 8 + (v & 1) * 4 + ((lane >> 2) & 1);
            pend = ptr_off(g_kv, ((kv_head(pair) + (item == 1 || item == 4 ? 8 : 0)) * 16 + kv_tokens(pair) * 2) * 65536 + w * 8192 +
                                     (c ? 32768 + vrow * 128 + (((lane & 3) ^ (vrow & 7)) << 4) : v * 2048 + chunk0));
            prow = c ? 0x120 : 0x400;
            PROF(3 + 2 * item, w);
            continue;
        }

        float O[64], S[64];
        auto issue_q = [&](int first_acc) {
            wait_full(g);
            const uint32_t pg = sb + (g & 3) * (3 * PAGE);
            const uint64_t da = make_desc(pg + w * 8192, 16), db = make_desc(pg + 2 * PAGE, 8192);
            const uint64_t dab = make_desc(pg + PAGE + (1 - w) * 8192, 16);
            wg_fence();
#pragma unroll
            for (int q = 0; q < 4; q++) wgmma_n128_ss(S, da + 2 * q, db + 128 * q, q ? 1 : first_acc);
            wg_commit();
#pragma unroll
            for (int q = 0; q < 4; q++) wgmma_n128_ss(O, dab + 2 * q, db + 128 * q, q ? 1 : first_acc);
            wg_commit();
            g++;
        };
        issue_q(0);
#pragma unroll 1
        for (int kb = 1; kb < DM / 64; kb++) {
            if (kb == DM / 64 - 2 && w == 1) bar_sync(4, 256);
            issue_q(1);
            if (kb == DM / 64 - 1 && w == 0) bar_arrive(4, 256);
            wg_wait<QSPLIT ? 2 : 1>();
            release(g - 2);
            if (kb <= 8) {
                write_part(kb - 1);
                if (kb == 8) mark_done();
            }
        }
        uint32_t Q[32], Pm[32];
#pragma unroll
        for (int i = 0; i < 32; i++) Pm[i] = PMINIT ? pk[i] : 0;
        float lim = (float)(v * 16 + (lane >> 2) - 8 * (lane & 3));
        float mc[2] = {0.f, 0.f}, l[2] = {0.f, 0.f}, scale[2] = {0.f, 0.f}, sum[NSUM];
        uint32_t ctl = __shfl_sync(~0u, ctl_tab, 0), nxt = __shfl_sync(~0u, ctl_tab, 1);
        int t = 1;
        asm volatile("" : "+f"(lim), "+f"(mc[0]), "+f"(mc[1]), "+f"(l[0]), "+f"(l[1]), "+r"(ctl), "+r"(nxt), "+r"(t));
        constexpr float qsc = QSCALE ? SM_SCALE : 1.0f;
        wg_wait<QSPLIT ? 1 : 0>();
        reg_fence(S);
#pragma unroll
        for (int i = 0; i < 32; i++) Q[i] = pack_bf16(S[2 * i] * qsc, S[2 * i + 1] * qsc);
        reg_fence(Q);
        wait_full(g);
        wg_wait<0>();
        reg_fence(O);
        release(g - 1);
        PROF(2 + 2 * item, w);
        if (w == 0) PROF_GT(2 + 2 * item);

        const uint32_t qaddr = QOPQ ? __shfl_sync(~0u, stg + lane * 16, lane) : stg + lane * 16;
        auto put_queries = [&](const float (&A)[64]) {
#pragma unroll
            for (int i = 0; i < 8; i++)
                sts128(qaddr + (i >> 2) * 8192 + (i & 3) * 512, pack_bf16(A[8 * i] * qsc, A[8 * i + 1] * qsc), pack_bf16(A[8 * i + 2] * qsc, A[8 * i + 3] * qsc),
                       pack_bf16(A[8 * i + 4] * qsc, A[8 * i + 5] * qsc), pack_bf16(A[8 * i + 6] * qsc, A[8 * i + 7] * qsc));
        };
        auto get_queries = [&](int i0, int i1) {
#pragma unroll
            for (int i = i0; i < i1; i++) lds128(qaddr + (i >> 2) * 8192 + (i & 3) * 512, Q[4 * i], Q[4 * i + 1], Q[4 * i + 2], Q[4 * i + 3]);
        };
        const uint32_t kdesc0 = (uint32_t)make_desc(sb, PAGE), vdesc0 = (uint32_t)make_desc(sb, 16);
        auto wait_block = [&](uint32_t word) { mbar_wait(sb + BAR_FULL + (word & 56), (word >> 6) & 1); };
        auto write_out = [&](auto early) {
            uint8_t* dst = ctx_dst(item == 5, 0);
            uint8_t* d[2] = {ptr_off(dst, chunk0), ptr_off(dst, chunk0 ^ 64)};
#pragma unroll
            for (int i = early.value ? 0 : WN; i < (early.value ? WN : 8); i++) {
                const float sc = scale[i & 1];
                uint32_t q[4];
#pragma unroll
                for (int k = 0; k < 4; k++) q[k] = pack_bf16(O[chunk_src(4 * i + k)] * sc, O[chunk_src(4 * i + k) + 1] * sc);
                if (WINP && early.value && i > 0) {
#pragma unroll
                    for (int k = 0; k < 4; k++) O[4 * (i - 1) + k] = __uint_as_float(q[k]);
                }
                __stcg(reinterpret_cast<uint4*>(d[(i >> 1) & 1] + (i >> 2) * PAGE + (i & 1) * 1024), make_uint4(q[0], q[1], q[2], q[3]));
            }
            if (early.value == (WN == 8)) mark_done();
        };
        put_queries(O);
        bar_sync(2 + w, 256);
        wg_fence();
        issue_qk(S, Q, kdesc0);
        wg_commit();
        wg_fence();
        wg_commit();
        wg_commit();
        bar_arrive(3 - w, 256);
        for (;;) {
            const bool kready = KTRY ? mbar_try(sb + BAR_FULL + (nxt & 56), (nxt >> 6) & 1) : true;
            if (!KTRY) wait_block(nxt);
            wg_wait<2>();
            reg_fence(S);
            if (ctl & (CTL_HALF | CTL_MASKHI | CTL_SHIFT)) {
                if (LQN < 8 && (nxt & CTL_SWITCH)) get_queries(LQN, 8);
                if (ctl & CTL_HALF) mask_half<0>(S, lim, v);
                if (ctl & CTL_MASKHI) mask_half<8>(S, lim, v);
                if (ctl & CTL_SHIFT) shift_rows(S, mc[0], mc[1]);
            }
            float early[4 * EARLY + 1];
#pragma unroll
            for (int j = 0; j < EARLY; j++) {
#pragma unroll
                for (int i = 4 * j; i < 4 * j + 4; i++) early[i] = ex2(S[i]);
                sum[0] = (j ? sum[0] + early[4 * j] : early[4 * j]) + early[4 * j + 1];
                sum[1] = (j ? sum[1] + early[4 * j + 2] : early[4 * j + 2]) + early[4 * j + 3];
            }
            const uint32_t tie = EARLY ? __float_as_uint(sum[0]) & __float_as_uint(sum[1]) & (ctl & 0x80000000u) : 0;
            if (lane < 3) mbar_arrive_cluster(empty_rel + tie + (ctl & 56));
            wg_wait<1>();
#pragma unroll
            for (int j = 0; j < EARLY; j++) {
                asm volatile("" : "+r"(Pm[2 * j]), "+r"(Pm[2 * j + 1])::"memory");
                Pm[2 * j] = pack_bf16(early[4 * j], early[4 * j + 1]);
                Pm[2 * j + 1] = pack_bf16(early[4 * j + 2], early[4 * j + 3]);
            }
            exp_groups<EARLY, 8>(S, Pm, sum);
            const bool half = ctl & CTL_HALF;
            if (!half) {
                wg_wait<0>();
                reg_fence(O);
                if (lane < ((ctl >> 16) & 3)) mbar_arrive_cluster(empty_rel + ((ctl >> 16) & 56));
                exp_groups<8, 16>(S, Pm, sum);
            } else {
                asm volatile("wgmma.wait_group.sync.aligned 0;\n" ::: "memory");
                reg_fence(O);
                if (lane < ((ctl >> 16) & 3)) asm volatile("mbarrier.arrive.shared::cluster.b64 _, [%0];\n" ::"r"(empty_rel + ((ctl >> 16) & 56)) : "memory");
            }
            if (NSUM == 4) { sum[0] += sum[2]; sum[1] += sum[3]; }
            const bool over = !(sum[0] + sum[1] <= SUM_HI);
            if (__any_sync(~0u, over || !kready) || (((ctl & CTL_FIRST) | (nxt & (CTL_SWITCH | CTL_LAST))) != 0)) {
                bool bad = __any_sync(~0u, over);
                if (KTRY && !kready) wait_block(nxt);
                const bool first = ctl & CTL_FIRST;
                if (first) {
                    uint32_t b0 = __ballot_sync(~0u, sum[0] >= SUM_LO), b1 = __ballot_sync(~0u, sum[1] >= SUM_LO);
                    b0 |= b0 >> 1; b1 |= b1 >> 1;
                    b0 |= b0 >> 2; b1 |= b1 >> 2;
                    bad |= (b0 & b1 & 0x11111111u) != 0x11111111u;
                }
                if (bad) {
                    if (half) {
#pragma unroll
                        for (int i = 32; i < 64; i++) S[i] = -INFINITY;
                    }
                    float d0 = fmaxf(S[0], S[1]), d1 = fmaxf(S[2], S[3]);
#pragma unroll
                    for (int j = 1; j < 16; j++) {
                        d0 = fmaxf(d0, fmaxf(S[4 * j], S[4 * j + 1]));
                        d1 = fmaxf(d1, fmaxf(S[4 * j + 2], S[4 * j + 3]));
                    }
                    d0 = fmaxf(d0, __shfl_xor_sync(~0u, d0, 1));
                    d1 = fmaxf(d1, __shfl_xor_sync(~0u, d1, 1));
                    d0 = fmaxf(d0, __shfl_xor_sync(~0u, d0, 2));
                    d1 = fmaxf(d1, __shfl_xor_sync(~0u, d1, 2));
                    if (!first) {
                        d0 = fmaxf(d0, 0.f);
                        d1 = fmaxf(d1, 0.f);
                        const float a0 = ex2(-d0), a1 = ex2(-d1);
#pragma unroll
                        for (int j = 0; j < 16; j++) {
                            O[4 * j] *= a0; O[4 * j + 1] *= a0; O[4 * j + 2] *= a1; O[4 * j + 3] *= a1;
                        }
                        l[0] *= a0; l[1] *= a1;
                    }
                    mc[0] += d0; mc[1] += d1;
                    ctl_tab |= CTL_SHIFT;
                    nxt |= CTL_SHIFT;
                    shift_rows(S, d0, d1);
                    exp_groups<0, 16>(S, Pm, sum);
                    if (NSUM == 4) { sum[0] += sum[2]; sum[1] += sum[3]; }
                }
                if (WN && (ctl & CTL_SWITCH)) write_out(std::true_type());
                if (nxt & CTL_LAST) break;
                if (nxt & CTL_SWITCH) {
                    get_queries(0, LQN);
                    nxt &= ~CTL_SHIFT;
                    ctl_tab &= ~CTL_SHIFT;
                }
            }
            ctl = nxt;
            bar_sync(2 + w, 256);
            wg_fence();
            issue_qk(S, Q, kdesc0 + (ctl & 0x3800));
            wg_commit();
            l[0] += sum[0]; l[1] += sum[1];
            nxt = __shfl_sync(~0u, ctl_tab, ++t);
            if (ctl & (CTL_SWITCH | CTL_WOUT)) {
                if (ctl & CTL_SWITCH) {
                    scale[0] = rcp_approx(quad_sum(l[0]));
                    scale[1] = rcp_approx(quad_sum(l[1]));
                    l[0] = l[1] = mc[0] = mc[1] = 0.f;
                    if (w == 1) { release((ctl >> 3) - 2); release((ctl >> 3) + 1); }
                } else {
                    write_out(std::false_type());
                }
            }
            wait_block(ctl >> 16);
            const uint32_t vdesc = vdesc0 + ((ctl >> 16) & 0x3800);
            if (!(ctl & CTL_PVHALF)) {
                wg_fence();
                issue_pv<0>(O, Pm, vdesc, ctl & CTL_PVACC);
                wg_commit();
                issue_pv<1>(O, Pm, vdesc, 1);
                wg_commit();
            } else {
                wg_fence();
                issue_pv<0>(O, Pm, vdesc, ctl & CTL_PVACC);
                wg_commit();
                wg_commit();
            }
            bar_arrive(3 - w, 256);
        }
        g += 36;
        if (w == 0) release(g - 3);
        if (WN < 8 && (nxt & CTL_WOUT)) write_out(std::false_type());
        const uint32_t vdesc = vdesc0 + (nxt & 0x3800);
        if (nxt & CTL_PVHALF) {
            wg_fence();
            issue_pv<0>(O, Pm, vdesc, nxt & CTL_PVACC);
            wg_commit();
        } else {
            wg_fence();
            issue_pv<0>(O, Pm, vdesc, nxt & CTL_PVACC);
            issue_pv<1>(O, Pm, vdesc, 1);
            wg_commit();
        }
        l[0] += sum[0]; l[1] += sum[1];
        ctl_tab = (ctl_tab & ~(0x00780078u | CTL_SHIFT)) | ((ctl_tab + 0x00200020u) & 0x00780078u);
        const float i0 = rcp_approx(quad_sum(l[0])), i1 = rcp_approx(quad_sum(l[1]));
        wg_wait<0>();
        reg_fence(O);
        if (w == 0) release(g - 2);
        release(g - 1);
#pragma unroll
        for (int i = 0; i < 32; i++) {
            const float sc = (i & 4) ? i1 : i0;
            pk[i] = pack_bf16(O[chunk_src(i)] * sc, O[chunk_src(i) + 1] * sc);
        }
        pend = ptr_off(ctx_dst(item == 5, 1), chunk0);
        prow = 0x400;
#pragma unroll
        for (int i = 32; i < 64; i++) pk[i] = 0;
        PROF(3 + 2 * item, w);
        if (w == 0) PROF_GT(3 + 2 * item);
    }

    float acc[64];
    uint32_t slot = 0;
    auto issue_out = [&](int first_acc) {
        wait_full(g);
        const uint64_t da = make_desc(sb + slot + w * 8192, 16), db = make_desc(sb + slot + PAGE, 8192);
        wg_fence();
#pragma unroll
        for (int q = 0; q < 4; q++) wgmma_n128_ss(acc, da + 2 * q, db + 128 * q, q ? 1 : first_acc);
        wg_commit();
        g++;
        slot = slot == SM_REGION - 2 * PAGE ? 0 : slot + 2 * PAGE;
    };
    issue_out(0);
#pragma unroll 1
    for (int kb = 1; kb < 64 - PEEL; kb++) {
        issue_out(1);
        wg_wait<1>();
        if (kb <= 58) release(g - 2);
        if (kb <= 8 && !(kb & 1)) {
            write_part((kb >> 1) - 1);
            if (kb == 8) mark_done();
        }
        if (kb >= 32 - PEEL && ((kb + PEEL) & 3) == 2 * w) {
            uint32_t u0, u1, u2, u3;
            const uint32_t a = stg + ((kb + PEEL) & 16) * 512 + ((kb + PEEL) & 12) * 128 + lane * 16;
            mbar_wait(sb + BAR_G + w * 8, 0);
            lds128(a, u0, u1, u2, u3);
            sts128(a, pack_bf16(silu_f(bf_lo(u0)), silu_f(bf_hi(u0))), pack_bf16(silu_f(bf_lo(u1)), silu_f(bf_hi(u1))),
                   pack_bf16(silu_f(bf_lo(u2)), silu_f(bf_hi(u2))), pack_bf16(silu_f(bf_lo(u3)), silu_f(bf_hi(u3))));
        }
    }
    const uint32_t goff = (((pair >> 1) & 7) * 256 + c * 128 + w * 64 + v * 16 + (lane >> 3)) * (DM * 2) +
                          ((pair >> 4) * 256 + (pair & 1) * 128) * 2 + (((lane & 7) ^ (lane >> 3)) << 4);
    uint32_t xr[32], gr[32];
    {
        const uint8_t* src[2] = {ptr_off(x, goff), ptr_off(x, goff ^ 64)};
#pragma unroll
        for (int i = 0; i < 8; i++) {
            const uint4 t = __ldcg(reinterpret_cast<const uint4*>(src[i & 1] + (i & 3) * (4 * DM * 2) + (i >> 2) * 128));
            xr[4 * i] = t.x; xr[4 * i + 1] = t.y; xr[4 * i + 2] = t.z; xr[4 * i + 3] = t.w;
        }
    }
#pragma unroll 1
    for (int i = 0; i < PEEL; i++) {
        if (STAG && i == PEEL - STAG && w == 1) bar_sync(4, 256);
        issue_out(1);
        if (STAG && i == PEEL - 1 && w == 0) bar_arrive(4, 256);
        wg_wait<1>();
        if (PEEL > 5 && i < PEEL - 5) release(g - 2);
    }
    asm volatile("barrier.cluster.arrive.relaxed.aligned;" ::: "memory");
#pragma unroll
    for (int i = 0; i < 8; i++) lds128(stg + (i >> 2) * 8192 + (i & 3) * 512 + lane * 16, gr[4 * i], gr[4 * i + 1], gr[4 * i + 2], gr[4 * i + 3]);
    uint8_t* dst[2] = {ptr_off(out, goff), ptr_off(out, goff ^ 64)};
    __syncwarp();
    wg_wait<0>();
    reg_fence(acc);
    PROF(14, w);
    if (w == 0) PROF_GT(14);
#pragma unroll
    for (int s = 0; s < 8; s++)
        stmatrix_x4(slab_addr(stg, lane, s), pack_bf16(acc[8 * s], acc[8 * s + 1]), pack_bf16(acc[8 * s + 2], acc[8 * s + 3]),
                    pack_bf16(acc[8 * s + 4], acc[8 * s + 5]), pack_bf16(acc[8 * s + 6], acc[8 * s + 7]));
    __syncwarp();
    uint32_t o[32];
#pragma unroll
    for (int i = 0; i < 8; i++) lds128(stg + (i >> 2) * 8192 + (i & 3) * 512 + lane * 16, o[4 * i], o[4 * i + 1], o[4 * i + 2], o[4 * i + 3]);
    if (TBAR) bar_sync(8 + w, 128);
#pragma unroll
    for (int i = 0; i < 8; i++) {
#pragma unroll
        for (int k = 0; k < 4; k++) xr[4 * i + k] = bf2_add(xr[4 * i + k], bf2_mul(o[4 * i + k], gr[4 * i + k]));
        __stcg(reinterpret_cast<uint4*>(dst[i & 1] + (i & 3) * (4 * DM * 2) + (i >> 2) * 128), make_uint4(xr[4 * i], xr[4 * i + 1], xr[4 * i + 2], xr[4 * i + 3]));
    }
    PROF(28, w);
}

__global__ void __cluster_dims__(2, 1, 1) __launch_bounds__(384, 1)
fused_kernel(const __grid_constant__ CUtensorMap m_ckv, const __grid_constant__ CUtensorMap m_wuk,
             const __grid_constant__ CUtensorMap m_wuv, const __grid_constant__ CUtensorMap m_wq,
             const __grid_constant__ CUtensorMap m_wo, const __grid_constant__ CUtensorMap m_gate,
             const __grid_constant__ CUtensorMap m_up, const __grid_constant__ CUtensorMap m_down, const Params P) {
    extern __shared__ __align__(1024) uint8_t smem[];
    const uint32_t sb = __shfl_sync(~0u, smem_u32(smem), 0);
    const int tid = threadIdx.x;
    const int cl = blockIdx.x >> 1, c = blockIdx.x & 1;
    const int pair = cl >= 64 ? cl : cl < 4 ? cl * 16 + 15 : cl < 36 ? ((cl - 4) >> 3) * 16 + ((cl - 4) & 7)
                                                                    : ((cl - 36) / 7) * 16 + 8 + (cl - 36) % 7;
    const bool starter = tid == 256 && pair < NMAIN / 2;
    const CUtensorMap* m_wu = c ? &m_wuv : &m_wuk;
    if (tid == 256) {
        mbar_init(sb + BAR_FULL, 1);
        if (starter) {
            asm volatile("fence.mbarrier_init.release.cluster;" ::: "memory");
            mbar_expect_tx(sb + BAR_FULL, 3 * PAGE);
            tma_3d(sb, m_wu, 0, 0, kv_head(pair) * 2, sb + BAR_FULL);
            tma_3d(sb + PAGE, &m_ckv, 0, kv_tokens(pair) * 256, 0, sb + BAR_FULL);
            tma_3d(sb + 2 * PAGE, &m_ckv, 0, kv_tokens(pair) * 256 + 128, 0, sb + BAR_FULL);
        }
#pragma unroll
        for (int i = START == 2; i < NBAR; i++) mbar_init(sb + SM_BAR + i * 8, (i >> 3) == 1 ? 16 : i >= 25 ? 8 : 1);
        asm volatile("fence.mbarrier_init.release.cluster;" ::: "memory");
    }
    if (starter) {
        if (START != 2) prefetch_map(&m_ckv);
        if (START == 1) mbar_arrive(sb + BAR_FULL);
#pragma unroll 1
        for (int kb = START ? 1 : 0; kb < 4; kb++) {
            mbar_expect_tx(sb + BAR_FULL + kb * 8, 3 * PAGE);
            if (kb < EARLYW) tma_3d(sb + kb * (3 * PAGE), m_wu, 0, kb * 64, kv_head(pair) * 2, sb + BAR_FULL + kb * 8);
        }
    }
    PROF(18, (tid >> 7) & 1);
    __syncthreads();
    cluster_sync();
    PROF(22, (tid >> 7) & 1);
    auto start_loads = [&]() {
#pragma unroll 1
        for (int kb = START ? 1 : 0; kb < 4; kb++) {
            if (kb >= EARLYW) tma_3d(sb + kb * (3 * PAGE), m_wu, 0, kb * 64, kv_head(pair) * 2, sb + BAR_FULL + kb * 8);
            tma_3d_mc(sb + kb * (3 * PAGE) + (1 + c) * PAGE, &m_ckv, 0, kv_tokens(pair) * 256 + c * 128, kb, sb + BAR_FULL + kb * 8);
        }
    };
    if (!LATEMC && starter) start_loads();
    PROF(19, (tid >> 7) & 1);
    const int warp = __shfl_sync(~0u, tid >> 5, 0), lane = tid & 31;
    auto dump_prof = [&]() {
    };
    if (pair >= NMAIN / 2) {
        if (warp < 8) ffn_cta(smem, sb, blockIdx.x - NMAIN, __ldcg(&g_sync.done) / NCTA, P.w_r);
        else if (tid == 256) ffn_producer(sb, blockIdx.x - NMAIN, &m_gate, &m_up, &m_down);
        __syncwarp();
        PROF(29, tid >> 7);
        cluster_sync();
        if (tid == 0) atomicAdd(&g_sync.done, 1u);
        if (warp < 8) dump_prof();
    } else if (warp < 8) {
        asm volatile("setmaxnreg.inc.sync.aligned.u32 232;");
        consumer(sb, pair, c, P.out, (const uint8_t*)P.x);
        PROF(29, tid >> 7);
        asm volatile("barrier.cluster.wait.aligned;" ::: "memory");
        dump_prof();
    } else {
        asm volatile("setmaxnreg.dec.sync.aligned.u32 40;");
        if (LATEMC && starter) start_loads();
        if (PF4 && warp == 9) {
            const int cta = pair * 2 + c;
            if (lane < 16 * PF4) lsu_prefetch(ptr_off((cta & 64) ? P.w_uv : P.w_uk, (256 + (lane >> 4) * 64 + (cta & 63)) * 8192 + (lane & 15) * 128));
            lsu_prefetch(ptr_off(P.c_kv, (cta * 16 + (lane >> 1)) * 1024 + 512 + (lane & 1) * 128));
        }
        if (warp == 10) {
            sync_helper(sb, lane, pair, c);
        } else if (warp & 1) {
            fetch_helper((warp & 2) ? P.w_uv : P.w_uk, (const uint8_t*)P.x, sb, (warp >> 1) & 1, lane, pair, c);
        } else {
            producer(P, sb, pair, c, &m_ckv, m_wu, &m_wq, &m_wo);
        }
        bar_sync(6, 128);
        if (tid == 256) atomicAdd(&g_sync.done, 1u);
        cluster_sync();
    }
}

typedef CUresult (*EncodeFn)(CUtensorMap*, CUtensorMapDataType, cuuint32_t, void*, const cuuint64_t*, const cuuint64_t*,
                             const cuuint32_t*, const cuuint32_t*, CUtensorMapInterleave, CUtensorMapSwizzle,
                             CUtensorMapL2promotion, CUtensorMapFloatOOBfill);

void make_map_w(EncodeFn fn, CUtensorMap* m, const void* ptr, int rows, int cols, int blocks, int box_rows = 32) {
    cuuint64_t dims[3] = {64, (cuuint64_t)rows, (cuuint64_t)cols / 64};
    cuuint64_t strides[2] = {(cuuint64_t)cols * 2, 128};
    cuuint32_t box[3] = {64, (cuuint32_t)box_rows, (cuuint32_t)blocks};
    cuuint32_t es[3] = {1, 1, 1};
    fn(m, CU_TENSOR_MAP_DATA_TYPE_BFLOAT16, 3, const_cast<void*>(ptr), dims, strides, box, es, CU_TENSOR_MAP_INTERLEAVE_NONE,
       CU_TENSOR_MAP_SWIZZLE_128B, CU_TENSOR_MAP_L2_PROMOTION_L2_256B, CU_TENSOR_MAP_FLOAT_OOB_FILL_NONE);
}

}

extern "C" void kernel_launch(void* const* d_in, const int* in_sizes, int n_in, void* d_out, int out_size) {
    static EncodeFn fn = nullptr;
    if (!fn) {
        void* f = nullptr;
        cudaDriverEntryPointQueryResult qr;
        cudaGetDriverEntryPoint("cuTensorMapEncodeTiled", &f, cudaEnableDefault, &qr);
        fn = (EncodeFn)f;
        cudaFuncSetAttribute(fused_kernel, cudaFuncAttributeMaxDynamicSharedMemorySize, SMEM_BYTES);
    }
    CUtensorMap m_ckv, m_wuk, m_wuv, m_wq, m_wo, m_gate, m_up, m_down;
    make_map_w(fn, &m_gate, d_in[8], DM, FF, FS / 64, 16);
    make_map_w(fn, &m_up, d_in[9], DM, FF, FS / 64, 16);
    make_map_w(fn, &m_down, d_in[10], FF, DM, DM / 64, 16);
    make_map_w(fn, &m_ckv, d_in[1], SEQ, DC, 1, 128);
    make_map_w(fn, &m_wq, d_in[2], DM, NH * 128, 1, 64);
    make_map_w(fn, &m_wuk, d_in[3], DC, NH * 128, 2, 64);
    make_map_w(fn, &m_wuv, d_in[4], DC, NH * 128, 2, 64);
    make_map_w(fn, &m_wo, d_in[5], NH * 128, DM, 1, 64);
    Params P;
    P.x = (const __nv_bfloat16*)d_in[0];
    P.w_r = (const __nv_bfloat16*)d_in[7];
    P.c_kv = (const uint8_t*)d_in[1];
    P.w_uk = (const uint8_t*)d_in[3];
    P.w_uv = (const uint8_t*)d_in[4];
    P.out = (uint8_t*)d_out;
    fused_kernel<<<NCTA, 384, SMEM_BYTES>>>(m_ckv, m_wuk, m_wuv, m_wq, m_wo, m_gate, m_up, m_down, P);
}
```

```cpp
#include <cuda_runtime.h>
#include <cuda_bf16.h>
#include <cuda.h>
#include <stdint.h>
#include <type_traits>

namespace {

constexpr int SEQ = 2048, DM = 1024, NH = 32, DC = 512, FF = 3584;
constexpr int PAGE = 16384;
constexpr int NRING = 12;
constexpr int NCTA = 132, NMAIN = 128;
constexpr uint32_t SM_REGION = NRING * PAGE;
constexpr uint32_t SM_BAR = (NRING + 2) * PAGE;
constexpr uint32_t BAR_FULL = SM_BAR, BAR_EMPTY = SM_BAR + 64;
constexpr uint32_t BAR_DEP = SM_BAR + 128;
constexpr uint32_t BAR_G = SM_BAR + 184;
constexpr uint32_t BAR_DONE = SM_BAR + 200;
constexpr uint32_t BAR_EMPTYL = SM_BAR + 216;
constexpr int NBAR = 35;
constexpr uint32_t SM_PROF = SM_BAR + 320;
constexpr int SMEM_BYTES = SM_PROF + 512;
constexpr uint32_t SPIN_LIMIT = 1u << 16;
constexpr uint32_t POLL_MASK = 7;
constexpr int EARLY = 2;
constexpr int WN = 6;
constexpr int PEEL = 5, STAG = 3;

struct SyncBlock {
    unsigned done;       unsigned pad0[31];
    unsigned ln;         unsigned pad1[31];
    unsigned router;     unsigned pad4[31];
    unsigned ffn_ticket; unsigned pad2[31];
    unsigned ffn_done;   unsigned pad3[31];
    unsigned kv[NH * 8];
    unsigned kvfree[16 * 8];
    unsigned ctx[32 * NH];
};

__device__ __align__(1024) uint8_t g_xn[8 * 16 * 4 * 8192];
__device__ __align__(4096) uint8_t g_kv[16 * 16 * 65536];
__device__ __align__(4096) uint8_t g_ctx[16 * 64 * 16384];
__device__ __align__(16) uint4 g_routed[2 * 128];
__device__ int g_sel[2];
__device__ __align__(16) float g_r[SEQ];
__device__ __align__(16) float g_ypart[4 * 2 * DM];
__device__ SyncBlock g_sync;

__device__ __forceinline__ uint32_t smem_u32(const void* p) { return (uint32_t)__cvta_generic_to_shared(p); }

__device__ __forceinline__ void mbar_init(uint32_t bar, uint32_t count) {
    asm volatile("mbarrier.init.shared::cta.b64 [%0], %1;" ::"r"(bar), "r"(count) : "memory");
}
#define MBAR_WAIT_ASM(HINT, LIMIT)                                                                  \
    asm volatile("{\n.reg .pred p;\n.reg .u32 n;\nmov.u32 n, 0;\n"                                  \
                 "WAIT_LOOP:\n"                                                                     \
                 "mbarrier.try_wait.parity.shared::cta.b64 p, [%0], %1" HINT ";\n"                  \
                 "@p bra WAIT_DONE;\n"                                                              \
                 "add.u32 n, n, 1;\n"                                                               \
                 "setp.lt.u32 p, n, " LIMIT ";\n"                                                   \
                 "@p bra WAIT_LOOP;\n"                                                              \
                 "WAIT_DONE:\n}\n" ::"r"(bar), "r"(parity) : "memory")
__device__ __forceinline__ void mbar_wait(uint32_t bar, uint32_t parity) { MBAR_WAIT_ASM("", "131072"); }
__device__ __forceinline__ void mbar_sleep(uint32_t bar, uint32_t parity) { MBAR_WAIT_ASM(", 2000", "8192"); }
__device__ __forceinline__ bool mbar_try(uint32_t bar, uint32_t parity) {
    uint32_t ok;
    asm volatile("{\n.reg .pred p;\nmbarrier.try_wait.parity.shared::cta.b64 p, [%1], %2;\nselp.u32 %0, 1, 0, p;\n}\n"
                 : "=r"(ok) : "r"(bar), "r"(parity) : "memory");
    return ok;
}
__device__ __forceinline__ bool mbar_test(uint32_t bar, uint32_t parity) {
    uint32_t ok;
    asm volatile("{\n.reg .pred p;\nmbarrier.test_wait.parity.shared::cta.b64 p, [%1], %2;\nselp.u32 %0, 1, 0, p;\n}\n"
                 : "=r"(ok) : "r"(bar), "r"(parity) : "memory");
    return ok;
}
__device__ __forceinline__ bool elect_one() {
    uint32_t ok;
    asm volatile("{\n.reg .pred p;\nelect.sync _|p, 0xffffffff;\nselp.u32 %0, 1, 0, p;\n}\n" : "=r"(ok));
    return ok;
}
__device__ __forceinline__ void mbar_arrive(uint32_t bar) {
    asm volatile("mbarrier.arrive.shared::cta.b64 _, [%0];" ::"r"(bar) : "memory");
}
__device__ __forceinline__ void mbar_expect_tx(uint32_t bar, uint32_t bytes) {
    asm volatile("mbarrier.arrive.expect_tx.shared::cta.b64 _, [%0], %1;" ::"r"(bar), "r"(bytes) : "memory");
}
__device__ __forceinline__ void mbar_arrive_cluster(uint32_t cluster_addr) {
    asm volatile("mbarrier.arrive.shared::cluster.b64 _, [%0];" ::"r"(cluster_addr) : "memory");
}
__device__ __forceinline__ uint32_t mapa(uint32_t addr, uint32_t rank) {
    uint32_t r;
    asm("mapa.shared::cluster.u32 %0, %1, %2;" : "=r"(r) : "r"(addr), "r"(rank));
    return r;
}
__device__ __forceinline__ void tma_3d(uint32_t dst, const CUtensorMap* m, int c0, int c1, int c2, uint32_t bar) {
    asm volatile("cp.async.bulk.tensor.3d.shared::cluster.global.mbarrier::complete_tx::bytes [%0], [%1, {%3, %4, %5}], [%2];"
                 ::"r"(dst), "l"(m), "r"(bar), "r"(c0), "r"(c1), "r"(c2) : "memory");
}
__device__ __forceinline__ void tma_3d_hint(uint32_t dst, const CUtensorMap* m, int c0, int c1, int c2, uint32_t bar, uint64_t pol) {
    asm volatile("cp.async.bulk.tensor.3d.shared::cluster.global.mbarrier::complete_tx::bytes.L2::cache_hint [%0], [%1, {%3, %4, %5}], [%2], %6;"
                 ::"r"(dst), "l"(m), "r"(bar), "r"(c0), "r"(c1), "r"(c2), "l"(pol) : "memory");
}
__device__ __forceinline__ void tma_3d_mc(uint32_t dst, const CUtensorMap* m, int c0, int c1, int c2, uint32_t bar) {
    asm volatile("cp.async.bulk.tensor.3d.shared::cluster.global.mbarrier::complete_tx::bytes.multicast::cluster [%0], [%1, {%3, %4, %5}], [%2], %6;"
                 ::"r"(dst), "l"(m), "r"(bar), "r"(c0), "r"(c1), "r"(c2), "h"((uint16_t)3) : "memory");
}
__device__ __forceinline__ void bulk_load(uint32_t dst, const void* src, uint32_t bytes, uint32_t bar) {
    asm volatile("cp.async.bulk.shared::cluster.global.mbarrier::complete_tx::bytes [%0], [%1], %2, [%3];"
                 ::"r"(dst), "l"(src), "r"(bytes), "r"(bar) : "memory");
}
__device__ __forceinline__ void cp_async16(uint32_t dst, const void* src) {
    asm volatile("cp.async.cg.shared.global [%0], [%1], 16;" ::"r"(dst), "l"(src) : "memory");
}
__device__ __forceinline__ void bulk_load_mc(uint32_t dst, const void* src, uint32_t bytes, uint32_t bar) {
    asm volatile("cp.async.bulk.shared::cluster.global.mbarrier::complete_tx::bytes.multicast::cluster [%0], [%1], %2, [%3], %4;"
                 ::"r"(dst), "l"(src), "r"(bytes), "r"(bar), "h"((uint16_t)3) : "memory");
}
__device__ __forceinline__ void tma_store_2d(const CUtensorMap* m, int c0, int c1, uint32_t src) {
    asm volatile("cp.async.bulk.tensor.2d.global.shared::cta.bulk_group [%0, {%2, %3}], [%1];"
                 ::"l"(m), "r"(src), "r"(c0), "r"(c1) : "memory");
}
__device__ __forceinline__ void bulk_commit() { asm volatile("cp.async.bulk.commit_group;" ::: "memory"); }
__device__ __forceinline__ void bulk_wait_read() { asm volatile("cp.async.bulk.wait_group.read 0;" ::: "memory"); }
__device__ __forceinline__ void fence_async_smem() { asm volatile("fence.proxy.async.shared::cta;" ::: "memory"); }
__device__ __forceinline__ void prefetch_map(const CUtensorMap* m) {
    asm volatile("prefetch.tensormap [%0];" ::"l"(m) : "memory");
}
__device__ __forceinline__ void red_release(unsigned* p) {
    asm volatile("red.release.gpu.global.add.u32 [%0], 1;" ::"l"(p) : "memory");
}
__device__ __forceinline__ unsigned ld_relaxed(const unsigned* p) {
    unsigned v;
    asm volatile("ld.relaxed.gpu.global.u32 %0, [%1];" : "=r"(v) : "l"(p) : "memory");
    return v;
}
__device__ __forceinline__ void wait_counter(const unsigned* p, unsigned target) {
    for (uint32_t n = 0; (int)(ld_relaxed(p) - target) < 0 && n < SPIN_LIMIT; n++) __nanosleep(100);
    asm volatile("fence.acquire.gpu;" ::: "memory");
    asm volatile("fence.proxy.async.global;" ::: "memory");
}
__device__ __forceinline__ void bar_sync(int id, int n) { asm volatile("bar.sync %0, %1;" ::"r"(id), "r"(n) : "memory"); }
__device__ __forceinline__ void bar_arrive(int id, int n) { asm volatile("bar.arrive %0, %1;" ::"r"(id), "r"(n) : "memory"); }
__device__ __forceinline__ void cluster_sync() {
    asm volatile("barrier.cluster.arrive.relaxed.aligned;\nbarrier.cluster.wait.aligned;" ::: "memory");
}
__device__ __forceinline__ void wg_fence() { asm volatile("wgmma.fence.sync.aligned;" ::: "memory"); }
__device__ __forceinline__ void wg_commit() { asm volatile("wgmma.commit_group.sync.aligned;" ::: "memory"); }
template <int N> __device__ __forceinline__ void wg_wait() { asm volatile("wgmma.wait_group.sync.aligned %0;" ::"n"(N) : "memory"); }
template <int N> __device__ __forceinline__ void reg_fence(float (&a)[N]) {
#pragma unroll
    for (int i = 0; i < N; i++) asm volatile("" : "+f"(a[i])::"memory");
}
template <int N> __device__ __forceinline__ void reg_fence(uint32_t (&a)[N]) {
#pragma unroll
    for (int i = 0; i < N; i++) asm volatile("" : "+r"(a[i])::"memory");
}
__device__ __forceinline__ uint32_t pack_bf16(float lo, float hi) {
    uint32_t r;
    asm("cvt.rn.bf16x2.f32 %0, %1, %2;" : "=r"(r) : "f"(hi), "f"(lo));
    return r;
}
__device__ __forceinline__ float bf_lo(uint32_t v) { return __uint_as_float(v << 16); }
__device__ __forceinline__ float bf_hi(uint32_t v) { return __uint_as_float(v & 0xffff0000u); }
__device__ __forceinline__ float bf_round(float v) { return __bfloat162float(__float2bfloat16_rn(v)); }
__device__ __forceinline__ float ex2(float v) {
    float r;
    asm("ex2.approx.ftz.f32 %0, %1;" : "=f"(r) : "f"(v));
    return r;
}
__device__ __forceinline__ float sqrt_approx(float v) {
    float r;
    asm("sqrt.approx.ftz.f32 %0, %1;" : "=f"(r) : "f"(v));
    return r;
}
__device__ __forceinline__ float rcp_approx(float v) {
    float r;
    asm("rcp.approx.ftz.f32 %0, %1;" : "=f"(r) : "f"(v));
    return r;
}
__device__ __forceinline__ float silu_f(float v) { return v * rcp_approx(1.0f + ex2(v * -1.4426950408889634f)); }
__device__ __forceinline__ void stmatrix_x4(uint32_t addr, uint32_t r0, uint32_t r1, uint32_t r2, uint32_t r3) {
    asm volatile("stmatrix.sync.aligned.m8n8.x4.shared.b16 [%0], {%1, %2, %3, %4};"
                 ::"r"(addr), "r"(r0), "r"(r1), "r"(r2), "r"(r3) : "memory");
}
__device__ __forceinline__ void sts128(uint32_t addr, uint32_t r0, uint32_t r1, uint32_t r2, uint32_t r3) {
    asm volatile("st.shared.v4.b32 [%0], {%1, %2, %3, %4};" ::"r"(addr), "r"(r0), "r"(r1), "r"(r2), "r"(r3) : "memory");
}
__device__ __forceinline__ void lds128(uint32_t addr, uint32_t& r0, uint32_t& r1, uint32_t& r2, uint32_t& r3) {
    asm volatile("ld.shared.v4.b32 {%0, %1, %2, %3}, [%4];" : "=r"(r0), "=r"(r1), "=r"(r2), "=r"(r3) : "r"(addr) : "memory");
}
__device__ __forceinline__ void ldmatrix_x4(uint32_t addr, uint32_t& r0, uint32_t& r1, uint32_t& r2, uint32_t& r3) {
    asm volatile("ldmatrix.sync.aligned.m8n8.x4.shared.b16 {%0, %1, %2, %3}, [%4];"
                 : "=r"(r0), "=r"(r1), "=r"(r2), "=r"(r3) : "r"(addr) : "memory");
}
__device__ __forceinline__ uint32_t bf2_mul(uint32_t a, uint32_t b) {
    uint32_t r;
    asm("mul.rn.bf16x2 %0, %1, %2;" : "=r"(r) : "r"(a), "r"(b));
    return r;
}
__device__ __forceinline__ uint32_t bf2_add(uint32_t a, uint32_t b) {
    uint32_t r;
    asm("add.rn.bf16x2 %0, %1, %2;" : "=r"(r) : "r"(a), "r"(b));
    return r;
}
__device__ __forceinline__ uint64_t policy_evict_first() {
    uint64_t p;
    asm("createpolicy.fractional.L2::evict_first.b64 %0, 1.0;" : "=l"(p));
    return p;
}

__device__ __forceinline__ uint64_t make_desc(uint32_t addr, uint32_t lbo_bytes) {
    return (uint64_t)((addr & 0x3FFFF) >> 4) | ((uint64_t)(lbo_bytes >> 4) << 16) | ((uint64_t)(1024 >> 4) << 32) | (1ull << 62);
}

__device__ __forceinline__ void wgmma_n256_ss(float (&d)[128], uint64_t da, uint64_t db, int acc) {
    asm volatile(
        "{\n.reg .pred p;\nsetp.ne.b32 p, %130, 0;\n"
        "wgmma.mma_async.sync.aligned.m64n256k16.f32.bf16.bf16 {"
        "%0, %1, %2, %3, %4, %5, %6, %7, %8, %9, %10, %11, %12, %13, %14, %15, "
        "%16, %17, %18, %19, %20, %21, %22, %23, %24, %25, %26, %27, %28, %29, %30, %31, "
        "%32, %33, %34, %35, %36, %37, %38, %39, %40, %41, %42, %43, %44, %45, %46, %47, "
        "%48, %49, %50, %51, %52, %53, %54, %55, %56, %57, %58, %59, %60, %61, %62, %63, "
        "%64, %65, %66, %67, %68, %69, %70, %71, %72, %73, %74, %75, %76, %77, %78, %79, "
        "%80, %81, %82, %83, %84, %85, %86, %87, %88, %89, %90, %91, %92, %93, %94, %95, "
        "%96, %97, %98, %99, %100, %101, %102, %103, %104, %105, %106, %107, %108, %109, %110, %111, "
        "%112, %113, %114, %115, %116, %117, %118, %119, %120, %121, %122, %123, %124, %125, %126, %127"
        "}, %128, %129, p, 1, 1, 1, 0;\n}\n"
        :
        "+f"(d[0]), "+f"(d[1]), "+f"(d[2]), "+f"(d[3]), "+f"(d[4]), "+f"(d[5]), "+f"(d[6]), "+f"(d[7]),
        "+f"(d[8]), "+f"(d[9]), "+f"(d[10]), "+f"(d[11]), "+f"(d[12]), "+f"(d[13]), "+f"(d[14]), "+f"(d[15]),
        "+f"(d[16]), "+f"(d[17]), "+f"(d[18]), "+f"(d[19]), "+f"(d[20]), "+f"(d[21]), "+f"(d[22]), "+f"(d[23]),
        "+f"(d[24]), "+f"(d[25]), "+f"(d[26]), "+f"(d[27]), "+f"(d[28]), "+f"(d[29]), "+f"(d[30]), "+f"(d[31]),
        "+f"(d[32]), "+f"(d[33]), "+f"(d[34]), "+f"(d[35]), "+f"(d[36]), "+f"(d[37]), "+f"(d[38]), "+f"(d[39]),
        "+f"(d[40]), "+f"(d[41]), "+f"(d[42]), "+f"(d[43]), "+f"(d[44]), "+f"(d[45]), "+f"(d[46]), "+f"(d[47]),
        "+f"(d[48]), "+f"(d[49]), "+f"(d[50]), "+f"(d[51]), "+f"(d[52]), "+f"(d[53]), "+f"(d[54]), "+f"(d[55]),
        "+f"(d[56]), "+f"(d[57]), "+f"(d[58]), "+f"(d[59]), "+f"(d[60]), "+f"(d[61]), "+f"(d[62]), "+f"(d[63]),
        "+f"(d[64]), "+f"(d[65]), "+f"(d[66]), "+f"(d[67]), "+f"(d[68]), "+f"(d[69]), "+f"(d[70]), "+f"(d[71]),
        "+f"(d[72]), "+f"(d[73]), "+f"(d[74]), "+f"(d[75]), "+f"(d[76]), "+f"(d[77]), "+f"(d[78]), "+f"(d[79]),
        "+f"(d[80]), "+f"(d[81]), "+f"(d[82]), "+f"(d[83]), "+f"(d[84]), "+f"(d[85]), "+f"(d[86]), "+f"(d[87]),
        "+f"(d[88]), "+f"(d[89]), "+f"(d[90]), "+f"(d[91]), "+f"(d[92]), "+f"(d[93]), "+f"(d[94]), "+f"(d[95]),
        "+f"(d[96]), "+f"(d[97]), "+f"(d[98]), "+f"(d[99]), "+f"(d[100]), "+f"(d[101]), "+f"(d[102]), "+f"(d[103]),
        "+f"(d[104]), "+f"(d[105]), "+f"(d[106]), "+f"(d[107]), "+f"(d[108]), "+f"(d[109]), "+f"(d[110]), "+f"(d[111]),
        "+f"(d[112]), "+f"(d[113]), "+f"(d[114]), "+f"(d[115]), "+f"(d[116]), "+f"(d[117]), "+f"(d[118]), "+f"(d[119]),
        "+f"(d[120]), "+f"(d[121]), "+f"(d[122]), "+f"(d[123]), "+f"(d[124]), "+f"(d[125]), "+f"(d[126]), "+f"(d[127])
        : "l"(da), "l"(db), "r"(acc));
}

__device__ __forceinline__ void wgmma_n192_ss(float* d, uint64_t da, uint64_t db, int acc) {
    asm volatile(
        "{\n.reg .pred p;\nsetp.ne.b32 p, %98, 0;\n"
        "wgmma.mma_async.sync.aligned.m64n192k16.f32.bf16.bf16 {"
        "%0, %1, %2, %3, %4, %5, %6, %7, %8, %9, %10, %11, %12, %13, %14, %15, "
        "%16, %17, %18, %19, %20, %21, %22, %23, %24, %25, %26, %27, %28, %29, %30, %31, "
        "%32, %33, %34, %35, %36, %37, %38, %39, %40, %41, %42, %43, %44, %45, %46, %47, "
        "%48, %49, %50, %51, %52, %53, %54, %55, %56, %57, %58, %59, %60, %61, %62, %63, "
        "%64, %65, %66, %67, %68, %69, %70, %71, %72, %73, %74, %75, %76, %77, %78, %79, "
        "%80, %81, %82, %83, %84, %85, %86, %87, %88, %89, %90, %91, %92, %93, %94, %95"
        "}, %96, %97, p, 1, 1, 1, 0;\n}\n"
        :
        "+f"(d[0]), "+f"(d[1]), "+f"(d[2]), "+f"(d[3]), "+f"(d[4]), "+f"(d[5]), "+f"(d[6]), "+f"(d[7]),
        "+f"(d[8]), "+f"(d[9]), "+f"(d[10]), "+f"(d[11]), "+f"(d[12]), "+f"(d[13]), "+f"(d[14]), "+f"(d[15]),
        "+f"(d[16]), "+f"(d[17]), "+f"(d[18]), "+f"(d[19]), "+f"(d[20]), "+f"(d[21]), "+f"(d[22]), "+f"(d[23]),
        "+f"(d[24]), "+f"(d[25]), "+f"(d[26]), "+f"(d[27]), "+f"(d[28]), "+f"(d[29]), "+f"(d[30]), "+f"(d[31]),
        "+f"(d[32]), "+f"(d[33]), "+f"(d[34]), "+f"(d[35]), "+f"(d[36]), "+f"(d[37]), "+f"(d[38]), "+f"(d[39]),
        "+f"(d[40]), "+f"(d[41]), "+f"(d[42]), "+f"(d[43]), "+f"(d[44]), "+f"(d[45]), "+f"(d[46]), "+f"(d[47]),
        "+f"(d[48]), "+f"(d[49]), "+f"(d[50]), "+f"(d[51]), "+f"(d[52]), "+f"(d[53]), "+f"(d[54]), "+f"(d[55]),
        "+f"(d[56]), "+f"(d[57]), "+f"(d[58]), "+f"(d[59]), "+f"(d[60]), "+f"(d[61]), "+f"(d[62]), "+f"(d[63]),
        "+f"(d[64]), "+f"(d[65]), "+f"(d[66]), "+f"(d[67]), "+f"(d[68]), "+f"(d[69]), "+f"(d[70]), "+f"(d[71]),
        "+f"(d[72]), "+f"(d[73]), "+f"(d[74]), "+f"(d[75]), "+f"(d[76]), "+f"(d[77]), "+f"(d[78]), "+f"(d[79]),
        "+f"(d[80]), "+f"(d[81]), "+f"(d[82]), "+f"(d[83]), "+f"(d[84]), "+f"(d[85]), "+f"(d[86]), "+f"(d[87]),
        "+f"(d[88]), "+f"(d[89]), "+f"(d[90]), "+f"(d[91]), "+f"(d[92]), "+f"(d[93]), "+f"(d[94]), "+f"(d[95])
        : "l"(da), "l"(db), "r"(acc));
}

template <int TB>
__device__ __forceinline__ void wgmma_n128_rs(float (&d)[64], uint32_t a0, uint32_t a1, uint32_t a2, uint32_t a3, uint32_t db, int acc) {
    asm volatile(
        "{\n.reg .pred p;\n.reg .b64 db;\nsetp.ne.b32 p, %69, 0;\nmov.b64 db, {%68, 0x40000040};\n"
        "wgmma.mma_async.sync.aligned.m64n128k16.f32.bf16.bf16 {"
        "%0, %1, %2, %3, %4, %5, %6, %7, %8, %9, %10, %11, %12, %13, %14, %15, "
        "%16, %17, %18, %19, %20, %21, %22, %23, %24, %25, %26, %27, %28, %29, %30, %31, "
        "%32, %33, %34, %35, %36, %37, %38, %39, %40, %41, %42, %43, %44, %45, %46, %47, "
        "%48, %49, %50, %51, %52, %53, %54, %55, %56, %57, %58, %59, %60, %61, %62, %63"
        "}, {%64, %65, %66, %67}, db, p, 1, 1, %70;\n}\n"
        :
        "+f"(d[0]), "+f"(d[1]), "+f"(d[2]), "+f"(d[3]), "+f"(d[4]), "+f"(d[5]), "+f"(d[6]), "+f"(d[7]),
        "+f"(d[8]), "+f"(d[9]), "+f"(d[10]), "+f"(d[11]), "+f"(d[12]), "+f"(d[13]), "+f"(d[14]), "+f"(d[15]),
        "+f"(d[16]), "+f"(d[17]), "+f"(d[18]), "+f"(d[19]), "+f"(d[20]), "+f"(d[21]), "+f"(d[22]), "+f"(d[23]),
        "+f"(d[24]), "+f"(d[25]), "+f"(d[26]), "+f"(d[27]), "+f"(d[28]), "+f"(d[29]), "+f"(d[30]), "+f"(d[31]),
        "+f"(d[32]), "+f"(d[33]), "+f"(d[34]), "+f"(d[35]), "+f"(d[36]), "+f"(d[37]), "+f"(d[38]), "+f"(d[39]),
        "+f"(d[40]), "+f"(d[41]), "+f"(d[42]), "+f"(d[43]), "+f"(d[44]), "+f"(d[45]), "+f"(d[46]), "+f"(d[47]),
        "+f"(d[48]), "+f"(d[49]), "+f"(d[50]), "+f"(d[51]), "+f"(d[52]), "+f"(d[53]), "+f"(d[54]), "+f"(d[55]),
        "+f"(d[56]), "+f"(d[57]), "+f"(d[58]), "+f"(d[59]), "+f"(d[60]), "+f"(d[61]), "+f"(d[62]), "+f"(d[63])
        : "r"(a0), "r"(a1), "r"(a2), "r"(a3), "r"(db), "r"(acc), "n"(TB));
}

__device__ __forceinline__ void wgmma_n128_ss(float* d, uint64_t da, uint64_t db, int acc) {
    asm volatile(
        "{\n.reg .pred p;\nsetp.ne.b32 p, %66, 0;\n"
        "wgmma.mma_async.sync.aligned.m64n128k16.f32.bf16.bf16 {"
        "%0, %1, %2, %3, %4, %5, %6, %7, %8, %9, %10, %11, %12, %13, %14, %15, "
        "%16, %17, %18, %19, %20, %21, %22, %23, %24, %25, %26, %27, %28, %29, %30, %31, "
        "%32, %33, %34, %35, %36, %37, %38, %39, %40, %41, %42, %43, %44, %45, %46, %47, "
        "%48, %49, %50, %51, %52, %53, %54, %55, %56, %57, %58, %59, %60, %61, %62, %63"
        "}, %64, %65, p, 1, 1, 0, 1;\n}\n"
        :
        "+f"(d[0]), "+f"(d[1]), "+f"(d[2]), "+f"(d[3]), "+f"(d[4]), "+f"(d[5]), "+f"(d[6]), "+f"(d[7]),
        "+f"(d[8]), "+f"(d[9]), "+f"(d[10]), "+f"(d[11]), "+f"(d[12]), "+f"(d[13]), "+f"(d[14]), "+f"(d[15]),
        "+f"(d[16]), "+f"(d[17]), "+f"(d[18]), "+f"(d[19]), "+f"(d[20]), "+f"(d[21]), "+f"(d[22]), "+f"(d[23]),
        "+f"(d[24]), "+f"(d[25]), "+f"(d[26]), "+f"(d[27]), "+f"(d[28]), "+f"(d[29]), "+f"(d[30]), "+f"(d[31]),
        "+f"(d[32]), "+f"(d[33]), "+f"(d[34]), "+f"(d[35]), "+f"(d[36]), "+f"(d[37]), "+f"(d[38]), "+f"(d[39]),
        "+f"(d[40]), "+f"(d[41]), "+f"(d[42]), "+f"(d[43]), "+f"(d[44]), "+f"(d[45]), "+f"(d[46]), "+f"(d[47]),
        "+f"(d[48]), "+f"(d[49]), "+f"(d[50]), "+f"(d[51]), "+f"(d[52]), "+f"(d[53]), "+f"(d[54]), "+f"(d[55]),
        "+f"(d[56]), "+f"(d[57]), "+f"(d[58]), "+f"(d[59]), "+f"(d[60]), "+f"(d[61]), "+f"(d[62]), "+f"(d[63])
        : "l"(da), "l"(db), "r"(acc));
}

__device__ __forceinline__ void wgmma_n8_ta(float* d, uint64_t da, uint64_t db) {
    asm volatile("wgmma.mma_async.sync.aligned.m64n8k16.f32.bf16.bf16 {%0, %1, %2, %3}, %4, %5, 1, 1, 1, 1, 0;\n"
                 : "+f"(d[0]), "+f"(d[1]), "+f"(d[2]), "+f"(d[3]) : "l"(da), "l"(db));
}

#define PROF(slot, role)
#undef PROF_GT
#define PROF_GT(slot)

struct Params {
    const __nv_bfloat16* x;
    const __nv_bfloat16* w_r;
    const uint8_t *c_kv, *w_uk, *w_uv;
    uint8_t* out;
};
__device__ __forceinline__ void lsu_prefetch(const void* p) { asm volatile("prefetch.global.L2 [%0];" ::"l"(p) : "memory"); }

template <typename T>
__device__ __forceinline__ T* ptr_off(T* base, uint32_t off) {
    uint32_t lo, hi;
    asm("mov.b64 {%0, %1}, %2;" : "=r"(lo), "=r"(hi) : "l"(base));
    asm("add.cc.u32 %0, %0, %2;\naddc.u32 %1, %1, 0;" : "+r"(lo), "+r"(hi) : "r"(off));
    T* r;
    asm("mov.b64 %0, {%1, %2};" : "=l"(r) : "r"(lo), "r"(hi));
    return r;
}
__device__ __forceinline__ int kv_head(int pair) { return (pair & 15) >> 1; }
__device__ __forceinline__ int kv_tokens(int pair) { return (pair & 1) * 4 + (pair >> 4); }
__device__ __forceinline__ int attn_rowblock(int pair, int seg) {
    int j = pair & 3, hl = pair >> 2;
    return ((hl & 1) ^ seg) ? j : 7 - j;
}
__device__ __forceinline__ int outproj_head(int i, int ib) {
    if (i < 16) return i;
    return 16 + 2 * (i & 7) + ((ib < 4) ^ ((i >> 3) & 1));
}

__device__ __forceinline__ void pin_value(uint32_t& v) { asm volatile("" : "+r"(v)); }
__device__ __forceinline__ void pin_value(int& v) { asm volatile("" : "+r"(v)); }
__device__ __forceinline__ void pin_value(const uint8_t*& v) { asm volatile("" : "+l"(v)); }

__device__ __forceinline__ void producer(const Params& P, uint32_t sb, int pair, int c,
                                         const CUtensorMap* m_ckv, const CUtensorMap* m_wu,
                                         const CUtensorMap* m_wq, const CUtensorMap* m_wo) {
    const int hl = pair >> 2;
    const int ibA = attn_rowblock(pair, 0), nA = 2 * ibA + 2;
    const int ib = (pair >> 1) & 7, mi = 2 * ib + c, nb = (pair >> 4) * 4 + (pair & 1) * 2;
    const bool leader = elect_one();
    uint32_t g = 4, tail = 0;
    if (leader) prefetch_map(m_wq);
    auto wait_released = [&](uint32_t need) {
#pragma unroll 1
        for (; tail <= need; tail++) mbar_wait(sb + BAR_EMPTY + (tail & 7) * 8, (tail >> 3) & 1);
    };
    auto wait_released_here = [&](uint32_t need) {
#pragma unroll 1
        for (; tail < need; tail++) mbar_wait(sb + BAR_EMPTY + (tail & 7) * 8, (tail >> 3) & 1);
        if (tail == need) mbar_wait(sb + BAR_EMPTYL + (need & 7) * 8, (need >> 3) & 1);
    };
    auto wait_released_peer = [&](uint32_t need) {
        if (tail == need) {
            uint32_t eb = sb + BAR_EMPTY + (need & 7) * 8, ep = (need >> 3) & 1;
            tail++;
            mbar_wait(eb, ep);
        }
    };
    auto full_bar = [&]() { return sb + BAR_FULL + (g & 7) * 8; };
    auto pin = [](auto&... v) { (pin_value(v), ...); };
#pragma unroll 1
    for (int rnd = 0; rnd < 2; rnd++) {
#pragma unroll 1
        for (int i = rnd ? 0 : 4; i < 16; i++) {
            int kb = i & 7, h2 = (kv_head(pair) + (i & 8) + rnd * 16) * 2, krow = kb * 64;
            uint32_t pg = sb + (i & 3) * (3 * PAGE), pb = pg + (1 + c) * PAGE, bar = full_bar();
            pin(kb, h2, krow, pg, pb, bar);
            const uint32_t need = g - 4 - (i < 2);
            wait_released_here(need);
            if (leader) {
                mbar_expect_tx(bar, 3 * PAGE);
                tma_3d(pg, m_wu, 0, krow, h2, bar);
            }
            wait_released_peer(need);
            if (leader) {
                tma_3d_mc(pb, m_ckv, 0, kv_tokens(pair) * 256 + c * 128, kb, bar);
                if (rnd == 1 && i == 3) asm volatile("red.relaxed.gpu.global.add.u32 [%0], 1;" ::"l"(ptr_off(g_sync.kvfree, hl * 32)) : "memory");
            }
            g++;
        }
        mbar_sleep(sb + BAR_DEP, 0);
        const uint8_t* xa = ptr_off(g_xn, ibA * (16 * 32768) + c * PAGE);
        const uint8_t* xb = ptr_off(g_xn, (7 - ibA) * (16 * 32768) + (1 - c) * PAGE);
#pragma unroll 1
        for (int kb = 0; kb < DM / 64; kb++) {
            uint32_t pg = sb + (kb & 3) * (3 * PAGE), pw = pg + 2 * PAGE + c * 8192, bar = full_bar(), p2 = pg + PAGE;
            int krow = kb * 64;
            pin(pg, pw, p2, bar, krow);
            wait_released_here(g - 4);
            if (leader) {
                mbar_expect_tx(bar, 3 * PAGE);
                bulk_load(pg, xa, PAGE, bar);
            }
            wait_released_peer(g - 4);
            if (leader) {
                tma_3d_mc(pw, m_wq, 0, krow, (rnd * 16 + hl) * 2 + c, bar);
                bulk_load(p2, xb, PAGE, bar);
            }
            g++;
            xa += 32768;
            xb += 32768;
        }
        mbar_sleep(sb + BAR_DEP + 8 + rnd * 16, 0);
        if (rnd == 1 && leader) prefetch_map(m_wo);
        uint32_t pg = sb + c * PAGE;
#pragma unroll 1
        for (int j = 0; j < 36; j++) {
            const bool isk = j == 0 || ((j & 1) && j != 35);
            const int t = isk ? (j + 1) >> 1 : (j - 1) >> 1;
            const uint8_t* src = ptr_off(g_kv, (hl * 16 + (t >= nA ? t - nA : t)) * 65536 + (isk ? 0 : 32768) + c * PAGE);
            uint32_t bar = full_bar(), need = g - 6 + (j < 2) + (j < 5);
            pin(src, bar, need);
            wait_released(need);
            if (leader) {
                mbar_expect_tx(bar, 2 * PAGE);
                bulk_load_mc(pg, src, PAGE, bar);
            }
            g++;
            if (rnd == 0 && j >= 22 && j < 34) {
                const int cta = pair * 2 + c, i = j - 22;
                const uint32_t l = (threadIdx.x & 31) * 128;
                if (i < 8) lsu_prefetch(ptr_off(i & 1 ? P.w_uv : P.w_uk, cta * 32768 + (i >> 1) * 8192 + 4096 + l));
                else lsu_prefetch(ptr_off(P.c_kv, cta * 16384 + (i - 8) * 4096 + l));
            }
            pg = pg >= sb + SM_REGION - 2 * PAGE ? pg - (SM_REGION - 2 * PAGE) : pg + 2 * PAGE;
        }
    }
    uint32_t pg = sb;
#pragma unroll 1
    for (int i = 0; i < 64; i++) {
        if ((i & 15) == 0 && i != 16) mbar_sleep(sb + BAR_DEP + 32 + (i >> 1) - (i ? 8 : 0), 0);
        const int kb = outproj_head(i >> 1, ib) * 2 + (i & 1);
        const uint8_t* src = ptr_off(g_ctx, (mi * 64 + kb) * PAGE);
        uint32_t bar = full_bar(), pw = pg + PAGE + c * 8192;
        int krow = kb * 64;
        pin(src, bar, pw, krow);
        wait_released_here(g - 6);
        if (leader) {
            mbar_expect_tx(bar, 2 * PAGE);
            bulk_load(pg, src, PAGE, bar);
        }
        wait_released_peer(g - 6);
        if (leader) tma_3d_mc(pw, m_wo, 0, krow, nb + c, bar);
        g++;
        pg = pg == sb + SM_REGION - 2 * PAGE ? sb : pg + 2 * PAGE;
    }
}

__device__ __forceinline__ uint32_t xn_block(int row64, int kb) {
    return (((row64 >> 2) * 16 + kb) * 4 + ((row64 & 1) * 2 + (((row64 >> 1) & 1) ^ 1))) * 8192;
}
__device__ __forceinline__ uint32_t image_offset(int row, int ch) {
    return xn_block(row >> 6, ch >> 3) + (row & 63) * 128 + (((ch & 7) ^ (row & 7)) << 4);
}
__device__ __forceinline__ uint32_t bf2_sub(uint32_t a, uint32_t b) {
    uint32_t r;
    asm("sub.rn.bf16x2 %0, %1, %2;" : "=r"(r) : "r"(a), "r"(b));
    return r;
}
__device__ __forceinline__ uint32_t bf2_fma(uint32_t a, uint32_t b, uint32_t c) {
    uint32_t r;
    asm("fma.rn.bf16x2 %0, %1, %2, %3;" : "=r"(r) : "r"(a), "r"(b), "r"(c));
    return r;
}
template <int N0, int N>
__device__ __forceinline__ void ln_sums(const uint32_t (&u)[N], float& sum, float& sq) {
    float s0 = 0.f, s1 = 0.f, q0 = 0.f, q1 = 0.f;
#pragma unroll
    for (int k = N0; k < N0 + 16; k++) {
        const float a = bf_lo(u[k]), b = bf_hi(u[k]);
        s0 += a; s1 += b;
        q0 = fmaf(a, a, q0); q1 = fmaf(b, b, q1);
    }
    sum = s0 + s1;
    sq = q0 + q1;
}
__device__ __forceinline__ void ln_finish(float sum, float sq, uint32_t& mean2, uint32_t& rhi2, uint32_t& rlo2) {
    const float ms = sum * (1.0f / DM);
    const float var = fmaxf(fmaf(-ms, ms, sq * (1.0f / DM)), 0.f);
    const float rden = rcp_approx(bf_round(sqrt_approx(bf_round(bf_round(var) + 1e-5f))));
    const float rhi = bf_round(rden);
    mean2 = pack_bf16(ms, ms);
    rhi2 = pack_bf16(rhi, rhi);
    rlo2 = pack_bf16(rden - rhi, rden - rhi);
}
template <int N0, int N>
__device__ __forceinline__ void ln_apply(uint32_t (&u)[N], uint32_t mean2, uint32_t rhi2, uint32_t rlo2, uint8_t* dst) {
#pragma unroll
    for (int i = 0; i < 4; i++) {
        uint32_t o[4];
#pragma unroll
        for (int k = 0; k < 4; k++) {
            const uint32_t d = bf2_sub(u[N0 + 4 * i + k], mean2);
            o[k] = bf2_fma(d, rhi2, bf2_mul(d, rlo2));
        }
#pragma unroll
        for (int k = 0; k < 4; k++) u[N0 + 4 * i + k] = o[k];
        __stcg(reinterpret_cast<uint4*>(dst + i * 131072), make_uint4(o[0], o[1], o[2], o[3]));
    }
}
__device__ __forceinline__ int query_rowblock(int pair, int c, int w, int seg) {
    const int qA = (w ? 0 : 2) + c;
    return 4 * attn_rowblock(pair, seg) + (seg ? 3 - qA : qA);
}

__device__ __noinline__ void fetch_helper(const uint8_t* w_u, const uint8_t* x, uint32_t sb, int w, int lane, int pair, int c) {
    const uint32_t page = sb + SM_REGION + w * PAGE + lane * 16;
    mbar_sleep(sb + BAR_FULL + 5 * 8, 0);
#pragma unroll 1
    for (int i = 0; i < 2; i++) {
        lsu_prefetch(ptr_off(w_u, ((pair * 2 + c) * 4 + i * 2 + (lane >> 4)) * 8192 + 2048 + (lane & 15) * 128));
        __nanosleep(300);
    }
    const unsigned e1 = __ldcg(&g_sync.done) / NCTA + 1;
#pragma unroll 1
    for (int e = 1; e <= 7; e += 2) mbar_sleep(sb + BAR_DONE + 8, (e >> 1) & 1);
    const int rb = ((pair >> 1) & 7) * 4 + c * 2 + w, kb0 = (pair >> 4) * 4 + (pair & 1) * 2;
    const uint8_t* src = ptr_off(g_xn, xn_block(rb, kb0) + lane * 16);
#pragma unroll 1
    for (int i = 0; i < 32; i += 4) {
#pragma unroll
        for (int k = 0; k < 4; k++) cp_async16(page + (i + k) * 512, src + (i + k) * 512 + (i >> 4) * (32768 - 8192));
        __nanosleep(200);
    }
#pragma unroll 1
    for (int i = 0; i < 4; i++) lsu_prefetch(ptr_off(x, (rb * 64 + i * 16 + (lane >> 1)) * (DM * 2) + kb0 * 128 + (lane & 1) * 128));
    wait_counter(&g_sync.ffn_done, e1);
    const int r = __ldcg(ptr_off(g_sel, (lane >> 4) * 4)) - rb * 64, ch = lane & 15;
    const uint4 t = __ldcg(ptr_off(g_routed, ((lane >> 4) * 128 + kb0 * 8 + ch) * 16));
    asm volatile("cp.async.wait_all;" ::: "memory");
    __syncwarp();
    if (r >= 0 && r < 64)
        sts128(sb + SM_REGION + w * PAGE + (ch >> 3) * 8192 + r * 128 + (((ch & 7) ^ (r & 7)) << 4), t.x, t.y, t.z, t.w);
    __syncwarp();
    if (lane == 0) mbar_arrive(sb + BAR_G + w * 8);
    PROF(20, 2);
}

__device__ __noinline__ void sync_helper(uint32_t sb, int lane, int pair, int c) {
    const unsigned e1 = __ldcg(&g_sync.done) / NCTA + 1;
    const int ib = (pair >> 1) & 7;
    int e = 0, b = 0;
#pragma unroll 1
    for (uint32_t n = 0; (e < 9 || b < 7) && n < SPIN_LIMIT; n++) {
        if (e < 9 && __all_sync(~0u, mbar_test(sb + BAR_DONE + (e & 1) * 8, (e >> 1) & 1))) {
            const int rnd = e > 4, ev = (e - 1) & 3;
            unsigned* flag = e == 0 ? &g_sync.ln
                           : ev < 2 ? ptr_off(g_sync.kv, (rnd * 16 + kv_head(pair) + 8 * ev) * 32)
                                    : ptr_off(g_sync.ctx, (query_rowblock(pair, c, lane & 1, ev & 1) * NH + rnd * 16 + (pair >> 2)) * 4);
            asm volatile("fence.proxy.async.global;\nfence.release.gpu;" ::: "memory");
            if (lane < ((e == 0 || ev < 2) ? 1 : 2)) asm volatile("red.relaxed.gpu.global.add.u32 [%0], 1;" ::"l"(flag) : "memory");
            PROF(10 + e, 2);
            e++;
        }
        if (b < 7 && e > 0 && (b < 4 || (n & POLL_MASK) == 0)) {
            const int i = b == 4 ? lane >> 1 : 8 * b - 24 + ((lane >> 1) & 7);
            const unsigned* cnt = b == 0 ? &g_sync.ln
                                : b == 2 ? ptr_off(g_sync.kvfree, (kv_head(pair) + 8 * (lane & 1)) * 32)
                                : b < 4 ? ptr_off(g_sync.kv, ((b >> 1) * 16 + (pair >> 2)) * 32)
                                        : ptr_off(g_sync.ctx, ((4 * ib + 2 * c + (lane & 1)) * NH + outproj_head(i & 31, ib)) * 4);
            if (__all_sync(~0u, (int)(ld_relaxed(cnt) - e1 * (b == 0 ? NMAIN : b == 2 ? 8 : b < 4 ? 16 : 1)) >= 0)) {
                asm volatile("fence.acquire.gpu;\nfence.proxy.async.global;" ::: "memory");
                __syncwarp();
                if (lane == 0) mbar_arrive(sb + BAR_DEP + b * 8);
                PROF(1 + b, 2);
                b++;
            }
        }
        __nanosleep(150);
    }
}

__device__ __forceinline__ unsigned long long block_max_key(unsigned long long k, unsigned long long* red, int tid) {
#pragma unroll
    for (int o = 16; o; o >>= 1) {
        unsigned long long t = __shfl_xor_sync(~0u, k, o);
        k = t > k ? t : k;
    }
    bar_sync(1, 256);
    if ((tid & 31) == 0) red[tid >> 5] = k;
    bar_sync(1, 256);
    k = red[0];
#pragma unroll
    for (int i = 1; i < 8; i++) k = red[i] > k ? red[i] : k;
    return k;
}

constexpr int FS = FF / 4;
constexpr int FSTAGE = 32768, FNST = 6;
constexpr int FN1 = 2 * (DM / 16), FN2 = FS / 16;

__device__ __forceinline__ void ffn_producer(uint32_t sb, int s, const CUtensorMap* m_gate, const CUtensorMap* m_up,
                                             const CUtensorMap* m_down) {
    const uint64_t pol = policy_evict_first();
    wait_counter(&g_sync.ln, (__ldcg(&g_sync.done) / NCTA + 1) * NMAIN);
    int slot = 0, ph = 1;
#pragma unroll 1
    for (int st = 0; st < FN1 + FN2; st++) {
        mbar_sleep(sb + BAR_EMPTY + slot * 8, ph);
        const uint32_t bar = sb + BAR_FULL + slot * 8;
        const bool up = st < FN1;
        mbar_expect_tx(bar, up ? FS * 32 : DM * 32);
        tma_3d_hint(sb + slot * FSTAGE, up ? ((st & 1) ? m_up : m_gate) : m_down, 0,
                    up ? (st >> 1) * 16 : s * FS + (st - FN1) * 16, up ? s * (FS / 64) : 0, bar, pol);
        if (++slot == FNST) { slot = 0; ph ^= 1; }
    }
}

__device__ __forceinline__ void ffn_cta(uint8_t* smem, uint32_t sb, int s, unsigned epoch, const __nv_bfloat16* w_r) {
    const int tid = threadIdx.x, lane = tid & 31;
    const int warp = __shfl_sync(~0u, tid >> 5, 0), w = warp >> 2;
    constexpr uint32_t XB = FNST * FSTAGE, HB = XB + 16384, AUX = HB + 14336;
    unsigned long long* red = reinterpret_cast<unsigned long long*>(smem + AUX);
    unsigned* flag = reinterpret_cast<unsigned*>(smem + AUX + 128);
    const unsigned e1 = epoch + 1;
    for (int i = tid; i < (16384 + 14336) / 16; i += 256) reinterpret_cast<uint4*>(smem + XB)[i] = make_uint4(0, 0, 0, 0);
    {
        float wf[32];
#pragma unroll
        for (int i = 0; i < 4; i++) {
            const uint4 t = __ldg(reinterpret_cast<const uint4*>(w_r) + lane + 32 * i);
            const uint32_t tu[4] = {t.x, t.y, t.z, t.w};
#pragma unroll
            for (int k = 0; k < 4; k++) { wf[8 * i + 2 * k] = bf_lo(tu[k]); wf[8 * i + 2 * k + 1] = bf_hi(tu[k]); }
        }
        if (tid == 0) wait_counter(&g_sync.ln, e1 * NMAIN);
        bar_sync(1, 256);
#pragma unroll 1
        for (int r0 = s * (SEQ / 4) + warp * (SEQ / 32); r0 < s * (SEQ / 4) + (warp + 1) * (SEQ / 32); r0 += 4) {
            uint4 t[4][4];
#pragma unroll
            for (int r = 0; r < 4; r++)
#pragma unroll
                for (int i = 0; i < 4; i++) t[r][i] = __ldcg(reinterpret_cast<const uint4*>(g_xn + image_offset(r0 + r, lane) + i * 131072));
            float acc[4];
#pragma unroll
            for (int r = 0; r < 4; r++) {
                float a = 0.f, b = 0.f;
#pragma unroll
                for (int i = 0; i < 4; i++) {
                    const uint32_t tu[4] = {t[r][i].x, t[r][i].y, t[r][i].z, t[r][i].w};
#pragma unroll
                    for (int k = 0; k < 4; k++) {
                        a = fmaf(bf_lo(tu[k]), wf[8 * i + 2 * k], a);
                        b = fmaf(bf_hi(tu[k]), wf[8 * i + 2 * k + 1], b);
                    }
                }
                acc[r] = a + b;
            }
#pragma unroll
            for (int o = 16; o; o >>= 1)
#pragma unroll
                for (int r = 0; r < 4; r++) acc[r] += __shfl_xor_sync(~0u, acc[r], o);
            if (lane < 4) __stcg(&g_r[r0 + lane], bf_round(lane == 0 ? acc[0] : lane == 1 ? acc[1] : lane == 2 ? acc[2] : acc[3]));
        }
        __threadfence();
        bar_sync(1, 256);
        if (tid == 0) {
            red_release(&g_sync.router);
            wait_counter(&g_sync.router, e1 * 4);
        }
        bar_sync(1, 256);
    }
    unsigned long long keys[8];
    unsigned long long best = 0;
#pragma unroll
    for (int i = 0; i < 8; i++) {
        int idx = tid + 256 * i;
        uint32_t b = __float_as_uint(__ldcg(&g_r[idx]) + 0.0f);
        b = (b & 0x80000000u) ? ~b : (b | 0x80000000u);
        keys[i] = ((unsigned long long)b << 32) | (unsigned)(SEQ - 1 - idx);
        best = keys[i] > best ? keys[i] : best;
    }
    const unsigned long long k0 = block_max_key(best, red, tid);
    best = 0;
#pragma unroll
    for (int i = 0; i < 8; i++) best = (keys[i] != k0 && keys[i] > best) ? keys[i] : best;
    const unsigned long long k1 = block_max_key(best, red, tid);
    const int row = SEQ - 1 - (int)((w ? k1 : k0) & 0xffffffffu);
    const int ch = tid & 127;
    const uint4 xrow = __ldcg(reinterpret_cast<const uint4*>(g_xn + image_offset(row, ch)));
    *reinterpret_cast<uint4*>(smem + XB + (ch >> 3) * 1024 + w * 128 + (((ch & 7) ^ w) << 4)) = xrow;
    fence_async_smem();
    bar_sync(1, 256);
    PROF(20, tid >> 7);
    int slot = 0, ph = 0, prev = 0;
    auto next_stage = [&](bool has_prev) {
        wg_commit();
        wg_wait<1>();
        if (has_prev && lane < 2) mbar_arrive(sb + BAR_EMPTY + prev * 8);
        prev = slot;
        if (++slot == FNST) { slot = 0; ph ^= 1; }
    };
    {
        float ag[28], au[28];
#pragma unroll
        for (int i = 0; i < 28; i++) ag[i] = au[i] = 0.f;
#pragma unroll 1
        for (int ks = 0; ks < DM / 16; ks++) {
            const uint64_t db = make_desc(sb + XB + (ks >> 2) * 1024 + (ks & 3) * 32, 16);
            mbar_wait(sb + BAR_FULL + slot * 8, ph);
            uint64_t da = make_desc(sb + slot * FSTAGE + w * (7 * 2048), 16);
            wg_fence();
#pragma unroll
            for (int b = 0; b < 7; b++) wgmma_n8_ta(ag + 4 * b, da + b * 128, db);
            next_stage(ks > 0);
            mbar_wait(sb + BAR_FULL + slot * 8, ph);
            da = make_desc(sb + slot * FSTAGE + w * (7 * 2048), 16);
            wg_fence();
#pragma unroll
            for (int b = 0; b < 7; b++) wgmma_n8_ta(au + 4 * b, da + b * 128, db);
            next_stage(true);
        }
        wg_wait<0>();
        reg_fence(ag);
        reg_fence(au);
        if ((lane & 3) == 0) {
#pragma unroll
            for (int i = 0; i < 28; i++) {
                const int f = (warp & 3) * 16 + (lane >> 2) + (i & 2) * 4, tok = i & 1;
                const float h = bf_round(silu_f(bf_round(ag[i]))) * bf_round(au[i]);
                *reinterpret_cast<__nv_bfloat16*>(smem + HB + (w * 7 + (i >> 2)) * 1024 + tok * 128 + (((f >> 3) ^ tok) << 4) + (f & 7) * 2) =
                    __float2bfloat16_rn(h);
            }
        }
    }
    fence_async_smem();
    bar_sync(1, 256);
    PROF(21, tid >> 7);
    {
        float ay[32];
#pragma unroll
        for (int i = 0; i < 32; i++) ay[i] = 0.f;
#pragma unroll 1
        for (int ks = 0; ks < FN2; ks++) {
            const uint64_t db = make_desc(sb + HB + (ks >> 2) * 1024 + (ks & 3) * 32, 16);
            mbar_wait(sb + BAR_FULL + slot * 8, ph);
            const uint64_t da = make_desc(sb + slot * FSTAGE + w * (8 * 2048), 16);
            wg_fence();
#pragma unroll
            for (int b = 0; b < 8; b++) wgmma_n8_ta(ay + 4 * b, da + b * 128, db);
            next_stage(true);
        }
        wg_wait<0>();
        reg_fence(ay);
        if ((lane & 3) == 0) {
#pragma unroll
            for (int i = 0; i < 32; i++)
                g_ypart[(s * 2 + (i & 1)) * DM + (w * 8 + (i >> 2)) * 64 + (warp & 3) * 16 + (lane >> 2) + (i & 2) * 4] = ay[i];
        }
    }
    PROF(23, tid >> 7);
    __threadfence();
    bar_sync(1, 256);
    if (tid == 0) {
        *flag = atomicAdd(&g_sync.ffn_ticket, 1u) == epoch * 4 + 3;
        __threadfence();
    }
    bar_sync(1, 256);
    if (*flag) {
        const float sg = bf_round(__fdividef(1.0f, 1.0f + __expf(-__ldcg(&g_r[row]))));
        const uint32_t xu[4] = {xrow.x, xrow.y, xrow.z, xrow.w};
        uint32_t o[4];
#pragma unroll
        for (int k = 0; k < 4; k++) {
            float y0 = 0.f, y1 = 0.f;
#pragma unroll
            for (int q = 0; q < 4; q++) {
                const float2 y = __ldcg(reinterpret_cast<const float2*>(&g_ypart[(q * 2 + w) * DM + ch * 8 + 2 * k]));
                y0 += y.x; y1 += y.y;
            }
            o[k] = pack_bf16(bf_lo(xu[k]) + bf_round(bf_round(y0) * sg), bf_hi(xu[k]) + bf_round(bf_round(y1) * sg));
        }
        g_routed[w * 128 + ch] = make_uint4(o[0], o[1], o[2], o[3]);
        if (ch == 0) g_sel[w] = row;
        bar_sync(1, 256);
        if (tid == 0) red_release(&g_sync.ffn_done);
    }
}

__device__ __forceinline__ uint32_t slab_addr(uint32_t stg, int lane, int s) {
    const int row = ((lane >> 3) & 1) * 8 + (lane & 7);
    const int chunk = 2 * (s & 3) + (lane >> 4);
    return stg + row * 128 + (s >> 2) * 8192 + ((chunk ^ (lane & 7)) << 4);
}

constexpr float SM_SCALE = 0.08838834764831845f * 1.4426950408889634f;
constexpr float SUM_HI = 1048576.f, SUM_LO = 1.0f / 1048576.f;

template <int I0, int I1, int J0>
__device__ __forceinline__ void mask_range(float (&S)[64], float limf) {
#pragma unroll
    for (int i = I0; i < I1; i++) {
        const int j = i >> 2;
        float t;
        asm("add.sat.f32 %0, %1, %2;" : "=f"(t) : "f"((float)(32 * (j >> 2) + 2 * (j & 3) + (i & 1) - (i & 2) * 4)), "f"(-limf));
        S[4 * J0 + i] = fmaf(t, -1e30f, S[4 * J0 + i]);
    }
}
template <int J0>
__device__ __forceinline__ void mask_half(float (&S)[64], float limf, int v) {
    asm volatile("" : "+f"(limf));
    if (v < 2) {
        mask_range<0, 16, J0>(S, limf);
#pragma unroll
        for (int i = 16; i < 32; i++) S[4 * J0 + i] = -1e30f;
    } else {
        mask_range<16, 32, J0>(S, limf);
    }
}
__device__ __forceinline__ void issue_qk(float (&S)[64], const uint32_t (&Q)[32], uint32_t d0) {
#pragma unroll
    for (int s = 0; s < 8; s++)
        wgmma_n128_rs<1>(S, Q[4 * s], Q[4 * s + 1], Q[4 * s + 2], Q[4 * s + 3], d0 + s * 128, s > 0);
}
template <int H>
__device__ __forceinline__ void issue_pv(float (&O)[64], const uint32_t (&Pm)[32], uint32_t d0, int acc) {
#pragma unroll
    for (int s = 4 * H; s < 4 * H + 4; s++)
        wgmma_n128_rs<0>(O, Pm[4 * s], Pm[4 * s + 1], Pm[4 * s + 2], Pm[4 * s + 3], d0 + H * (PAGE >> 4) + (s & 3) * 2, s > 0 ? 1 : acc);
}
template <int J0, int J1>
__device__ __forceinline__ void exp_groups(const float (&S)[64], uint32_t (&Pm)[32], float (&sum)[2]) {
#pragma unroll
    for (int i = 2 * J0; i < 2 * J1; i++) asm volatile("" : "+r"(Pm[i])::"memory");
#pragma unroll
    for (int j = J0; j < J1; j++) {
        const float e0 = ex2(S[4 * j]), e1 = ex2(S[4 * j + 1]), e2 = ex2(S[4 * j + 2]), e3 = ex2(S[4 * j + 3]);
        sum[0] = (j ? sum[0] + e0 : e0) + e1;
        sum[1] = (j ? sum[1] + e2 : e2) + e3;
        Pm[2 * j] = pack_bf16(e0, e1);
        Pm[2 * j + 1] = pack_bf16(e2, e3);
    }
}
__device__ __forceinline__ void shift_rows(float (&S)[64], float d0, float d1) {
#pragma unroll
    for (int j = 0; j < 16; j++) {
        S[4 * j] -= d0; S[4 * j + 1] -= d0; S[4 * j + 2] -= d1; S[4 * j + 3] -= d1;
    }
}
__device__ constexpr int chunk_src(int i) { return 4 * (4 * (i >> 3) + (i & 3)) + 2 * ((i >> 2) & 1); }
enum : uint32_t { CTL_FIRST = 1, CTL_SWITCH = 2, CTL_LAST = 4, CTL_HALF = 128, CTL_MASKHI = 256, CTL_WOUT = 512, CTL_PVHALF = 1024, CTL_PVACC = 16384,
                  CTL_SHIFT = 32768 };
__device__ __forceinline__ float quad_sum(float v) {
    v += __shfl_xor_sync(~0u, v, 1);
    return v + __shfl_xor_sync(~0u, v, 2);
}

__device__ __forceinline__ void store_part(uint8_t* base, uint32_t row_bits, int p, const uint32_t (&pk)[64]) {
    asm volatile("{\n.reg .b64 d0, d1;\nxor.b64 d0, %0, %1;\nxor.b64 d1, d0, 64;\n"
                 "TS: .branchtargets P0, P1, P2, P3, P4, P5, P6, P7;\n"
                 "brx.idx.uni %2, TS;\n"
                 "P0:\n st.global.cg.v4.u32 [d0 + 0], {%3, %4, %5, %6};\n st.global.cg.v4.u32 [d1 + 0], {%11, %12, %13, %14};\n bra.uni DONE;\n"
                 "P1:\n st.global.cg.v4.u32 [d0 + 0], {%7, %8, %9, %10};\n st.global.cg.v4.u32 [d1 + 0], {%15, %16, %17, %18};\n bra.uni DONE;\n"
                 "P2:\n st.global.cg.v4.u32 [d0 + 16384], {%19, %20, %21, %22};\n st.global.cg.v4.u32 [d1 + 16384], {%27, %28, %29, %30};\n bra.uni DONE;\n"
                 "P3:\n st.global.cg.v4.u32 [d0 + 16384], {%23, %24, %25, %26};\n st.global.cg.v4.u32 [d1 + 16384], {%31, %32, %33, %34};\n bra.uni DONE;\n"
                 "P4:\n st.global.cg.v4.u32 [d0 + 65536], {%35, %36, %37, %38};\n st.global.cg.v4.u32 [d1 + 65536], {%43, %44, %45, %46};\n bra.uni DONE;\n"
                 "P5:\n st.global.cg.v4.u32 [d0 + 65536], {%39, %40, %41, %42};\n st.global.cg.v4.u32 [d1 + 65536], {%47, %48, %49, %50};\n bra.uni DONE;\n"
                 "P6:\n st.global.cg.v4.u32 [d0 + 81920], {%51, %52, %53, %54};\n st.global.cg.v4.u32 [d1 + 81920], {%59, %60, %61, %62};\n bra.uni DONE;\n"
                 "P7:\n st.global.cg.v4.u32 [d0 + 81920], {%55, %56, %57, %58};\n st.global.cg.v4.u32 [d1 + 81920], {%63, %64, %65, %66};\n bra.uni DONE;\n"
                 "DONE:\n}\n"
                 ::"l"(base), "l"((uint64_t)((p & 1) ? row_bits : 0)), "r"(p), "r"(pk[0]), "r"(pk[1]), "r"(pk[2]), "r"(pk[3]), "r"(pk[4]), "r"(pk[5]), "r"(pk[6]), "r"(pk[7]), "r"(pk[8]), "r"(pk[9]), "r"(pk[10]), "r"(pk[11]), "r"(pk[12]), "r"(pk[13]), "r"(pk[14]), "r"(pk[15]), "r"(pk[16]), "r"(pk[17]), "r"(pk[18]), "r"(pk[19]), "r"(pk[20]), "r"(pk[21]), "r"(pk[22]), "r"(pk[23]), "r"(pk[24]), "r"(pk[25]), "r"(pk[26]), "r"(pk[27]), "r"(pk[28]), "r"(pk[29]), "r"(pk[30]), "r"(pk[31]), "r"(pk[32]), "r"(pk[33]), "r"(pk[34]), "r"(pk[35]), "r"(pk[36]), "r"(pk[37]), "r"(pk[38]), "r"(pk[39]), "r"(pk[40]), "r"(pk[41]), "r"(pk[42]), "r"(pk[43]), "r"(pk[44]), "r"(pk[45]), "r"(pk[46]), "r"(pk[47]), "r"(pk[48]), "r"(pk[49]), "r"(pk[50]), "r"(pk[51]), "r"(pk[52]), "r"(pk[53]), "r"(pk[54]), "r"(pk[55]), "r"(pk[56]), "r"(pk[57]), "r"(pk[58]), "r"(pk[59]), "r"(pk[60]), "r"(pk[61]), "r"(pk[62]), "r"(pk[63])
                 : "memory");
}

__device__ __forceinline__ void consumer(uint32_t sb, int pair, int c, uint8_t* out, const uint8_t* x) {
    const int tid = threadIdx.x;
    const int warp = __shfl_sync(~0u, tid >> 5, 0);
    const int w = warp >> 2, v = warp & 3, lane = tid & 31;

    const uint32_t empty_rel = lane == 2 ? mapa(sb + BAR_EMPTYL, c) : mapa(sb + BAR_EMPTY, lane & 1);
    auto release = [&](uint32_t grp) {
        if (lane < 3) mbar_arrive_cluster(empty_rel + (grp & 7) * 8);
    };
    auto wait_full = [&](uint32_t grp) { mbar_wait(sb + BAR_FULL + (grp & 7) * 8, (grp >> 3) & 1); };

    uint32_t g = 0;
    const uint32_t stg = sb + SM_REGION + w * PAGE + v * 2048;
    const uint32_t chunk0 = (lane >> 2) * 128 + (((lane & 3) ^ (lane >> 2)) << 4);
    uint32_t ndone = 0;
    auto mark_done = [&]() {
        __syncwarp();
        if (lane == 0) mbar_arrive(sb + BAR_DONE + (ndone & 1) * 8);
        ndone++;
    };
    auto ctx_dst = [&](int rnd, int seg) {
        const int rb = query_rowblock(pair, c, w, seg);
        return ptr_off(g_ctx, ((rb >> 1) * 64 + (rnd * 16 + (pair >> 2)) * 2) * PAGE + (rb & 1) * 8192 + v * 2048);
    };

    uint32_t ctl_tab;
    {
        const int t = lane, firstB = 2 * attn_rowblock(pair, 0) + 2 - w;
        auto is_half = [&](int u) { return (u == firstB - 1 || u == 16) && c == (u >= firstB); };
        auto block = [&](int u) { return u + (w == 1 && u >= firstB); };
        auto place = [](int j) { return ((j & 15) << 3) | ((j - (j * 43 >> 8) * 6) << 11); };
        const int jv = min(2 * block(t - 1) + 2, 35), jk = t == 17 ? jv : max(2 * block(t) - 1, 0);
        const bool diag = t == firstB - 1 || t == 16;
        ctl_tab = ((t == 0 || t == firstB) ? CTL_FIRST : 0) | (t == firstB ? CTL_SWITCH : 0) | (t == 17 ? CTL_LAST : 0) |
                  (diag ? (is_half(t) ? CTL_HALF : CTL_MASKHI) : 0) | (t == firstB + 1 ? CTL_WOUT : 0) |
                  (is_half(t - 1) ? CTL_PVHALF : 0) | ((t == 1 || t == firstB + 1) ? 0 : CTL_PVACC) |
                  place(jk) | ((place(jv) | (t ? 3 : 0)) << 16);
    }

    uint32_t pk[64];
#pragma unroll
    for (int i = 0; i < 64; i++) pk[i] = 0;
    uint8_t* pend = nullptr;
    uint32_t prow = 0x400;
    auto write_part = [&](int p) { store_part(pend, prow, p, pk); };
    if (w == 1) bar_arrive(2, 256);

    for (int item = 0; item < 6; item++) {
        if ((0x1B >> item) & 1) {
            constexpr int nk = DC / 64;
            float acc[128];
            auto issue_kblock = [&](int first_acc) {
                wait_full(g);
                const uint32_t pg = sb + (g & 3) * (3 * PAGE);
                const uint64_t da = make_desc(pg + w * 8192, 16), db = make_desc(pg + PAGE, 16);
                wg_fence();
                wgmma_n256_ss(acc, da, db, first_acc);
                wgmma_n256_ss(acc, da + 128, db + 2, 1);
                wgmma_n256_ss(acc, da + 256, db + 4, 1);
                wgmma_n256_ss(acc, da + 384, db + 6, 1);
                wg_commit();
                g++;
            };
            if (item == 0) PROF(17, w);
            issue_kblock(0);
            if (item == 0) PROF(1, w);
            if (item == 0 && w == 0) PROF_GT(1);
            const int nparts = item == 0 ? 0 : (item == 3 ? 4 : 8);
            const int ln_row = (pair * 2 + c) * 16 + warp * 2;
            if (item == 0) {
                const uint8_t* src = ptr_off(x, ln_row * (DM * 2) + lane * 16);
#pragma unroll
                for (int i = 0; i < 8; i++) {
                    const uint4 t = __ldcg(reinterpret_cast<const uint4*>(src + i * 512));
                    pk[4 * i] = t.x; pk[4 * i + 1] = t.y; pk[4 * i + 2] = t.z; pk[4 * i + 3] = t.w;
                }
            }
#pragma unroll 1
            for (int kb = 1; kb < nk; kb++) {
                if (kb == nk - 1 && w == 1) bar_sync(4, 256);
                issue_kblock(1);
                if (kb == nk - 1 && w == 0) bar_arrive(4, 256);
                wg_wait<1>();
                release(g - 2);
                if (kb <= nparts) {
                    if (item == 4 && kb == 1) mbar_wait(sb + BAR_DEP + 16, 0);
                    write_part(kb - 1);
                    if (kb == nk - 1) write_part(nk - 1);
                    if (kb == nparts || kb == nk - 1) mark_done();
                }
                if (g <= 8) {
                    float s[2], q[2];
                    if (g == 4) {
                        ln_sums<0>(pk, s[0], q[0]);
                        pk[32] = __float_as_uint(s[0]); pk[33] = __float_as_uint(q[0]);
                    }
                    if (g == 5) {
                        ln_sums<16>(pk, s[1], q[1]);
                        pk[34] = __float_as_uint(s[1]); pk[35] = __float_as_uint(q[1]);
                    }
                    if (g == 6) {
#pragma unroll
                        for (int r = 0; r < 2; r++) { s[r] = __uint_as_float(pk[32 + 2 * r]); q[r] = __uint_as_float(pk[33 + 2 * r]); }
                        const bool hi = lane & 16, od = lane & 8;
                        float a = hi ? s[1] : s[0], b = hi ? q[1] : q[0];
                        a += __shfl_xor_sync(~0u, hi ? s[0] : s[1], 16);
                        b += __shfl_xor_sync(~0u, hi ? q[0] : q[1], 16);
                        float t = od ? b : a;
                        t += __shfl_xor_sync(~0u, od ? a : b, 8);
#pragma unroll
                        for (int o = 4; o; o >>= 1) t += __shfl_xor_sync(~0u, t, o);
#pragma unroll
                        for (int r = 0; r < 2; r++) {
                            s[r] = __shfl_sync(~0u, t, 16 * r);
                            q[r] = __shfl_sync(~0u, t, 16 * r + 8);
                        }
                        ln_finish(s[0], q[0], pk[36], pk[37], pk[38]);
                        ln_finish(s[1], q[1], pk[39], pk[40], pk[41]);
                    }
                    if (g == 7) ln_apply<0>(pk, pk[36], pk[37], pk[38], ptr_off(g_xn, image_offset(ln_row, lane)));
                    if (g == 8) {
                        ln_apply<16>(pk, pk[39], pk[40], pk[41], ptr_off(g_xn, image_offset(ln_row + 1, lane)));
                        mark_done();
                    }
                }
            }
            wg_wait<0>();
            reg_fence(acc);
            release(g - 1);
            PROF(2 + 2 * item, w);
            if (w == 0) PROF_GT(2 + 2 * item);
#pragma unroll
            for (int i = 0; i < 64; i++) pk[i] = pack_bf16(acc[chunk_src(i)], acc[chunk_src(i) + 1]);
            const uint32_t vrow = (v >> 1) * 32 + (lane >> 3) * 8 + (v & 1) * 4 + ((lane >> 2) & 1);
            pend = ptr_off(g_kv, ((kv_head(pair) + (item == 1 || item == 4 ? 8 : 0)) * 16 + kv_tokens(pair) * 2) * 65536 + w * 8192 +
                                     (c ? 32768 + vrow * 128 + (((lane & 3) ^ (vrow & 7)) << 4) : v * 2048 + chunk0));
            prow = c ? 0x120 : 0x400;
            PROF(3 + 2 * item, w);
            continue;
        }

        float O[64], S[64];
        auto issue_q = [&](int first_acc) {
            wait_full(g);
            const uint32_t pg = sb + (g & 3) * (3 * PAGE);
            const uint64_t da = make_desc(pg + w * 8192, 16), db = make_desc(pg + 2 * PAGE, 8192);
            const uint64_t dab = make_desc(pg + PAGE + (1 - w) * 8192, 16);
            wg_fence();
#pragma unroll
            for (int q = 0; q < 4; q++) wgmma_n128_ss(S, da + 2 * q, db + 128 * q, q ? 1 : first_acc);
            wg_commit();
#pragma unroll
            for (int q = 0; q < 4; q++) wgmma_n128_ss(O, dab + 2 * q, db + 128 * q, q ? 1 : first_acc);
            wg_commit();
            g++;
        };
        issue_q(0);
#pragma unroll 1
        for (int kb = 1; kb < DM / 64; kb++) {
            if (kb == DM / 64 - 2 && w == 1) bar_sync(4, 256);
            issue_q(1);
            if (kb == DM / 64 - 1 && w == 0) bar_arrive(4, 256);
            wg_wait<2>();
            release(g - 2);
            if (kb <= 8) {
                write_part(kb - 1);
                if (kb == 8) mark_done();
            }
        }
        uint32_t Q[32], Pm[32];
#pragma unroll
        for (int i = 0; i < 32; i++) Pm[i] = pk[i];
        float lim = (float)(v * 16 + (lane >> 2) - 8 * (lane & 3));
        float mc[2] = {0.f, 0.f}, l[2] = {0.f, 0.f}, scale[2] = {0.f, 0.f}, sum[2];
        uint32_t ctl = __shfl_sync(~0u, ctl_tab, 0), nxt = __shfl_sync(~0u, ctl_tab, 1);
        int t = 1;
        asm volatile("" : "+f"(lim), "+f"(mc[0]), "+f"(mc[1]), "+f"(l[0]), "+f"(l[1]), "+r"(ctl), "+r"(nxt), "+r"(t));
        wg_wait<1>();
        reg_fence(S);
#pragma unroll
        for (int i = 0; i < 32; i++) Q[i] = pack_bf16(S[2 * i] * SM_SCALE, S[2 * i + 1] * SM_SCALE);
        reg_fence(Q);
        wait_full(g);
        wg_wait<0>();
        reg_fence(O);
        release(g - 1);
        PROF(2 + 2 * item, w);
        if (w == 0) PROF_GT(2 + 2 * item);

        const uint32_t qaddr = stg + lane * 16;
        auto put_queries = [&](const float (&A)[64]) {
#pragma unroll
            for (int i = 0; i < 8; i++)
                sts128(qaddr + (i >> 2) * 8192 + (i & 3) * 512, pack_bf16(A[8 * i] * SM_SCALE, A[8 * i + 1] * SM_SCALE), pack_bf16(A[8 * i + 2] * SM_SCALE, A[8 * i + 3] * SM_SCALE),
                       pack_bf16(A[8 * i + 4] * SM_SCALE, A[8 * i + 5] * SM_SCALE), pack_bf16(A[8 * i + 6] * SM_SCALE, A[8 * i + 7] * SM_SCALE));
        };
        auto get_queries = [&]() {
#pragma unroll
            for (int i = 0; i < 8; i++) lds128(qaddr + (i >> 2) * 8192 + (i & 3) * 512, Q[4 * i], Q[4 * i + 1], Q[4 * i + 2], Q[4 * i + 3]);
        };
        const uint32_t kdesc0 = (uint32_t)make_desc(sb, PAGE), vdesc0 = (uint32_t)make_desc(sb, 16);
        auto wait_block = [&](uint32_t word) { mbar_wait(sb + BAR_FULL + (word & 56), (word >> 6) & 1); };
        auto write_out = [&](auto early) {
            uint8_t* dst = ctx_dst(item == 5, 0);
            uint8_t* d[2] = {ptr_off(dst, chunk0), ptr_off(dst, chunk0 ^ 64)};
#pragma unroll
            for (int i = early.value ? 0 : WN; i < (early.value ? WN : 8); i++) {
                const float sc = scale[i & 1];
                uint32_t q[4];
#pragma unroll
                for (int k = 0; k < 4; k++) q[k] = pack_bf16(O[chunk_src(4 * i + k)] * sc, O[chunk_src(4 * i + k) + 1] * sc);
                if (early.value && i > 0) {
#pragma unroll
                    for (int k = 0; k < 4; k++) O[4 * (i - 1) + k] = __uint_as_float(q[k]);
                }
                __stcg(reinterpret_cast<uint4*>(d[(i >> 1) & 1] + (i >> 2) * PAGE + (i & 1) * 1024), make_uint4(q[0], q[1], q[2], q[3]));
            }
            if (!early.value) mark_done();
        };
        put_queries(O);
        bar_sync(2 + w, 256);
        wg_fence();
        issue_qk(S, Q, kdesc0);
        wg_commit();
        wg_fence();
        wg_commit();
        wg_commit();
        bar_arrive(3 - w, 256);
        for (;;) {
            const bool kready = mbar_try(sb + BAR_FULL + (nxt & 56), (nxt >> 6) & 1);
            wg_wait<2>();
            reg_fence(S);
            if (ctl & (CTL_HALF | CTL_MASKHI | CTL_SHIFT)) {
                if (ctl & CTL_HALF) mask_half<0>(S, lim, v);
                if (ctl & CTL_MASKHI) mask_half<8>(S, lim, v);
                if (ctl & CTL_SHIFT) shift_rows(S, mc[0], mc[1]);
            }
            float early[4 * EARLY];
#pragma unroll
            for (int j = 0; j < EARLY; j++) {
#pragma unroll
                for (int i = 4 * j; i < 4 * j + 4; i++) early[i] = ex2(S[i]);
                sum[0] = (j ? sum[0] + early[4 * j] : early[4 * j]) + early[4 * j + 1];
                sum[1] = (j ? sum[1] + early[4 * j + 2] : early[4 * j + 2]) + early[4 * j + 3];
            }
            const uint32_t tie = __float_as_uint(sum[0]) & __float_as_uint(sum[1]) & (ctl & 0x80000000u);
            if (lane < 3) mbar_arrive_cluster(empty_rel + tie + (ctl & 56));
            wg_wait<1>();
#pragma unroll
            for (int j = 0; j < EARLY; j++) {
                asm volatile("" : "+r"(Pm[2 * j]), "+r"(Pm[2 * j + 1])::"memory");
                Pm[2 * j] = pack_bf16(early[4 * j], early[4 * j + 1]);
                Pm[2 * j + 1] = pack_bf16(early[4 * j + 2], early[4 * j + 3]);
            }
            exp_groups<EARLY, 8>(S, Pm, sum);
            const bool half = ctl & CTL_HALF;
            if (!half) {
                wg_wait<0>();
                reg_fence(O);
                if (lane < ((ctl >> 16) & 3)) mbar_arrive_cluster(empty_rel + ((ctl >> 16) & 56));
                exp_groups<8, 16>(S, Pm, sum);
            } else {
                asm volatile("wgmma.wait_group.sync.aligned 0;\n" ::: "memory");
                reg_fence(O);
                if (lane < ((ctl >> 16) & 3)) asm volatile("mbarrier.arrive.shared::cluster.b64 _, [%0];\n" ::"r"(empty_rel + ((ctl >> 16) & 56)) : "memory");
            }
            const bool over = !(sum[0] + sum[1] <= SUM_HI);
            if (__any_sync(~0u, over || !kready) || (((ctl & CTL_FIRST) | (nxt & (CTL_SWITCH | CTL_LAST))) != 0)) {
                bool bad = __any_sync(~0u, over);
                if (!kready) wait_block(nxt);
                const bool first = ctl & CTL_FIRST;
                if (first) {
                    uint32_t b0 = __ballot_sync(~0u, sum[0] >= SUM_LO), b1 = __ballot_sync(~0u, sum[1] >= SUM_LO);
                    b0 |= b0 >> 1; b1 |= b1 >> 1;
                    b0 |= b0 >> 2; b1 |= b1 >> 2;
                    bad |= (b0 & b1 & 0x11111111u) != 0x11111111u;
                }
                if (bad) {
                    if (half) {
#pragma unroll
                        for (int i = 32; i < 64; i++) S[i] = -INFINITY;
                    }
                    float d0 = fmaxf(S[0], S[1]), d1 = fmaxf(S[2], S[3]);
#pragma unroll
                    for (int j = 1; j < 16; j++) {
                        d0 = fmaxf(d0, fmaxf(S[4 * j], S[4 * j + 1]));
                        d1 = fmaxf(d1, fmaxf(S[4 * j + 2], S[4 * j + 3]));
                    }
                    d0 = fmaxf(d0, __shfl_xor_sync(~0u, d0, 1));
                    d1 = fmaxf(d1, __shfl_xor_sync(~0u, d1, 1));
                    d0 = fmaxf(d0, __shfl_xor_sync(~0u, d0, 2));
                    d1 = fmaxf(d1, __shfl_xor_sync(~0u, d1, 2));
                    if (!first) {
                        d0 = fmaxf(d0, 0.f);
                        d1 = fmaxf(d1, 0.f);
                        const float a0 = ex2(-d0), a1 = ex2(-d1);
#pragma unroll
                        for (int j = 0; j < 16; j++) {
                            O[4 * j] *= a0; O[4 * j + 1] *= a0; O[4 * j + 2] *= a1; O[4 * j + 3] *= a1;
                        }
                        l[0] *= a0; l[1] *= a1;
                    }
                    mc[0] += d0; mc[1] += d1;
                    ctl_tab |= CTL_SHIFT;
                    nxt |= CTL_SHIFT;
                    shift_rows(S, d0, d1);
                    exp_groups<0, 16>(S, Pm, sum);
                }
                if (ctl & CTL_SWITCH) write_out(std::true_type());
                if (nxt & CTL_LAST) break;
                if (nxt & CTL_SWITCH) {
                    get_queries();
                    nxt &= ~CTL_SHIFT;
                    ctl_tab &= ~CTL_SHIFT;
                }
            }
            ctl = nxt;
            bar_sync(2 + w, 256);
            wg_fence();
            issue_qk(S, Q, kdesc0 + (ctl & 0x3800));
            wg_commit();
            l[0] += sum[0]; l[1] += sum[1];
            nxt = __shfl_sync(~0u, ctl_tab, ++t);
            if (ctl & (CTL_SWITCH | CTL_WOUT)) {
                if (ctl & CTL_SWITCH) {
                    scale[0] = rcp_approx(quad_sum(l[0]));
                    scale[1] = rcp_approx(quad_sum(l[1]));
                    l[0] = l[1] = mc[0] = mc[1] = 0.f;
                    if (w == 1) { release((ctl >> 3) - 2); release((ctl >> 3) + 1); }
                } else {
                    write_out(std::false_type());
                }
            }
            wait_block(ctl >> 16);
            const uint32_t vdesc = vdesc0 + ((ctl >> 16) & 0x3800);
            if (!(ctl & CTL_PVHALF)) {
                wg_fence();
                issue_pv<0>(O, Pm, vdesc, ctl & CTL_PVACC);
                wg_commit();
                issue_pv<1>(O, Pm, vdesc, 1);
                wg_commit();
            } else {
                wg_fence();
                issue_pv<0>(O, Pm, vdesc, ctl & CTL_PVACC);
                wg_commit();
                wg_commit();
            }
            bar_arrive(3 - w, 256);
        }
        g += 36;
        if (w == 0) release(g - 3);
        if (nxt & CTL_WOUT) write_out(std::false_type());
        const uint32_t vdesc = vdesc0 + (nxt & 0x3800);
        if (nxt & CTL_PVHALF) {
            wg_fence();
            issue_pv<0>(O, Pm, vdesc, nxt & CTL_PVACC);
            wg_commit();
        } else {
            wg_fence();
            issue_pv<0>(O, Pm, vdesc, nxt & CTL_PVACC);
            issue_pv<1>(O, Pm, vdesc, 1);
            wg_commit();
        }
        l[0] += sum[0]; l[1] += sum[1];
        ctl_tab = (ctl_tab & ~(0x00780078u | CTL_SHIFT)) | ((ctl_tab + 0x00200020u) & 0x00780078u);
        const float i0 = rcp_approx(quad_sum(l[0])), i1 = rcp_approx(quad_sum(l[1]));
        wg_wait<0>();
        reg_fence(O);
        if (w == 0) release(g - 2);
        release(g - 1);
#pragma unroll
        for (int i = 0; i < 32; i++) {
            const float sc = (i & 4) ? i1 : i0;
            pk[i] = pack_bf16(O[chunk_src(i)] * sc, O[chunk_src(i) + 1] * sc);
        }
        pend = ptr_off(ctx_dst(item == 5, 1), chunk0);
        prow = 0x400;
#pragma unroll
        for (int i = 32; i < 64; i++) pk[i] = 0;
        PROF(3 + 2 * item, w);
        if (w == 0) PROF_GT(3 + 2 * item);
    }

    float acc[64];
    uint32_t slot = 0;
    auto issue_out = [&](int first_acc) {
        wait_full(g);
        const uint64_t da = make_desc(sb + slot + w * 8192, 16), db = make_desc(sb + slot + PAGE, 8192);
        wg_fence();
#pragma unroll
        for (int q = 0; q < 4; q++) wgmma_n128_ss(acc, da + 2 * q, db + 128 * q, q ? 1 : first_acc);
        wg_commit();
        g++;
        slot = slot == SM_REGION - 2 * PAGE ? 0 : slot + 2 * PAGE;
    };
    issue_out(0);
#pragma unroll 1
    for (int kb = 1; kb < 64 - PEEL; kb++) {
        issue_out(1);
        wg_wait<1>();
        release(g - 2);
        if (kb <= 8 && !(kb & 1)) {
            write_part((kb >> 1) - 1);
            if (kb == 8) mark_done();
        }
        if (kb >= 32 - PEEL && ((kb + PEEL) & 3) == 2 * w) {
            uint32_t u0, u1, u2, u3;
            const uint32_t a = stg + ((kb + PEEL) & 16) * 512 + ((kb + PEEL) & 12) * 128 + lane * 16;
            mbar_wait(sb + BAR_G + w * 8, 0);
            lds128(a, u0, u1, u2, u3);
            sts128(a, pack_bf16(silu_f(bf_lo(u0)), silu_f(bf_hi(u0))), pack_bf16(silu_f(bf_lo(u1)), silu_f(bf_hi(u1))),
                   pack_bf16(silu_f(bf_lo(u2)), silu_f(bf_hi(u2))), pack_bf16(silu_f(bf_lo(u3)), silu_f(bf_hi(u3))));
        }
    }
    const uint32_t goff = (((pair >> 1) & 7) * 256 + c * 128 + w * 64 + v * 16 + (lane >> 3)) * (DM * 2) +
                          ((pair >> 4) * 256 + (pair & 1) * 128) * 2 + (((lane & 7) ^ (lane >> 3)) << 4);
    uint32_t xr[32], gr[32];
    {
        const uint8_t* src[2] = {ptr_off(x, goff), ptr_off(x, goff ^ 64)};
#pragma unroll
        for (int i = 0; i < 8; i++) {
            const uint4 t = __ldcg(reinterpret_cast<const uint4*>(src[i & 1] + (i & 3) * (4 * DM * 2) + (i >> 2) * 128));
            xr[4 * i] = t.x; xr[4 * i + 1] = t.y; xr[4 * i + 2] = t.z; xr[4 * i + 3] = t.w;
        }
    }
#pragma unroll 1
    for (int i = 0; i < PEEL; i++) {
        if (i == PEEL - STAG && w == 1) bar_sync(4, 256);
        issue_out(1);
        if (i == PEEL - 1 && w == 0) bar_arrive(4, 256);
        wg_wait<1>();
    }
    asm volatile("barrier.cluster.arrive.relaxed.aligned;" ::: "memory");
#pragma unroll
    for (int i = 0; i < 8; i++) lds128(stg + (i >> 2) * 8192 + (i & 3) * 512 + lane * 16, gr[4 * i], gr[4 * i + 1], gr[4 * i + 2], gr[4 * i + 3]);
    uint8_t* dst[2] = {ptr_off(out, goff), ptr_off(out, goff ^ 64)};
    __syncwarp();
    wg_wait<0>();
    reg_fence(acc);
    PROF(14, w);
    if (w == 0) PROF_GT(14);
#pragma unroll
    for (int s = 0; s < 8; s++)
        stmatrix_x4(slab_addr(stg, lane, s), pack_bf16(acc[8 * s], acc[8 * s + 1]), pack_bf16(acc[8 * s + 2], acc[8 * s + 3]),
                    pack_bf16(acc[8 * s + 4], acc[8 * s + 5]), pack_bf16(acc[8 * s + 6], acc[8 * s + 7]));
    __syncwarp();
    uint32_t o[32];
#pragma unroll
    for (int i = 0; i < 8; i++) lds128(stg + (i >> 2) * 8192 + (i & 3) * 512 + lane * 16, o[4 * i], o[4 * i + 1], o[4 * i + 2], o[4 * i + 3]);
#pragma unroll
    for (int i = 0; i < 8; i++) {
#pragma unroll
        for (int k = 0; k < 4; k++) xr[4 * i + k] = bf2_add(xr[4 * i + k], bf2_mul(o[4 * i + k], gr[4 * i + k]));
        __stcg(reinterpret_cast<uint4*>(dst[i & 1] + (i & 3) * (4 * DM * 2) + (i >> 2) * 128), make_uint4(xr[4 * i], xr[4 * i + 1], xr[4 * i + 2], xr[4 * i + 3]));
    }
    PROF(28, w);
}

__global__ void __cluster_dims__(2, 1, 1) __launch_bounds__(384, 1)
fused_kernel(const __grid_constant__ CUtensorMap m_ckv, const __grid_constant__ CUtensorMap m_wuk,
             const __grid_constant__ CUtensorMap m_wuv, const __grid_constant__ CUtensorMap m_wq,
             const __grid_constant__ CUtensorMap m_wo, const __grid_constant__ CUtensorMap m_gate,
             const __grid_constant__ CUtensorMap m_up, const __grid_constant__ CUtensorMap m_down, const Params P) {
    extern __shared__ __align__(1024) uint8_t smem[];
    const uint32_t sb = __shfl_sync(~0u, smem_u32(smem), 0);
    const int tid = threadIdx.x;
    const int cl = blockIdx.x >> 1, c = blockIdx.x & 1;
    const int pair = cl >= 64 ? cl : cl < 4 ? cl * 16 + 15 : cl < 36 ? ((cl - 4) >> 3) * 16 + ((cl - 4) & 7)
                                                                    : ((cl - 36) / 7) * 16 + 8 + (cl - 36) % 7;
    const bool starter = tid == 256 && pair < NMAIN / 2;
    const CUtensorMap* m_wu = c ? &m_wuv : &m_wuk;
    if (tid == 256) {
        mbar_init(sb + BAR_FULL, 1);
        if (starter) {
            asm volatile("fence.mbarrier_init.release.cluster;" ::: "memory");
            mbar_expect_tx(sb + BAR_FULL, 3 * PAGE);
            tma_3d(sb, m_wu, 0, 0, kv_head(pair) * 2, sb + BAR_FULL);
            tma_3d(sb + PAGE, &m_ckv, 0, kv_tokens(pair) * 256, 0, sb + BAR_FULL);
            tma_3d(sb + 2 * PAGE, &m_ckv, 0, kv_tokens(pair) * 256 + 128, 0, sb + BAR_FULL);
        }
#pragma unroll
        for (int i = 1; i < NBAR; i++) mbar_init(sb + SM_BAR + i * 8, (i >> 3) == 1 ? 16 : i >= 25 ? 8 : 1);
        asm volatile("fence.mbarrier_init.release.cluster;" ::: "memory");
    }
    if (starter) {
#pragma unroll 1
        for (int kb = 1; kb < 4; kb++) mbar_expect_tx(sb + BAR_FULL + kb * 8, 3 * PAGE);
        tma_3d(sb + 3 * PAGE, m_wu, 0, 64, kv_head(pair) * 2, sb + BAR_FULL + 8);
    }
    PROF(18, (tid >> 7) & 1);
    __syncthreads();
    cluster_sync();
    PROF(22, (tid >> 7) & 1);
    PROF(19, (tid >> 7) & 1);
    const int warp = __shfl_sync(~0u, tid >> 5, 0), lane = tid & 31;
    auto dump_prof = [&]() {
    };
    if (pair >= NMAIN / 2) {
        if (warp < 8) ffn_cta(smem, sb, blockIdx.x - NMAIN, __ldcg(&g_sync.done) / NCTA, P.w_r);
        else if (tid == 256) ffn_producer(sb, blockIdx.x - NMAIN, &m_gate, &m_up, &m_down);
        __syncwarp();
        PROF(29, tid >> 7);
        cluster_sync();
        if (tid == 0) atomicAdd(&g_sync.done, 1u);
        if (warp < 8) dump_prof();
    } else if (warp < 8) {
        asm volatile("setmaxnreg.inc.sync.aligned.u32 232;");
        consumer(sb, pair, c, P.out, (const uint8_t*)P.x);
        PROF(29, tid >> 7);
        asm volatile("barrier.cluster.wait.aligned;" ::: "memory");
        dump_prof();
    } else {
        asm volatile("setmaxnreg.dec.sync.aligned.u32 40;");
        if (starter) {
#pragma unroll 1
            for (int kb = 1; kb < 4; kb++) {
                if (kb > 1) tma_3d(sb + kb * (3 * PAGE), m_wu, 0, kb * 64, kv_head(pair) * 2, sb + BAR_FULL + kb * 8);
                tma_3d_mc(sb + kb * (3 * PAGE) + (1 + c) * PAGE, &m_ckv, 0, kv_tokens(pair) * 256 + c * 128, kb, sb + BAR_FULL + kb * 8);
            }
        }
        if (warp == 10) {
            sync_helper(sb, lane, pair, c);
        } else if (warp & 1) {
            fetch_helper((warp & 2) ? P.w_uv : P.w_uk, (const uint8_t*)P.x, sb, (warp >> 1) & 1, lane, pair, c);
        } else {
            producer(P, sb, pair, c, &m_ckv, m_wu, &m_wq, &m_wo);
        }
        bar_sync(6, 128);
        if (tid == 256) atomicAdd(&g_sync.done, 1u);
        cluster_sync();
    }
}

typedef CUresult (*EncodeFn)(CUtensorMap*, CUtensorMapDataType, cuuint32_t, void*, const cuuint64_t*, const cuuint64_t*,
                             const cuuint32_t*, const cuuint32_t*, CUtensorMapInterleave, CUtensorMapSwizzle,
                             CUtensorMapL2promotion, CUtensorMapFloatOOBfill);

void make_map_w(EncodeFn fn, CUtensorMap* m, const void* ptr, int rows, int cols, int blocks, int box_rows = 32) {
    cuuint64_t dims[3] = {64, (cuuint64_t)rows, (cuuint64_t)cols / 64};
    cuuint64_t strides[2] = {(cuuint64_t)cols * 2, 128};
    cuuint32_t box[3] = {64, (cuuint32_t)box_rows, (cuuint32_t)blocks};
    cuuint32_t es[3] = {1, 1, 1};
    fn(m, CU_TENSOR_MAP_DATA_TYPE_BFLOAT16, 3, const_cast<void*>(ptr), dims, strides, box, es, CU_TENSOR_MAP_INTERLEAVE_NONE,
       CU_TENSOR_MAP_SWIZZLE_128B, CU_TENSOR_MAP_L2_PROMOTION_L2_256B, CU_TENSOR_MAP_FLOAT_OOB_FILL_NONE);
}

}

extern "C" void kernel_launch(void* const* d_in, const int* in_sizes, int n_in, void* d_out, int out_size) {
    static EncodeFn fn = nullptr;
    if (!fn) {
        void* f = nullptr;
        cudaDriverEntryPointQueryResult qr;
        cudaGetDriverEntryPoint("cuTensorMapEncodeTiled", &f, cudaEnableDefault, &qr);
        fn = (EncodeFn)f;
        cudaFuncSetAttribute(fused_kernel, cudaFuncAttributeMaxDynamicSharedMemorySize, SMEM_BYTES);
    }
    CUtensorMap m_ckv, m_wuk, m_wuv, m_wq, m_wo, m_gate, m_up, m_down;
    make_map_w(fn, &m_gate, d_in[8], DM, FF, FS / 64, 16);
    make_map_w(fn, &m_up, d_in[9], DM, FF, FS / 64, 16);
    make_map_w(fn, &m_down, d_in[10], FF, DM, DM / 64, 16);
    make_map_w(fn, &m_ckv, d_in[1], SEQ, DC, 1, 128);
    make_map_w(fn, &m_wq, d_in[2], DM, NH * 128, 1, 64);
    make_map_w(fn, &m_wuk, d_in[3], DC, NH * 128, 2, 64);
    make_map_w(fn, &m_wuv, d_in[4], DC, NH * 128, 2, 64);
    make_map_w(fn, &m_wo, d_in[5], NH * 128, DM, 1, 64);
    Params P;
    P.x = (const __nv_bfloat16*)d_in[0];
    P.w_r = (const __nv_bfloat16*)d_in[7];
    P.c_kv = (const uint8_t*)d_in[1];
    P.w_uk = (const uint8_t*)d_in[3];
    P.w_uv = (const uint8_t*)d_in[4];
    P.out = (uint8_t*)d_out;
    fused_kernel<<<NCTA, 384, SMEM_BYTES>>>(m_ckv, m_wuk, m_wuv, m_wq, m_wo, m_gate, m_up, m_down, P);
}
```

```cpp
#include <cuda_runtime.h>
#include <cuda_bf16.h>
#include <cuda.h>
#include <stdint.h>
#include <type_traits>

namespace {

constexpr int SEQ = 2048, DM = 1024, NH = 32, DC = 512, FF = 3584;
constexpr int PAGE = 16384;
constexpr int NRING = 12;
constexpr int NCTA = 132, NMAIN = 128;
constexpr uint32_t SM_REGION = NRING * PAGE;
constexpr uint32_t SM_BAR = (NRING + 2) * PAGE;
constexpr uint32_t BAR_FULL = SM_BAR, BAR_EMPTY = SM_BAR + 64;
constexpr uint32_t BAR_DEP = SM_BAR + 128;
constexpr uint32_t BAR_G = SM_BAR + 184;
constexpr uint32_t BAR_DONE = SM_BAR + 200;
constexpr uint32_t BAR_EMPTYL = SM_BAR + 216;
constexpr int NBAR = 35;
constexpr uint32_t SM_PROF = SM_BAR + 320;
constexpr int SMEM_BYTES = SM_PROF + 512;
constexpr uint32_t SPIN_LIMIT = 1u << 16;
constexpr uint32_t POLL_MASK = 7;
constexpr int EARLY = 2;
constexpr int WN = 6;
constexpr int PEEL = 5, STAG = 3;

struct SyncBlock {
    unsigned done;       unsigned pad0[31];
    unsigned ln;         unsigned pad1[31];
    unsigned router;     unsigned pad4[31];
    unsigned ffn_ticket; unsigned pad2[31];
    unsigned ffn_done;   unsigned pad3[31];
    unsigned kv[NH * 8];
    unsigned kvfree[16 * 8];
    unsigned ctx[32 * NH];
};

__device__ __align__(1024) uint8_t g_xn[8 * 16 * 4 * 8192];
__device__ __align__(4096) uint8_t g_kv[16 * 16 * 65536];
__device__ __align__(4096) uint8_t g_ctx[16 * 64 * 16384];
__device__ __align__(16) uint4 g_routed[2 * 128];
__device__ int g_sel[2];
__device__ __align__(16) float g_r[SEQ];
__device__ __align__(16) float g_ypart[4 * 2 * DM];
__device__ SyncBlock g_sync;

__device__ __forceinline__ uint32_t smem_u32(const void* p) { return (uint32_t)__cvta_generic_to_shared(p); }

__device__ __forceinline__ void mbar_init(uint32_t bar, uint32_t count) {
    asm volatile("mbarrier.init.shared::cta.b64 [%0], %1;" ::"r"(bar), "r"(count) : "memory");
}
#define MBAR_WAIT_ASM(HINT, LIMIT)                                                                  \
    asm volatile("{\n.reg .pred p;\n.reg .u32 n;\nmov.u32 n, 0;\n"                                  \
                 "WAIT_LOOP:\n"                                                                     \
                 "mbarrier.try_wait.parity.shared::cta.b64 p, [%0], %1" HINT ";\n"                  \
                 "@p bra WAIT_DONE;\n"                                                              \
                 "add.u32 n, n, 1;\n"                                                               \
                 "setp.lt.u32 p, n, " LIMIT ";\n"                                                   \
                 "@p bra WAIT_LOOP;\n"                                                              \
                 "WAIT_DONE:\n}\n" ::"r"(bar), "r"(parity) : "memory")
__device__ __forceinline__ void mbar_wait(uint32_t bar, uint32_t parity) { MBAR_WAIT_ASM("", "131072"); }
__device__ __forceinline__ void mbar_sleep(uint32_t bar, uint32_t parity) { MBAR_WAIT_ASM(", 2000", "8192"); }
__device__ __forceinline__ bool mbar_try(uint32_t bar, uint32_t parity) {
    uint32_t ok;
    asm volatile("{\n.reg .pred p;\nmbarrier.try_wait.parity.shared::cta.b64 p, [%1], %2;\nselp.u32 %0, 1, 0, p;\n}\n"
                 : "=r"(ok) : "r"(bar), "r"(parity) : "memory");
    return ok;
}
__device__ __forceinline__ bool mbar_test(uint32_t bar, uint32_t parity) {
    uint32_t ok;
    asm volatile("{\n.reg .pred p;\nmbarrier.test_wait.parity.shared::cta.b64 p, [%1], %2;\nselp.u32 %0, 1, 0, p;\n}\n"
                 : "=r"(ok) : "r"(bar), "r"(parity) : "memory");
    return ok;
}
__device__ __forceinline__ bool elect_one() {
    uint32_t ok;
    asm volatile("{\n.reg .pred p;\nelect.sync _|p, 0xffffffff;\nselp.u32 %0, 1, 0, p;\n}\n" : "=r"(ok));
    return ok;
}
__device__ __forceinline__ void mbar_arrive(uint32_t bar) {
    asm volatile("mbarrier.arrive.shared::cta.b64 _, [%0];" ::"r"(bar) : "memory");
}
__device__ __forceinline__ void mbar_expect_tx(uint32_t bar, uint32_t bytes) {
    asm volatile("mbarrier.arrive.expect_tx.shared::cta.b64 _, [%0], %1;" ::"r"(bar), "r"(bytes) : "memory");
}
__device__ __forceinline__ void mbar_arrive_cluster(uint32_t cluster_addr) {
    asm volatile("mbarrier.arrive.shared::cluster.b64 _, [%0];" ::"r"(cluster_addr) : "memory");
}
__device__ __forceinline__ uint32_t mapa(uint32_t addr, uint32_t rank) {
    uint32_t r;
    asm("mapa.shared::cluster.u32 %0, %1, %2;" : "=r"(r) : "r"(addr), "r"(rank));
    return r;
}
__device__ __forceinline__ void tma_3d(uint32_t dst, const CUtensorMap* m, int c0, int c1, int c2, uint32_t bar) {
    asm volatile("cp.async.bulk.tensor.3d.shared::cluster.global.mbarrier::complete_tx::bytes [%0], [%1, {%3, %4, %5}], [%2];"
                 ::"r"(dst), "l"(m), "r"(bar), "r"(c0), "r"(c1), "r"(c2) : "memory");
}
__device__ __forceinline__ void tma_3d_hint(uint32_t dst, const CUtensorMap* m, int c0, int c1, int c2, uint32_t bar, uint64_t pol) {
    asm volatile("cp.async.bulk.tensor.3d.shared::cluster.global.mbarrier::complete_tx::bytes.L2::cache_hint [%0], [%1, {%3, %4, %5}], [%2], %6;"
                 ::"r"(dst), "l"(m), "r"(bar), "r"(c0), "r"(c1), "r"(c2), "l"(pol) : "memory");
}
__device__ __forceinline__ void tma_3d_mc(uint32_t dst, const CUtensorMap* m, int c0, int c1, int c2, uint32_t bar) {
    asm volatile("cp.async.bulk.tensor.3d.shared::cluster.global.mbarrier::complete_tx::bytes.multicast::cluster [%0], [%1, {%3, %4, %5}], [%2], %6;"
                 ::"r"(dst), "l"(m), "r"(bar), "r"(c0), "r"(c1), "r"(c2), "h"((uint16_t)3) : "memory");
}
__device__ __forceinline__ void bulk_load(uint32_t dst, const void* src, uint32_t bytes, uint32_t bar) {
    asm volatile("cp.async.bulk.shared::cluster.global.mbarrier::complete_tx::bytes [%0], [%1], %2, [%3];"
                 ::"r"(dst), "l"(src), "r"(bytes), "r"(bar) : "memory");
}
__device__ __forceinline__ void cp_async16(uint32_t dst, const void* src) {
    asm volatile("cp.async.cg.shared.global [%0], [%1], 16;" ::"r"(dst), "l"(src) : "memory");
}
__device__ __forceinline__ void bulk_load_mc(uint32_t dst, const void* src, uint32_t bytes, uint32_t bar) {
    asm volatile("cp.async.bulk.shared::cluster.global.mbarrier::complete_tx::bytes.multicast::cluster [%0], [%1], %2, [%3], %4;"
                 ::"r"(dst), "l"(src), "r"(bytes), "r"(bar), "h"((uint16_t)3) : "memory");
}
__device__ __forceinline__ void fence_async_smem() { asm volatile("fence.proxy.async.shared::cta;" ::: "memory"); }
__device__ __forceinline__ void prefetch_map(const CUtensorMap* m) {
    asm volatile("prefetch.tensormap [%0];" ::"l"(m) : "memory");
}
__device__ __forceinline__ void red_release(unsigned* p) {
    asm volatile("red.release.gpu.global.add.u32 [%0], 1;" ::"l"(p) : "memory");
}
__device__ __forceinline__ unsigned ld_relaxed(const unsigned* p) {
    unsigned v;
    asm volatile("ld.relaxed.gpu.global.u32 %0, [%1];" : "=r"(v) : "l"(p) : "memory");
    return v;
}
__device__ __forceinline__ void wait_counter(const unsigned* p, unsigned target) {
    for (uint32_t n = 0; (int)(ld_relaxed(p) - target) < 0 && n < SPIN_LIMIT; n++) __nanosleep(100);
    asm volatile("fence.acquire.gpu;" ::: "memory");
    asm volatile("fence.proxy.async.global;" ::: "memory");
}
__device__ __forceinline__ void bar_sync(int id, int n) { asm volatile("bar.sync %0, %1;" ::"r"(id), "r"(n) : "memory"); }
__device__ __forceinline__ void bar_arrive(int id, int n) { asm volatile("bar.arrive %0, %1;" ::"r"(id), "r"(n) : "memory"); }
__device__ __forceinline__ void cluster_sync() {
    asm volatile("barrier.cluster.arrive.relaxed.aligned;\nbarrier.cluster.wait.aligned;" ::: "memory");
}
__device__ __forceinline__ void wg_fence() { asm volatile("wgmma.fence.sync.aligned;" ::: "memory"); }
__device__ __forceinline__ void wg_commit() { asm volatile("wgmma.commit_group.sync.aligned;" ::: "memory"); }
template <int N> __device__ __forceinline__ void wg_wait() { asm volatile("wgmma.wait_group.sync.aligned %0;" ::"n"(N) : "memory"); }
template <int N> __device__ __forceinline__ void reg_fence(float (&a)[N]) {
#pragma unroll
    for (int i = 0; i < N; i++) asm volatile("" : "+f"(a[i])::"memory");
}
template <int N> __device__ __forceinline__ void reg_fence(uint32_t (&a)[N]) {
#pragma unroll
    for (int i = 0; i < N; i++) asm volatile("" : "+r"(a[i])::"memory");
}
__device__ __forceinline__ uint32_t pack_bf16(float lo, float hi) {
    uint32_t r;
    asm("cvt.rn.bf16x2.f32 %0, %1, %2;" : "=r"(r) : "f"(hi), "f"(lo));
    return r;
}
__device__ __forceinline__ float bf_lo(uint32_t v) { return __uint_as_float(v << 16); }
__device__ __forceinline__ float bf_hi(uint32_t v) { return __uint_as_float(v & 0xffff0000u); }
__device__ __forceinline__ float bf_round(float v) { return __bfloat162float(__float2bfloat16_rn(v)); }
__device__ __forceinline__ float ex2(float v) {
    float r;
    asm("ex2.approx.ftz.f32 %0, %1;" : "=f"(r) : "f"(v));
    return r;
}
__device__ __forceinline__ float sqrt_approx(float v) {
    float r;
    asm("sqrt.approx.ftz.f32 %0, %1;" : "=f"(r) : "f"(v));
    return r;
}
__device__ __forceinline__ float rcp_approx(float v) {
    float r;
    asm("rcp.approx.ftz.f32 %0, %1;" : "=f"(r) : "f"(v));
    return r;
}
__device__ __forceinline__ float silu_f(float v) { return v * rcp_approx(1.0f + ex2(v * -1.4426950408889634f)); }
__device__ __forceinline__ void stmatrix_x4(uint32_t addr, uint32_t r0, uint32_t r1, uint32_t r2, uint32_t r3) {
    asm volatile("stmatrix.sync.aligned.m8n8.x4.shared.b16 [%0], {%1, %2, %3, %4};"
                 ::"r"(addr), "r"(r0), "r"(r1), "r"(r2), "r"(r3) : "memory");
}
__device__ __forceinline__ void sts128(uint32_t addr, uint32_t r0, uint32_t r1, uint32_t r2, uint32_t r3) {
    asm volatile("st.shared.v4.b32 [%0], {%1, %2, %3, %4};" ::"r"(addr), "r"(r0), "r"(r1), "r"(r2), "r"(r3) : "memory");
}
__device__ __forceinline__ void lds128(uint32_t addr, uint32_t& r0, uint32_t& r1, uint32_t& r2, uint32_t& r3) {
    asm volatile("ld.shared.v4.b32 {%0, %1, %2, %3}, [%4];" : "=r"(r0), "=r"(r1), "=r"(r2), "=r"(r3) : "r"(addr) : "memory");
}
__device__ __forceinline__ uint32_t bf2_mul(uint32_t a, uint32_t b) {
    uint32_t r;
    asm("mul.rn.bf16x2 %0, %1, %2;" : "=r"(r) : "r"(a), "r"(b));
    return r;
}
__device__ __forceinline__ uint32_t bf2_add(uint32_t a, uint32_t b) {
    uint32_t r;
    asm("add.rn.bf16x2 %0, %1, %2;" : "=r"(r) : "r"(a), "r"(b));
    return r;
}
constexpr uint64_t POL_FIRST = 0x12F0000000000000ull, POL_NORMAL = 0x1000000000000000ull;
__device__ __forceinline__ uint4 ldg_hint(const void* p, uint64_t pol) {
    uint4 v;
    asm volatile("ld.global.cg.L2::cache_hint.v4.u32 {%0, %1, %2, %3}, [%4], %5;" : "=r"(v.x), "=r"(v.y), "=r"(v.z), "=r"(v.w) : "l"(p), "l"(pol));
    return v;
}
__device__ __forceinline__ void stg_hint(void* p, uint32_t r0, uint32_t r1, uint32_t r2, uint32_t r3, uint64_t pol) {
    asm volatile("st.global.cg.L2::cache_hint.v4.u32 [%0], {%1, %2, %3, %4}, %5;" ::"l"(p), "r"(r0), "r"(r1), "r"(r2), "r"(r3), "l"(pol) : "memory");
}

__device__ __forceinline__ uint64_t make_desc(uint32_t addr, uint32_t lbo_bytes) {
    return (uint64_t)((addr & 0x3FFFF) >> 4) | ((uint64_t)(lbo_bytes >> 4) << 16) | ((uint64_t)(1024 >> 4) << 32) | (1ull << 62);
}

__device__ __forceinline__ void wgmma_n256_ss(float (&d)[128], uint64_t da, uint64_t db, int acc) {
    asm volatile(
        "{\n.reg .pred p;\nsetp.ne.b32 p, %130, 0;\n"
        "wgmma.mma_async.sync.aligned.m64n256k16.f32.bf16.bf16 {"
        "%0, %1, %2, %3, %4, %5, %6, %7, %8, %9, %10, %11, %12, %13, %14, %15, "
        "%16, %17, %18, %19, %20, %21, %22, %23, %24, %25, %26, %27, %28, %29, %30, %31, "
        "%32, %33, %34, %35, %36, %37, %38, %39, %40, %41, %42, %43, %44, %45, %46, %47, "
        "%48, %49, %50, %51, %52, %53, %54, %55, %56, %57, %58, %59, %60, %61, %62, %63, "
        "%64, %65, %66, %67, %68, %69, %70, %71, %72, %73, %74, %75, %76, %77, %78, %79, "
        "%80, %81, %82, %83, %84, %85, %86, %87, %88, %89, %90, %91, %92, %93, %94, %95, "
        "%96, %97, %98, %99, %100, %101, %102, %103, %104, %105, %106, %107, %108, %109, %110, %111, "
        "%112, %113, %114, %115, %116, %117, %118, %119, %120, %121, %122, %123, %124, %125, %126, %127"
        "}, %128, %129, p, 1, 1, 1, 0;\n}\n"
        :
        "+f"(d[0]), "+f"(d[1]), "+f"(d[2]), "+f"(d[3]), "+f"(d[4]), "+f"(d[5]), "+f"(d[6]), "+f"(d[7]),
        "+f"(d[8]), "+f"(d[9]), "+f"(d[10]), "+f"(d[11]), "+f"(d[12]), "+f"(d[13]), "+f"(d[14]), "+f"(d[15]),
        "+f"(d[16]), "+f"(d[17]), "+f"(d[18]), "+f"(d[19]), "+f"(d[20]), "+f"(d[21]), "+f"(d[22]), "+f"(d[23]),
        "+f"(d[24]), "+f"(d[25]), "+f"(d[26]), "+f"(d[27]), "+f"(d[28]), "+f"(d[29]), "+f"(d[30]), "+f"(d[31]),
        "+f"(d[32]), "+f"(d[33]), "+f"(d[34]), "+f"(d[35]), "+f"(d[36]), "+f"(d[37]), "+f"(d[38]), "+f"(d[39]),
        "+f"(d[40]), "+f"(d[41]), "+f"(d[42]), "+f"(d[43]), "+f"(d[44]), "+f"(d[45]), "+f"(d[46]), "+f"(d[47]),
        "+f"(d[48]), "+f"(d[49]), "+f"(d[50]), "+f"(d[51]), "+f"(d[52]), "+f"(d[53]), "+f"(d[54]), "+f"(d[55]),
        "+f"(d[56]), "+f"(d[57]), "+f"(d[58]), "+f"(d[59]), "+f"(d[60]), "+f"(d[61]), "+f"(d[62]), "+f"(d[63]),
        "+f"(d[64]), "+f"(d[65]), "+f"(d[66]), "+f"(d[67]), "+f"(d[68]), "+f"(d[69]), "+f"(d[70]), "+f"(d[71]),
        "+f"(d[72]), "+f"(d[73]), "+f"(d[74]), "+f"(d[75]), "+f"(d[76]), "+f"(d[77]), "+f"(d[78]), "+f"(d[79]),
        "+f"(d[80]), "+f"(d[81]), "+f"(d[82]), "+f"(d[83]), "+f"(d[84]), "+f"(d[85]), "+f"(d[86]), "+f"(d[87]),
        "+f"(d[88]), "+f"(d[89]), "+f"(d[90]), "+f"(d[91]), "+f"(d[92]), "+f"(d[93]), "+f"(d[94]), "+f"(d[95]),
        "+f"(d[96]), "+f"(d[97]), "+f"(d[98]), "+f"(d[99]), "+f"(d[100]), "+f"(d[101]), "+f"(d[102]), "+f"(d[103]),
        "+f"(d[104]), "+f"(d[105]), "+f"(d[106]), "+f"(d[107]), "+f"(d[108]), "+f"(d[109]), "+f"(d[110]), "+f"(d[111]),
        "+f"(d[112]), "+f"(d[113]), "+f"(d[114]), "+f"(d[115]), "+f"(d[116]), "+f"(d[117]), "+f"(d[118]), "+f"(d[119]),
        "+f"(d[120]), "+f"(d[121]), "+f"(d[122]), "+f"(d[123]), "+f"(d[124]), "+f"(d[125]), "+f"(d[126]), "+f"(d[127])
        : "l"(da), "l"(db), "r"(acc));
}

__device__ __forceinline__ void wgmma_n192_ss(float* d, uint64_t da, uint64_t db, int acc) {
    asm volatile(
        "{\n.reg .pred p;\nsetp.ne.b32 p, %98, 0;\n"
        "wgmma.mma_async.sync.aligned.m64n192k16.f32.bf16.bf16 {"
        "%0, %1, %2, %3, %4, %5, %6, %7, %8, %9, %10, %11, %12, %13, %14, %15, "
        "%16, %17, %18, %19, %20, %21, %22, %23, %24, %25, %26, %27, %28, %29, %30, %31, "
        "%32, %33, %34, %35, %36, %37, %38, %39, %40, %41, %42, %43, %44, %45, %46, %47, "
        "%48, %49, %50, %51, %52, %53, %54, %55, %56, %57, %58, %59, %60, %61, %62, %63, "
        "%64, %65, %66, %67, %68, %69, %70, %71, %72, %73, %74, %75, %76, %77, %78, %79, "
        "%80, %81, %82, %83, %84, %85, %86, %87, %88, %89, %90, %91, %92, %93, %94, %95"
        "}, %96, %97, p, 1, 1, 1, 0;\n}\n"
        :
        "+f"(d[0]), "+f"(d[1]), "+f"(d[2]), "+f"(d[3]), "+f"(d[4]), "+f"(d[5]), "+f"(d[6]), "+f"(d[7]),
        "+f"(d[8]), "+f"(d[9]), "+f"(d[10]), "+f"(d[11]), "+f"(d[12]), "+f"(d[13]), "+f"(d[14]), "+f"(d[15]),
        "+f"(d[16]), "+f"(d[17]), "+f"(d[18]), "+f"(d[19]), "+f"(d[20]), "+f"(d[21]), "+f"(d[22]), "+f"(d[23]),
        "+f"(d[24]), "+f"(d[25]), "+f"(d[26]), "+f"(d[27]), "+f"(d[28]), "+f"(d[29]), "+f"(d[30]), "+f"(d[31]),
        "+f"(d[32]), "+f"(d[33]), "+f"(d[34]), "+f"(d[35]), "+f"(d[36]), "+f"(d[37]), "+f"(d[38]), "+f"(d[39]),
        "+f"(d[40]), "+f"(d[41]), "+f"(d[42]), "+f"(d[43]), "+f"(d[44]), "+f"(d[45]), "+f"(d[46]), "+f"(d[47]),
        "+f"(d[48]), "+f"(d[49]), "+f"(d[50]), "+f"(d[51]), "+f"(d[52]), "+f"(d[53]), "+f"(d[54]), "+f"(d[55]),
        "+f"(d[56]), "+f"(d[57]), "+f"(d[58]), "+f"(d[59]), "+f"(d[60]), "+f"(d[61]), "+f"(d[62]), "+f"(d[63]),
        "+f"(d[64]), "+f"(d[65]), "+f"(d[66]), "+f"(d[67]), "+f"(d[68]), "+f"(d[69]), "+f"(d[70]), "+f"(d[71]),
        "+f"(d[72]), "+f"(d[73]), "+f"(d[74]), "+f"(d[75]), "+f"(d[76]), "+f"(d[77]), "+f"(d[78]), "+f"(d[79]),
        "+f"(d[80]), "+f"(d[81]), "+f"(d[82]), "+f"(d[83]), "+f"(d[84]), "+f"(d[85]), "+f"(d[86]), "+f"(d[87]),
        "+f"(d[88]), "+f"(d[89]), "+f"(d[90]), "+f"(d[91]), "+f"(d[92]), "+f"(d[93]), "+f"(d[94]), "+f"(d[95])
        : "l"(da), "l"(db), "r"(acc));
}

template <int TB>
__device__ __forceinline__ void wgmma_n128_rs(float (&d)[64], uint32_t a0, uint32_t a1, uint32_t a2, uint32_t a3, uint32_t db, int acc) {
    asm volatile(
        "{\n.reg .pred p;\n.reg .b64 db;\nsetp.ne.b32 p, %69, 0;\nmov.b64 db, {%68, 0x40000040};\n"
        "wgmma.mma_async.sync.aligned.m64n128k16.f32.bf16.bf16 {"
        "%0, %1, %2, %3, %4, %5, %6, %7, %8, %9, %10, %11, %12, %13, %14, %15, "
        "%16, %17, %18, %19, %20, %21, %22, %23, %24, %25, %26, %27, %28, %29, %30, %31, "
        "%32, %33, %34, %35, %36, %37, %38, %39, %40, %41, %42, %43, %44, %45, %46, %47, "
        "%48, %49, %50, %51, %52, %53, %54, %55, %56, %57, %58, %59, %60, %61, %62, %63"
        "}, {%64, %65, %66, %67}, db, p, 1, 1, %70;\n}\n"
        :
        "+f"(d[0]), "+f"(d[1]), "+f"(d[2]), "+f"(d[3]), "+f"(d[4]), "+f"(d[5]), "+f"(d[6]), "+f"(d[7]),
        "+f"(d[8]), "+f"(d[9]), "+f"(d[10]), "+f"(d[11]), "+f"(d[12]), "+f"(d[13]), "+f"(d[14]), "+f"(d[15]),
        "+f"(d[16]), "+f"(d[17]), "+f"(d[18]), "+f"(d[19]), "+f"(d[20]), "+f"(d[21]), "+f"(d[22]), "+f"(d[23]),
        "+f"(d[24]), "+f"(d[25]), "+f"(d[26]), "+f"(d[27]), "+f"(d[28]), "+f"(d[29]), "+f"(d[30]), "+f"(d[31]),
        "+f"(d[32]), "+f"(d[33]), "+f"(d[34]), "+f"(d[35]), "+f"(d[36]), "+f"(d[37]), "+f"(d[38]), "+f"(d[39]),
        "+f"(d[40]), "+f"(d[41]), "+f"(d[42]), "+f"(d[43]), "+f"(d[44]), "+f"(d[45]), "+f"(d[46]), "+f"(d[47]),
        "+f"(d[48]), "+f"(d[49]), "+f"(d[50]), "+f"(d[51]), "+f"(d[52]), "+f"(d[53]), "+f"(d[54]), "+f"(d[55]),
        "+f"(d[56]), "+f"(d[57]), "+f"(d[58]), "+f"(d[59]), "+f"(d[60]), "+f"(d[61]), "+f"(d[62]), "+f"(d[63])
        : "r"(a0), "r"(a1), "r"(a2), "r"(a3), "r"(db), "r"(acc), "n"(TB));
}

__device__ __forceinline__ void wgmma_n128_ss(float* d, uint64_t da, uint64_t db, int acc) {
    asm volatile(
        "{\n.reg .pred p;\nsetp.ne.b32 p, %66, 0;\n"
        "wgmma.mma_async.sync.aligned.m64n128k16.f32.bf16.bf16 {"
        "%0, %1, %2, %3, %4, %5, %6, %7, %8, %9, %10, %11, %12, %13, %14, %15, "
        "%16, %17, %18, %19, %20, %21, %22, %23, %24, %25, %26, %27, %28, %29, %30, %31, "
        "%32, %33, %34, %35, %36, %37, %38, %39, %40, %41, %42, %43, %44, %45, %46, %47, "
        "%48, %49, %50, %51, %52, %53, %54, %55, %56, %57, %58, %59, %60, %61, %62, %63"
        "}, %64, %65, p, 1, 1, 0, 1;\n}\n"
        :
        "+f"(d[0]), "+f"(d[1]), "+f"(d[2]), "+f"(d[3]), "+f"(d[4]), "+f"(d[5]), "+f"(d[6]), "+f"(d[7]),
        "+f"(d[8]), "+f"(d[9]), "+f"(d[10]), "+f"(d[11]), "+f"(d[12]), "+f"(d[13]), "+f"(d[14]), "+f"(d[15]),
        "+f"(d[16]), "+f"(d[17]), "+f"(d[18]), "+f"(d[19]), "+f"(d[20]), "+f"(d[21]), "+f"(d[22]), "+f"(d[23]),
        "+f"(d[24]), "+f"(d[25]), "+f"(d[26]), "+f"(d[27]), "+f"(d[28]), "+f"(d[29]), "+f"(d[30]), "+f"(d[31]),
        "+f"(d[32]), "+f"(d[33]), "+f"(d[34]), "+f"(d[35]), "+f"(d[36]), "+f"(d[37]), "+f"(d[38]), "+f"(d[39]),
        "+f"(d[40]), "+f"(d[41]), "+f"(d[42]), "+f"(d[43]), "+f"(d[44]), "+f"(d[45]), "+f"(d[46]), "+f"(d[47]),
        "+f"(d[48]), "+f"(d[49]), "+f"(d[50]), "+f"(d[51]), "+f"(d[52]), "+f"(d[53]), "+f"(d[54]), "+f"(d[55]),
        "+f"(d[56]), "+f"(d[57]), "+f"(d[58]), "+f"(d[59]), "+f"(d[60]), "+f"(d[61]), "+f"(d[62]), "+f"(d[63])
        : "l"(da), "l"(db), "r"(acc));
}

__device__ __forceinline__ void wgmma_n8_ta(float* d, uint64_t da, uint64_t db) {
    asm volatile("wgmma.mma_async.sync.aligned.m64n8k16.f32.bf16.bf16 {%0, %1, %2, %3}, %4, %5, 1, 1, 1, 1, 0;\n"
                 : "+f"(d[0]), "+f"(d[1]), "+f"(d[2]), "+f"(d[3]) : "l"(da), "l"(db));
}

#define PROF(slot, role)
#undef PROF_GT
#define PROF_GT(slot)

struct Params {
    const __nv_bfloat16* x;
    const __nv_bfloat16* w_r;
    const uint8_t *c_kv, *w_uk, *w_uv;
    uint8_t* out;
};
__device__ __forceinline__ void lsu_prefetch(const void* p) { asm volatile("prefetch.global.L2 [%0];" ::"l"(p) : "memory"); }

template <typename T>
__device__ __forceinline__ T* ptr_off(T* base, uint32_t off) {
    uint32_t lo, hi;
    asm("mov.b64 {%0, %1}, %2;" : "=r"(lo), "=r"(hi) : "l"(base));
    asm("add.cc.u32 %0, %0, %2;\naddc.u32 %1, %1, 0;" : "+r"(lo), "+r"(hi) : "r"(off));
    T* r;
    asm("mov.b64 %0, {%1, %2};" : "=l"(r) : "r"(lo), "r"(hi));
    return r;
}
__device__ __forceinline__ int kv_head(int pair) { return pair & 7; }
__device__ __forceinline__ int kv_tokens(int pair) { return ((pair >> 3) & 1) * 4 + (pair >> 4); }
__device__ __forceinline__ int out_rows(int pair) { return pair & 7; }
__device__ __forceinline__ int out_cols(int pair) { return (pair >> 4) * 4 + ((pair >> 3) & 1) * 2; }
__device__ __forceinline__ int attn_rowblock(int pair, int seg) {
    int j = pair & 3, hl = pair >> 2;
    return ((hl & 1) ^ seg) ? j : 7 - j;
}
__device__ __forceinline__ int outproj_head(int i, int ib) {
    if (i < 16) return i;
    return 16 + 2 * (i & 7) + ((ib < 4) ^ ((i >> 3) & 1));
}

__device__ __forceinline__ void pin_value(uint32_t& v) { asm volatile("" : "+r"(v)); }
__device__ __forceinline__ void pin_value(int& v) { asm volatile("" : "+r"(v)); }
__device__ __forceinline__ void pin_value(const uint8_t*& v) { asm volatile("" : "+l"(v)); }

__device__ __forceinline__ void producer(const Params& P, uint32_t sb, int pair, int c,
                                         const CUtensorMap* m_ckv, const CUtensorMap* m_wu,
                                         const CUtensorMap* m_wq, const CUtensorMap* m_wo) {
    const int hl = pair >> 2;
    const int ibA = attn_rowblock(pair, 0), nA = 2 * ibA + 2;
    const int ib = out_rows(pair), mi = 2 * ib + c, nb = out_cols(pair);
    const bool leader = elect_one();
    uint32_t g = 4, tail = 0;
    if (leader) prefetch_map(m_wq);
    auto wait_released = [&](uint32_t need) {
#pragma unroll 1
        for (; tail <= need; tail++) mbar_wait(sb + BAR_EMPTY + (tail & 7) * 8, (tail >> 3) & 1);
    };
    auto wait_released_here = [&](uint32_t need) {
#pragma unroll 1
        for (; tail < need; tail++) mbar_wait(sb + BAR_EMPTY + (tail & 7) * 8, (tail >> 3) & 1);
        if (tail == need) mbar_wait(sb + BAR_EMPTYL + (need & 7) * 8, (need >> 3) & 1);
    };
    auto wait_released_peer = [&](uint32_t need) {
        if (tail == need) {
            uint32_t eb = sb + BAR_EMPTY + (need & 7) * 8, ep = (need >> 3) & 1;
            tail++;
            mbar_wait(eb, ep);
        }
    };
    auto full_bar = [&]() { return sb + BAR_FULL + (g & 7) * 8; };
    auto pin = [](auto&... v) { (pin_value(v), ...); };
#pragma unroll 1
    for (int rnd = 0; rnd < 2; rnd++) {
#pragma unroll 1
        for (int i = rnd ? 0 : 4; i < 16; i++) {
            int kb = i & 7, h2 = (kv_head(pair) + (i & 8) + rnd * 16) * 2, krow = kb * 64;
            uint32_t pg = sb + (i & 3) * (3 * PAGE), pb = pg + (1 + c) * PAGE, bar = full_bar();
            pin(kb, h2, krow, pg, pb, bar);
            const uint32_t need = g - 4 - (i < 2);
            wait_released_here(need);
            if (leader) {
                mbar_expect_tx(bar, 3 * PAGE);
                tma_3d(pg, m_wu, 0, krow, h2, bar);
            }
            wait_released_peer(need);
            if (leader) {
                tma_3d_mc(pb, m_ckv, 0, kv_tokens(pair) * 256 + c * 128, kb, bar);
                if (rnd == 1 && i == 3) asm volatile("red.relaxed.gpu.global.add.u32 [%0], 1;" ::"l"(ptr_off(g_sync.kvfree, hl * 32)) : "memory");
            }
            g++;
        }
        mbar_sleep(sb + BAR_DEP, 0);
        const uint8_t* xa = ptr_off(g_xn, ibA * (16 * 32768) + c * PAGE);
        const uint8_t* xb = ptr_off(g_xn, (7 - ibA) * (16 * 32768) + (1 - c) * PAGE);
#pragma unroll 1
        for (int kb = 0; kb < DM / 64; kb++) {
            uint32_t pg = sb + (kb & 3) * (3 * PAGE), pw = pg + 2 * PAGE + c * 8192, bar = full_bar(), p2 = pg + PAGE;
            int krow = kb * 64;
            pin(pg, pw, p2, bar, krow);
            wait_released_here(g - 4);
            if (leader) {
                mbar_expect_tx(bar, 3 * PAGE);
                bulk_load(pg, xa, PAGE, bar);
            }
            wait_released_peer(g - 4);
            if (leader) {
                tma_3d_mc(pw, m_wq, 0, krow, (rnd * 16 + hl) * 2 + c, bar);
                bulk_load(p2, xb, PAGE, bar);
            }
            g++;
            xa += 32768;
            xb += 32768;
        }
        mbar_sleep(sb + BAR_DEP + 8 + rnd * 16, 0);
        if (rnd == 1 && leader) prefetch_map(m_wo);
        uint32_t pg = sb + c * PAGE;
#pragma unroll 1
        for (int j = 0; j < 36; j++) {
            const bool isk = j == 0 || ((j & 1) && j != 35);
            const int t = isk ? (j + 1) >> 1 : (j - 1) >> 1;
            const uint8_t* src = ptr_off(g_kv, (hl * 16 + (t >= nA ? t - nA : t)) * 65536 + (isk ? 0 : 32768) + c * PAGE);
            uint32_t bar = full_bar(), need = g - 6 + (j < 2) + (j < 5);
            pin(src, bar, need);
            wait_released(need);
            if (leader) {
                mbar_expect_tx(bar, 2 * PAGE);
                bulk_load_mc(pg, src, PAGE, bar);
            }
            g++;
            if (rnd == 0 && j >= 22 && j < 34) {
                const int cta = pair * 2 + c, i = j - 22;
                const uint32_t l = (threadIdx.x & 31) * 128;
                if (i < 8) lsu_prefetch(ptr_off(i & 1 ? P.w_uv : P.w_uk, cta * 32768 + (i >> 1) * 8192 + 4096 + l));
                else lsu_prefetch(ptr_off(P.c_kv, cta * 16384 + (i - 8) * 4096 + l));
            }
            pg = pg >= sb + SM_REGION - 2 * PAGE ? pg - (SM_REGION - 2 * PAGE) : pg + 2 * PAGE;
        }
    }
    uint32_t pg = sb;
#pragma unroll 1
    for (int i = 0; i < 64; i++) {
        if ((i & 15) == 0 && i != 16) mbar_sleep(sb + BAR_DEP + 32 + (i >> 1) - (i ? 8 : 0), 0);
        const int kb = outproj_head(i >> 1, ib) * 2 + (i & 1);
        const uint8_t* src = ptr_off(g_ctx, (mi * 64 + kb) * PAGE);
        uint32_t bar = full_bar(), pw = pg + PAGE + c * 8192;
        int krow = kb * 64;
        pin(src, bar, pw, krow);
        wait_released_here(g - 6);
        if (leader) {
            mbar_expect_tx(bar, 2 * PAGE);
            bulk_load(pg, src, PAGE, bar);
        }
        wait_released_peer(g - 6);
        if (leader) tma_3d_mc(pw, m_wo, 0, krow, nb + c, bar);
        g++;
        pg = pg == sb + SM_REGION - 2 * PAGE ? sb : pg + 2 * PAGE;
    }
}

__device__ __forceinline__ uint32_t xn_block(int row64, int kb) {
    return (((row64 >> 2) * 16 + kb) * 4 + ((row64 & 1) * 2 + (((row64 >> 1) & 1) ^ 1))) * 8192;
}
__device__ __forceinline__ uint32_t image_offset(int row, int ch) {
    return xn_block(row >> 6, ch >> 3) + (row & 63) * 128 + (((ch & 7) ^ (row & 7)) << 4);
}
__device__ __forceinline__ uint32_t bf2_sub(uint32_t a, uint32_t b) {
    uint32_t r;
    asm("sub.rn.bf16x2 %0, %1, %2;" : "=r"(r) : "r"(a), "r"(b));
    return r;
}
__device__ __forceinline__ uint32_t bf2_fma(uint32_t a, uint32_t b, uint32_t c) {
    uint32_t r;
    asm("fma.rn.bf16x2 %0, %1, %2, %3;" : "=r"(r) : "r"(a), "r"(b), "r"(c));
    return r;
}
template <int N0, int N>
__device__ __forceinline__ void ln_sums(const uint32_t (&u)[N], float& sum, float& sq) {
    float s0 = 0.f, s1 = 0.f, q0 = 0.f, q1 = 0.f;
#pragma unroll
    for (int k = N0; k < N0 + 16; k++) {
        const float a = bf_lo(u[k]), b = bf_hi(u[k]);
        s0 += a; s1 += b;
        q0 = fmaf(a, a, q0); q1 = fmaf(b, b, q1);
    }
    sum = s0 + s1;
    sq = q0 + q1;
}
__device__ __forceinline__ void ln_finish(float sum, float sq, uint32_t& mean2, uint32_t& rhi2, uint32_t& rlo2) {
    const float ms = sum * (1.0f / DM);
    const float var = fmaxf(fmaf(-ms, ms, sq * (1.0f / DM)), 0.f);
    const float rden = rcp_approx(bf_round(sqrt_approx(bf_round(bf_round(var) + 1e-5f))));
    const float rhi = bf_round(rden);
    mean2 = pack_bf16(ms, ms);
    rhi2 = pack_bf16(rhi, rhi);
    rlo2 = pack_bf16(rden - rhi, rden - rhi);
}
template <int N0, int N>
__device__ __forceinline__ void ln_apply(uint32_t (&u)[N], uint32_t mean2, uint32_t rhi2, uint32_t rlo2, uint8_t* dst) {
#pragma unroll
    for (int i = 0; i < 4; i++) {
        uint32_t o[4];
#pragma unroll
        for (int k = 0; k < 4; k++) {
            const uint32_t d = bf2_sub(u[N0 + 4 * i + k], mean2);
            o[k] = bf2_fma(d, rhi2, bf2_mul(d, rlo2));
        }
#pragma unroll
        for (int k = 0; k < 4; k++) u[N0 + 4 * i + k] = o[k];
        __stcg(reinterpret_cast<uint4*>(dst + i * 131072), make_uint4(o[0], o[1], o[2], o[3]));
    }
}
__device__ __forceinline__ int query_rowblock(int pair, int c, int w, int seg) {
    const int qA = (w ? 0 : 2) + c;
    return 4 * attn_rowblock(pair, seg) + (seg ? 3 - qA : qA);
}

__device__ __noinline__ void fetch_helper(const uint8_t* w_u, const uint8_t* x, uint32_t sb, int w, int lane, int pair, int c) {
    const uint32_t page = sb + SM_REGION + w * PAGE + lane * 16;
    mbar_sleep(sb + BAR_FULL + 5 * 8, 0);
#pragma unroll 1
    for (int i = 0; i < 2; i++) {
        lsu_prefetch(ptr_off(w_u, ((pair * 2 + c) * 4 + i * 2 + (lane >> 4)) * 8192 + 2048 + (lane & 15) * 128));
        __nanosleep(300);
    }
    const unsigned e1 = __ldcg(&g_sync.done) / NCTA + 1;
#pragma unroll 1
    for (int e = 1; e <= 7; e += 2) mbar_sleep(sb + BAR_DONE + 8, (e >> 1) & 1);
    const int rb = out_rows(pair) * 4 + c * 2 + w, kb0 = out_cols(pair);
    const uint8_t* src = ptr_off(g_xn, xn_block(rb, kb0) + lane * 16);
#pragma unroll 1
    for (int i = 0; i < 32; i += 4) {
#pragma unroll
        for (int k = 0; k < 4; k++) cp_async16(page + (i + k) * 512, src + (i + k) * 512 + (i >> 4) * (32768 - 8192));
        __nanosleep(200);
    }
#pragma unroll 1
    for (int i = 0; i < 4; i++) lsu_prefetch(ptr_off(x, (rb * 64 + i * 16 + (lane >> 1)) * (DM * 2) + kb0 * 128 + (lane & 1) * 128));
    wait_counter(&g_sync.ffn_done, e1);
    const int r = __ldcg(ptr_off(g_sel, (lane >> 4) * 4)) - rb * 64, ch = lane & 15;
    const uint4 t = __ldcg(ptr_off(g_routed, ((lane >> 4) * 128 + kb0 * 8 + ch) * 16));
    asm volatile("cp.async.wait_all;" ::: "memory");
    __syncwarp();
    if (r >= 0 && r < 64)
        sts128(sb + SM_REGION + w * PAGE + (ch >> 3) * 8192 + r * 128 + (((ch & 7) ^ (r & 7)) << 4), t.x, t.y, t.z, t.w);
    __syncwarp();
    if (lane == 0) mbar_arrive(sb + BAR_G + w * 8);
    PROF(20, 2);
}

__device__ __noinline__ void sync_helper(uint32_t sb, int lane, int pair, int c) {
    const unsigned e1 = __ldcg(&g_sync.done) / NCTA + 1;
    const int ib = out_rows(pair);
    int e = 0, b = 0;
#pragma unroll 1
    for (uint32_t n = 0; (e < 9 || b < 7) && n < SPIN_LIMIT; n++) {
        if (e < 9 && __all_sync(~0u, mbar_test(sb + BAR_DONE + (e & 1) * 8, (e >> 1) & 1))) {
            const int rnd = e > 4, ev = (e - 1) & 3;
            unsigned* flag = e == 0 ? &g_sync.ln
                           : ev < 2 ? ptr_off(g_sync.kv, (rnd * 16 + kv_head(pair) + 8 * ev) * 32)
                                    : ptr_off(g_sync.ctx, (query_rowblock(pair, c, lane & 1, ev & 1) * NH + rnd * 16 + (pair >> 2)) * 4);
            asm volatile("fence.proxy.async.global;\nfence.release.gpu;" ::: "memory");
            if (lane < ((e == 0 || ev < 2) ? 1 : 2)) asm volatile("red.relaxed.gpu.global.add.u32 [%0], 1;" ::"l"(flag) : "memory");
            PROF(10 + e, 2);
            e++;
        }
        if (b < 7 && e > 0 && (b < 4 || (n & POLL_MASK) == 0)) {
            const int i = b == 4 ? lane >> 1 : 8 * b - 24 + ((lane >> 1) & 7);
            const unsigned* cnt = b == 0 ? &g_sync.ln
                                : b == 2 ? ptr_off(g_sync.kvfree, (kv_head(pair) + 8 * (lane & 1)) * 32)
                                : b < 4 ? ptr_off(g_sync.kv, ((b >> 1) * 16 + (pair >> 2)) * 32)
                                        : ptr_off(g_sync.ctx, ((4 * ib + 2 * c + (lane & 1)) * NH + outproj_head(i & 31, ib)) * 4);
            if (__all_sync(~0u, (int)(ld_relaxed(cnt) - e1 * (b == 0 ? NMAIN : b == 2 ? 8 : b < 4 ? 16 : 1)) >= 0)) {
                asm volatile("fence.acquire.gpu;\nfence.proxy.async.global;" ::: "memory");
                __syncwarp();
                if (lane == 0) mbar_arrive(sb + BAR_DEP + b * 8);
                PROF(1 + b, 2);
                b++;
            }
        }
        __nanosleep(150);
    }
}

__device__ __forceinline__ unsigned long long block_max_key(unsigned long long k, unsigned long long* red, int tid) {
#pragma unroll
    for (int o = 16; o; o >>= 1) {
        unsigned long long t = __shfl_xor_sync(~0u, k, o);
        k = t > k ? t : k;
    }
    bar_sync(1, 256);
    if ((tid & 31) == 0) red[tid >> 5] = k;
    bar_sync(1, 256);
    k = red[0];
#pragma unroll
    for (int i = 1; i < 8; i++) k = red[i] > k ? red[i] : k;
    return k;
}

constexpr int FS = FF / 4;
constexpr int FSTAGE = 32768, FNST = 6;
constexpr int FN1 = 2 * (DM / 16), FN2 = FS / 16;

__device__ __forceinline__ void ffn_producer(uint32_t sb, int s, const CUtensorMap* m_gate, const CUtensorMap* m_up,
                                             const CUtensorMap* m_down) {
    wait_counter(&g_sync.ln, (__ldcg(&g_sync.done) / NCTA + 1) * NMAIN);
    int slot = 0, ph = 1;
#pragma unroll 1
    for (int st = 0; st < FN1 + FN2; st++) {
        mbar_sleep(sb + BAR_EMPTY + slot * 8, ph);
        const uint32_t bar = sb + BAR_FULL + slot * 8;
        const bool up = st < FN1;
        mbar_expect_tx(bar, up ? FS * 32 : DM * 32);
        tma_3d_hint(sb + slot * FSTAGE, up ? ((st & 1) ? m_up : m_gate) : m_down, 0,
                    up ? (st >> 1) * 16 : s * FS + (st - FN1) * 16, up ? s * (FS / 64) : 0, bar, POL_FIRST);
        if (++slot == FNST) { slot = 0; ph ^= 1; }
    }
}

__device__ __forceinline__ void ffn_cta(uint8_t* smem, uint32_t sb, int s, unsigned epoch, const __nv_bfloat16* w_r) {
    const int tid = threadIdx.x, lane = tid & 31;
    const int warp = __shfl_sync(~0u, tid >> 5, 0), w = warp >> 2;
    constexpr uint32_t XB = FNST * FSTAGE, HB = XB + 16384, AUX = HB + 14336;
    unsigned long long* red = reinterpret_cast<unsigned long long*>(smem + AUX);
    unsigned* flag = reinterpret_cast<unsigned*>(smem + AUX + 128);
    const unsigned e1 = epoch + 1;
    for (int i = tid; i < (16384 + 14336) / 16; i += 256) reinterpret_cast<uint4*>(smem + XB)[i] = make_uint4(0, 0, 0, 0);
    {
        float wf[32];
#pragma unroll
        for (int i = 0; i < 4; i++) {
            const uint4 t = __ldg(reinterpret_cast<const uint4*>(w_r) + lane + 32 * i);
            const uint32_t tu[4] = {t.x, t.y, t.z, t.w};
#pragma unroll
            for (int k = 0; k < 4; k++) { wf[8 * i + 2 * k] = bf_lo(tu[k]); wf[8 * i + 2 * k + 1] = bf_hi(tu[k]); }
        }
        if (tid == 0) wait_counter(&g_sync.ln, e1 * NMAIN);
        bar_sync(1, 256);
#pragma unroll 1
        for (int r0 = s * (SEQ / 4) + warp * (SEQ / 32); r0 < s * (SEQ / 4) + (warp + 1) * (SEQ / 32); r0 += 4) {
            uint4 t[4][4];
#pragma unroll
            for (int r = 0; r < 4; r++)
#pragma unroll
                for (int i = 0; i < 4; i++) t[r][i] = __ldcg(reinterpret_cast<const uint4*>(g_xn + image_offset(r0 + r, lane) + i * 131072));
            float acc[4];
#pragma unroll
            for (int r = 0; r < 4; r++) {
                float a = 0.f, b = 0.f;
#pragma unroll
                for (int i = 0; i < 4; i++) {
                    const uint32_t tu[4] = {t[r][i].x, t[r][i].y, t[r][i].z, t[r][i].w};
#pragma unroll
                    for (int k = 0; k < 4; k++) {
                        a = fmaf(bf_lo(tu[k]), wf[8 * i + 2 * k], a);
                        b = fmaf(bf_hi(tu[k]), wf[8 * i + 2 * k + 1], b);
                    }
                }
                acc[r] = a + b;
            }
#pragma unroll
            for (int o = 16; o; o >>= 1)
#pragma unroll
                for (int r = 0; r < 4; r++) acc[r] += __shfl_xor_sync(~0u, acc[r], o);
            if (lane < 4) __stcg(&g_r[r0 + lane], bf_round(lane == 0 ? acc[0] : lane == 1 ? acc[1] : lane == 2 ? acc[2] : acc[3]));
        }
        __threadfence();
        bar_sync(1, 256);
        if (tid == 0) {
            red_release(&g_sync.router);
            wait_counter(&g_sync.router, e1 * 4);
        }
        bar_sync(1, 256);
    }
    unsigned long long keys[8];
    unsigned long long best = 0;
#pragma unroll
    for (int i = 0; i < 8; i++) {
        int idx = tid + 256 * i;
        uint32_t b = __float_as_uint(__ldcg(&g_r[idx]) + 0.0f);
        b = (b & 0x80000000u) ? ~b : (b | 0x80000000u);
        keys[i] = ((unsigned long long)b << 32) | (unsigned)(SEQ - 1 - idx);
        best = keys[i] > best ? keys[i] : best;
    }
    const unsigned long long k0 = block_max_key(best, red, tid);
    best = 0;
#pragma unroll
    for (int i = 0; i < 8; i++) best = (keys[i] != k0 && keys[i] > best) ? keys[i] : best;
    const unsigned long long k1 = block_max_key(best, red, tid);
    const int row = SEQ - 1 - (int)((w ? k1 : k0) & 0xffffffffu);
    const int ch = tid & 127;
    const uint4 xrow = __ldcg(reinterpret_cast<const uint4*>(g_xn + image_offset(row, ch)));
    *reinterpret_cast<uint4*>(smem + XB + (ch >> 3) * 1024 + w * 128 + (((ch & 7) ^ w) << 4)) = xrow;
    fence_async_smem();
    bar_sync(1, 256);
    PROF(20, tid >> 7);
    int slot = 0, ph = 0, prev = 0;
    auto next_stage = [&](bool has_prev) {
        wg_commit();
        wg_wait<1>();
        if (has_prev && lane < 2) mbar_arrive(sb + BAR_EMPTY + prev * 8);
        prev = slot;
        if (++slot == FNST) { slot = 0; ph ^= 1; }
    };
    {
        float ag[28], au[28];
#pragma unroll
        for (int i = 0; i < 28; i++) ag[i] = au[i] = 0.f;
#pragma unroll 1
        for (int ks = 0; ks < DM / 16; ks++) {
            const uint64_t db = make_desc(sb + XB + (ks >> 2) * 1024 + (ks & 3) * 32, 16);
            mbar_wait(sb + BAR_FULL + slot * 8, ph);
            uint64_t da = make_desc(sb + slot * FSTAGE + w * (7 * 2048), 16);
            wg_fence();
#pragma unroll
            for (int b = 0; b < 7; b++) wgmma_n8_ta(ag + 4 * b, da + b * 128, db);
            next_stage(ks > 0);
            mbar_wait(sb + BAR_FULL + slot * 8, ph);
            da = make_desc(sb + slot * FSTAGE + w * (7 * 2048), 16);
            wg_fence();
#pragma unroll
            for (int b = 0; b < 7; b++) wgmma_n8_ta(au + 4 * b, da + b * 128, db);
            next_stage(true);
        }
        wg_wait<0>();
        reg_fence(ag);
        reg_fence(au);
        if ((lane & 3) == 0) {
#pragma unroll
            for (int i = 0; i < 28; i++) {
                const int f = (warp & 3) * 16 + (lane >> 2) + (i & 2) * 4, tok = i & 1;
                const float h = bf_round(silu_f(bf_round(ag[i]))) * bf_round(au[i]);
                *reinterpret_cast<__nv_bfloat16*>(smem + HB + (w * 7 + (i >> 2)) * 1024 + tok * 128 + (((f >> 3) ^ tok) << 4) + (f & 7) * 2) =
                    __float2bfloat16_rn(h);
            }
        }
    }
    fence_async_smem();
    bar_sync(1, 256);
    PROF(21, tid >> 7);
    {
        float ay[32];
#pragma unroll
        for (int i = 0; i < 32; i++) ay[i] = 0.f;
#pragma unroll 1
        for (int ks = 0; ks < FN2; ks++) {
            const uint64_t db = make_desc(sb + HB + (ks >> 2) * 1024 + (ks & 3) * 32, 16);
            mbar_wait(sb + BAR_FULL + slot * 8, ph);
            const uint64_t da = make_desc(sb + slot * FSTAGE + w * (8 * 2048), 16);
            wg_fence();
#pragma unroll
            for (int b = 0; b < 8; b++) wgmma_n8_ta(ay + 4 * b, da + b * 128, db);
            next_stage(true);
        }
        wg_wait<0>();
        reg_fence(ay);
        if ((lane & 3) == 0) {
#pragma unroll
            for (int i = 0; i < 32; i++)
                g_ypart[(s * 2 + (i & 1)) * DM + (w * 8 + (i >> 2)) * 64 + (warp & 3) * 16 + (lane >> 2) + (i & 2) * 4] = ay[i];
        }
    }
    PROF(23, tid >> 7);
    __threadfence();
    bar_sync(1, 256);
    if (tid == 0) {
        *flag = atomicAdd(&g_sync.ffn_ticket, 1u) == epoch * 4 + 3;
        __threadfence();
    }
    bar_sync(1, 256);
    if (*flag) {
        const float sg = bf_round(__fdividef(1.0f, 1.0f + __expf(-__ldcg(&g_r[row]))));
        const uint32_t xu[4] = {xrow.x, xrow.y, xrow.z, xrow.w};
        uint32_t o[4];
#pragma unroll
        for (int k = 0; k < 4; k++) {
            float y0 = 0.f, y1 = 0.f;
#pragma unroll
            for (int q = 0; q < 4; q++) {
                const float2 y = __ldcg(reinterpret_cast<const float2*>(&g_ypart[(q * 2 + w) * DM + ch * 8 + 2 * k]));
                y0 += y.x; y1 += y.y;
            }
            o[k] = pack_bf16(bf_lo(xu[k]) + bf_round(bf_round(y0) * sg), bf_hi(xu[k]) + bf_round(bf_round(y1) * sg));
        }
        g_routed[w * 128 + ch] = make_uint4(o[0], o[1], o[2], o[3]);
        if (ch == 0) g_sel[w] = row;
        bar_sync(1, 256);
        if (tid == 0) red_release(&g_sync.ffn_done);
    }
}

__device__ __forceinline__ uint32_t slab_addr(uint32_t stg, int lane, int s) {
    const int row = ((lane >> 3) & 1) * 8 + (lane & 7);
    const int chunk = 2 * (s & 3) + (lane >> 4);
    return stg + row * 128 + (s >> 2) * 8192 + ((chunk ^ (lane & 7)) << 4);
}

constexpr float SM_SCALE = 0.08838834764831845f * 1.4426950408889634f;
constexpr float SUM_HI = 1048576.f, SUM_LO = 1.0f / 1048576.f;

template <int I0, int I1, int J0>
__device__ __forceinline__ void mask_range(float (&S)[64], float limf) {
#pragma unroll
    for (int i = I0; i < I1; i++) {
        const int j = i >> 2;
        float t;
        asm("add.sat.f32 %0, %1, %2;" : "=f"(t) : "f"((float)(32 * (j >> 2) + 2 * (j & 3) + (i & 1) - (i & 2) * 4)), "f"(-limf));
        S[4 * J0 + i] = fmaf(t, -1e30f, S[4 * J0 + i]);
    }
}
template <int J0>
__device__ __forceinline__ void mask_half(float (&S)[64], float limf, int v) {
    asm volatile("" : "+f"(limf));
    if (v < 2) {
        mask_range<0, 16, J0>(S, limf);
#pragma unroll
        for (int i = 16; i < 32; i++) S[4 * J0 + i] = -1e30f;
    } else {
        mask_range<16, 32, J0>(S, limf);
    }
}
__device__ __forceinline__ void issue_qk(float (&S)[64], const uint32_t (&Q)[32], uint32_t d0) {
#pragma unroll
    for (int s = 0; s < 8; s++)
        wgmma_n128_rs<1>(S, Q[4 * s], Q[4 * s + 1], Q[4 * s + 2], Q[4 * s + 3], d0 + s * 128, s > 0);
}
template <int H>
__device__ __forceinline__ void issue_pv(float (&O)[64], const uint32_t (&Pm)[32], uint32_t d0, int acc) {
#pragma unroll
    for (int s = 4 * H; s < 4 * H + 4; s++)
        wgmma_n128_rs<0>(O, Pm[4 * s], Pm[4 * s + 1], Pm[4 * s + 2], Pm[4 * s + 3], d0 + H * (PAGE >> 4) + (s & 3) * 2, s > 0 ? 1 : acc);
}
template <int J0, int J1>
__device__ __forceinline__ void exp_groups(const float (&S)[64], uint32_t (&Pm)[32], float (&sum)[2]) {
#pragma unroll
    for (int i = 2 * J0; i < 2 * J1; i++) asm volatile("" : "+r"(Pm[i])::"memory");
#pragma unroll
    for (int j = J0; j < J1; j++) {
        const float e0 = ex2(S[4 * j]), e1 = ex2(S[4 * j + 1]), e2 = ex2(S[4 * j + 2]), e3 = ex2(S[4 * j + 3]);
        sum[0] = (j ? sum[0] + e0 : e0) + e1;
        sum[1] = (j ? sum[1] + e2 : e2) + e3;
        Pm[2 * j] = pack_bf16(e0, e1);
        Pm[2 * j + 1] = pack_bf16(e2, e3);
    }
}
__device__ __forceinline__ void shift_rows(float (&S)[64], float d0, float d1) {
#pragma unroll
    for (int j = 0; j < 16; j++) {
        S[4 * j] -= d0; S[4 * j + 1] -= d0; S[4 * j + 2] -= d1; S[4 * j + 3] -= d1;
    }
}
__device__ constexpr int chunk_src(int i) { return 4 * (4 * (i >> 3) + (i & 3)) + 2 * ((i >> 2) & 1); }
enum : uint32_t { CTL_FIRST = 1, CTL_SWITCH = 2, CTL_LAST = 4, CTL_HALF = 128, CTL_MASKHI = 256, CTL_WOUT = 512, CTL_PVHALF = 1024, CTL_PVACC = 16384,
                  CTL_SHIFT = 32768 };
__device__ __forceinline__ float quad_sum(float v) {
    v += __shfl_xor_sync(~0u, v, 1);
    return v + __shfl_xor_sync(~0u, v, 2);
}

__device__ __forceinline__ void store_part(uint8_t* base, uint32_t row_bits, int p, const uint32_t (&pk)[64], uint64_t pol) {
    asm volatile("{\n.reg .b64 d0, d1;\nxor.b64 d0, %0, %1;\nxor.b64 d1, d0, 64;\n"
                 "TS: .branchtargets P0, P1, P2, P3, P4, P5, P6, P7;\n"
                 "brx.idx.uni %2, TS;\n"
                 "P0:\n st.global.cg.L2::cache_hint.v4.u32 [d0 + 0], {%3, %4, %5, %6}, %67;\n st.global.cg.L2::cache_hint.v4.u32 [d1 + 0], {%11, %12, %13, %14}, %67;\n bra.uni DONE;\n"
                 "P1:\n st.global.cg.L2::cache_hint.v4.u32 [d0 + 0], {%7, %8, %9, %10}, %67;\n st.global.cg.L2::cache_hint.v4.u32 [d1 + 0], {%15, %16, %17, %18}, %67;\n bra.uni DONE;\n"
                 "P2:\n st.global.cg.L2::cache_hint.v4.u32 [d0 + 16384], {%19, %20, %21, %22}, %67;\n st.global.cg.L2::cache_hint.v4.u32 [d1 + 16384], {%27, %28, %29, %30}, %67;\n bra.uni DONE;\n"
                 "P3:\n st.global.cg.L2::cache_hint.v4.u32 [d0 + 16384], {%23, %24, %25, %26}, %67;\n st.global.cg.L2::cache_hint.v4.u32 [d1 + 16384], {%31, %32, %33, %34}, %67;\n bra.uni DONE;\n"
                 "P4:\n st.global.cg.L2::cache_hint.v4.u32 [d0 + 65536], {%35, %36, %37, %38}, %67;\n st.global.cg.L2::cache_hint.v4.u32 [d1 + 65536], {%43, %44, %45, %46}, %67;\n bra.uni DONE;\n"
                 "P5:\n st.global.cg.L2::cache_hint.v4.u32 [d0 + 65536], {%39, %40, %41, %42}, %67;\n st.global.cg.L2::cache_hint.v4.u32 [d1 + 65536], {%47, %48, %49, %50}, %67;\n bra.uni DONE;\n"
                 "P6:\n st.global.cg.L2::cache_hint.v4.u32 [d0 + 81920], {%51, %52, %53, %54}, %67;\n st.global.cg.L2::cache_hint.v4.u32 [d1 + 81920], {%59, %60, %61, %62}, %67;\n bra.uni DONE;\n"
                 "P7:\n st.global.cg.L2::cache_hint.v4.u32 [d0 + 81920], {%55, %56, %57, %58}, %67;\n st.global.cg.L2::cache_hint.v4.u32 [d1 + 81920], {%63, %64, %65, %66}, %67;\n bra.uni DONE;\n"
                 "DONE:\n}\n"
                 ::"l"(base), "l"((uint64_t)((p & 1) ? row_bits : 0)), "r"(p), "r"(pk[0]), "r"(pk[1]), "r"(pk[2]), "r"(pk[3]), "r"(pk[4]), "r"(pk[5]), "r"(pk[6]), "r"(pk[7]), "r"(pk[8]), "r"(pk[9]), "r"(pk[10]), "r"(pk[11]), "r"(pk[12]), "r"(pk[13]), "r"(pk[14]), "r"(pk[15]), "r"(pk[16]), "r"(pk[17]), "r"(pk[18]), "r"(pk[19]), "r"(pk[20]), "r"(pk[21]), "r"(pk[22]), "r"(pk[23]), "r"(pk[24]), "r"(pk[25]), "r"(pk[26]), "r"(pk[27]), "r"(pk[28]), "r"(pk[29]), "r"(pk[30]), "r"(pk[31]), "r"(pk[32]), "r"(pk[33]), "r"(pk[34]), "r"(pk[35]), "r"(pk[36]), "r"(pk[37]), "r"(pk[38]), "r"(pk[39]), "r"(pk[40]), "r"(pk[41]), "r"(pk[42]), "r"(pk[43]), "r"(pk[44]), "r"(pk[45]), "r"(pk[46]), "r"(pk[47]), "r"(pk[48]), "r"(pk[49]), "r"(pk[50]), "r"(pk[51]), "r"(pk[52]), "r"(pk[53]), "r"(pk[54]), "r"(pk[55]), "r"(pk[56]), "r"(pk[57]), "r"(pk[58]), "r"(pk[59]), "r"(pk[60]), "r"(pk[61]), "r"(pk[62]), "r"(pk[63]), "l"(pol)
                 : "memory");
}

__device__ __forceinline__ void consumer(uint32_t sb, int pair, int c, uint8_t* out, const uint8_t* x) {
    const int tid = threadIdx.x;
    const int warp = __shfl_sync(~0u, tid >> 5, 0);
    const int w = warp >> 2, v = warp & 3, lane = tid & 31;

    const uint32_t empty_rel = lane == 2 ? mapa(sb + BAR_EMPTYL, c) : mapa(sb + BAR_EMPTY, lane & 1);
    auto release = [&](uint32_t grp) {
        if (lane < 3) mbar_arrive_cluster(empty_rel + (grp & 7) * 8);
    };
    auto wait_full = [&](uint32_t grp) { mbar_wait(sb + BAR_FULL + (grp & 7) * 8, (grp >> 3) & 1); };

    uint32_t g = 0;
    const uint32_t stg = sb + SM_REGION + w * PAGE + v * 2048;
    const uint32_t chunk0 = (lane >> 2) * 128 + (((lane & 3) ^ (lane >> 2)) << 4);
    uint32_t ndone = 0;
    auto mark_done = [&]() {
        __syncwarp();
        if (lane == 0) mbar_arrive(sb + BAR_DONE + (ndone & 1) * 8);
        ndone++;
    };
    auto ctx_dst = [&](int rnd, int seg) {
        const int rb = query_rowblock(pair, c, w, seg);
        return ptr_off(g_ctx, ((rb >> 1) * 64 + (rnd * 16 + (pair >> 2)) * 2) * PAGE + (rb & 1) * 8192 + v * 2048);
    };

    uint32_t ctl_tab;
    {
        const int t = lane, firstB = 2 * attn_rowblock(pair, 0) + 2 - w;
        auto is_half = [&](int u) { return (u == firstB - 1 || u == 16) && c == (u >= firstB); };
        auto block = [&](int u) { return u + (w == 1 && u >= firstB); };
        auto place = [](int j) { return ((j & 15) << 3) | ((j - (j * 43 >> 8) * 6) << 11); };
        const int jv = min(2 * block(t - 1) + 2, 35), jk = t == 17 ? jv : max(2 * block(t) - 1, 0);
        const bool diag = t == firstB - 1 || t == 16;
        ctl_tab = ((t == 0 || t == firstB) ? CTL_FIRST : 0) | (t == firstB ? CTL_SWITCH : 0) | (t == 17 ? CTL_LAST : 0) |
                  (diag ? (is_half(t) ? CTL_HALF : CTL_MASKHI) : 0) | (t == firstB + 1 ? CTL_WOUT : 0) |
                  (is_half(t - 1) ? CTL_PVHALF : 0) | ((t == 1 || t == firstB + 1) ? 0 : CTL_PVACC) |
                  place(jk) | ((place(jv) | (t ? 3 : 0)) << 16);
    }

    uint32_t pk[64];
#pragma unroll
    for (int i = 0; i < 64; i++) pk[i] = 0;
    uint8_t* pend = nullptr;
    uint32_t prow = 0x400;
    auto write_part = [&](int p, uint64_t pol = POL_NORMAL) { store_part(pend, prow, p, pk, pol); };
    if (w == 1) bar_arrive(2, 256);

    for (int item = 0; item < 6; item++) {
        if ((0x1B >> item) & 1) {
            constexpr int nk = DC / 64;
            float acc[128];
            auto issue_kblock = [&](int first_acc) {
                wait_full(g);
                const uint32_t pg = sb + (g & 3) * (3 * PAGE);
                const uint64_t da = make_desc(pg + w * 8192, 16), db = make_desc(pg + PAGE, 16);
                wg_fence();
                wgmma_n256_ss(acc, da, db, first_acc);
                wgmma_n256_ss(acc, da + 128, db + 2, 1);
                wgmma_n256_ss(acc, da + 256, db + 4, 1);
                wgmma_n256_ss(acc, da + 384, db + 6, 1);
                wg_commit();
                g++;
            };
            if (item == 0) PROF(17, w);
            issue_kblock(0);
            if (item == 0) PROF(1, w);
            if (item == 0 && w == 0) PROF_GT(1);
            const int nparts = item == 0 ? 0 : (item == 3 ? 4 : 8);
            const int ln_row = (pair * 2 + c) * 16 + warp * 2;
            if (item == 0) {
                const uint8_t* src = ptr_off(x, ln_row * (DM * 2) + lane * 16);
#pragma unroll
                for (int i = 0; i < 8; i++) {
                    const uint4 t = __ldcg(reinterpret_cast<const uint4*>(src + i * 512));
                    pk[4 * i] = t.x; pk[4 * i + 1] = t.y; pk[4 * i + 2] = t.z; pk[4 * i + 3] = t.w;
                }
            }
#pragma unroll 1
            for (int kb = 1; kb < nk; kb++) {
                if (kb == nk - 1 && w == 1) bar_sync(4, 256);
                issue_kblock(1);
                if (kb == nk - 1 && w == 0) bar_arrive(4, 256);
                wg_wait<1>();
                release(g - 2);
                if (kb <= nparts) {
                    if (item == 4 && kb == 1) mbar_wait(sb + BAR_DEP + 16, 0);
                    write_part(kb - 1, item == 3 ? POL_FIRST : POL_NORMAL);
                    if (kb == nk - 1) write_part(nk - 1);
                    if (kb == nparts || kb == nk - 1) mark_done();
                }
                if (g <= 8) {
                    float s[2], q[2];
                    if (g == 4) {
                        ln_sums<0>(pk, s[0], q[0]);
                        pk[32] = __float_as_uint(s[0]); pk[33] = __float_as_uint(q[0]);
                    }
                    if (g == 5) {
                        ln_sums<16>(pk, s[1], q[1]);
                        pk[34] = __float_as_uint(s[1]); pk[35] = __float_as_uint(q[1]);
                    }
                    if (g == 6) {
#pragma unroll
                        for (int r = 0; r < 2; r++) { s[r] = __uint_as_float(pk[32 + 2 * r]); q[r] = __uint_as_float(pk[33 + 2 * r]); }
                        const bool hi = lane & 16, od = lane & 8;
                        float a = hi ? s[1] : s[0], b = hi ? q[1] : q[0];
                        a += __shfl_xor_sync(~0u, hi ? s[0] : s[1], 16);
                        b += __shfl_xor_sync(~0u, hi ? q[0] : q[1], 16);
                        float t = od ? b : a;
                        t += __shfl_xor_sync(~0u, od ? a : b, 8);
#pragma unroll
                        for (int o = 4; o; o >>= 1) t += __shfl_xor_sync(~0u, t, o);
#pragma unroll
                        for (int r = 0; r < 2; r++) {
                            s[r] = __shfl_sync(~0u, t, 16 * r);
                            q[r] = __shfl_sync(~0u, t, 16 * r + 8);
                        }
                        ln_finish(s[0], q[0], pk[36], pk[37], pk[38]);
                        ln_finish(s[1], q[1], pk[39], pk[40], pk[41]);
                    }
                    if (g == 7) ln_apply<0>(pk, pk[36], pk[37], pk[38], ptr_off(g_xn, image_offset(ln_row, lane)));
                    if (g == 8) {
                        ln_apply<16>(pk, pk[39], pk[40], pk[41], ptr_off(g_xn, image_offset(ln_row + 1, lane)));
                        mark_done();
                    }
                }
            }
            wg_wait<0>();
            reg_fence(acc);
            release(g - 1);
            PROF(2 + 2 * item, w);
            if (w == 0) PROF_GT(2 + 2 * item);
#pragma unroll
            for (int i = 0; i < 64; i++) pk[i] = pack_bf16(acc[chunk_src(i)], acc[chunk_src(i) + 1]);
            const uint32_t vrow = (v >> 1) * 32 + (lane >> 3) * 8 + (v & 1) * 4 + ((lane >> 2) & 1);
            pend = ptr_off(g_kv, ((kv_head(pair) + (item == 1 || item == 4 ? 8 : 0)) * 16 + kv_tokens(pair) * 2) * 65536 + w * 8192 +
                                     (c ? 32768 + vrow * 128 + (((lane & 3) ^ (vrow & 7)) << 4) : v * 2048 + chunk0));
            prow = c ? 0x120 : 0x400;
            PROF(3 + 2 * item, w);
            continue;
        }

        float O[64], S[64];
        auto issue_q = [&](int first_acc) {
            wait_full(g);
            const uint32_t pg = sb + (g & 3) * (3 * PAGE);
            const uint64_t da = make_desc(pg + w * 8192, 16), db = make_desc(pg + 2 * PAGE, 8192);
            const uint64_t dab = make_desc(pg + PAGE + (1 - w) * 8192, 16);
            wg_fence();
#pragma unroll
            for (int q = 0; q < 4; q++) wgmma_n128_ss(S, da + 2 * q, db + 128 * q, q ? 1 : first_acc);
            wg_commit();
#pragma unroll
            for (int q = 0; q < 4; q++) wgmma_n128_ss(O, dab + 2 * q, db + 128 * q, q ? 1 : first_acc);
            wg_commit();
            g++;
        };
        issue_q(0);
#pragma unroll 1
        for (int kb = 1; kb < DM / 64; kb++) {
            if (kb == DM / 64 - 2 && w == 1) bar_sync(4, 256);
            issue_q(1);
            if (kb == DM / 64 - 1 && w == 0) bar_arrive(4, 256);
            wg_wait<2>();
            release(g - 2);
            if (kb <= 8) {
                write_part(kb - 1);
                if (kb == 8) mark_done();
            }
        }
        uint32_t Q[32], Pm[32];
#pragma unroll
        for (int i = 0; i < 32; i++) Pm[i] = pk[i];
        float lim = (float)(v * 16 + (lane >> 2) - 8 * (lane & 3));
        float mc[2] = {0.f, 0.f}, l[2] = {0.f, 0.f}, scale[2] = {0.f, 0.f}, sum[2];
        uint32_t ctl = __shfl_sync(~0u, ctl_tab, 0), nxt = __shfl_sync(~0u, ctl_tab, 1);
        int t = 1;
        asm volatile("" : "+f"(lim), "+f"(mc[0]), "+f"(mc[1]), "+f"(l[0]), "+f"(l[1]), "+r"(ctl), "+r"(nxt), "+r"(t));
        wg_wait<1>();
        reg_fence(S);
#pragma unroll
        for (int i = 0; i < 32; i++) Q[i] = pack_bf16(S[2 * i] * SM_SCALE, S[2 * i + 1] * SM_SCALE);
        reg_fence(Q);
        wait_full(g);
        wg_wait<0>();
        reg_fence(O);
        release(g - 1);
        PROF(2 + 2 * item, w);
        if (w == 0) PROF_GT(2 + 2 * item);

        const uint32_t qaddr = stg + lane * 16;
        auto put_queries = [&](const float (&A)[64]) {
#pragma unroll
            for (int i = 0; i < 8; i++)
                sts128(qaddr + (i >> 2) * 8192 + (i & 3) * 512, pack_bf16(A[8 * i] * SM_SCALE, A[8 * i + 1] * SM_SCALE), pack_bf16(A[8 * i + 2] * SM_SCALE, A[8 * i + 3] * SM_SCALE),
                       pack_bf16(A[8 * i + 4] * SM_SCALE, A[8 * i + 5] * SM_SCALE), pack_bf16(A[8 * i + 6] * SM_SCALE, A[8 * i + 7] * SM_SCALE));
        };
        auto get_queries = [&]() {
#pragma unroll
            for (int i = 0; i < 8; i++) lds128(qaddr + (i >> 2) * 8192 + (i & 3) * 512, Q[4 * i], Q[4 * i + 1], Q[4 * i + 2], Q[4 * i + 3]);
        };
        const uint32_t kdesc0 = (uint32_t)make_desc(sb, PAGE), vdesc0 = (uint32_t)make_desc(sb, 16);
        auto wait_block = [&](uint32_t word) { mbar_wait(sb + BAR_FULL + (word & 56), (word >> 6) & 1); };
        auto write_out = [&](auto early) {
            uint8_t* dst = ctx_dst(item == 5, 0);
            uint8_t* d[2] = {ptr_off(dst, chunk0), ptr_off(dst, chunk0 ^ 64)};
#pragma unroll
            for (int i = early.value ? 0 : WN; i < (early.value ? WN : 8); i++) {
                const float sc = scale[i & 1];
                uint32_t q[4];
#pragma unroll
                for (int k = 0; k < 4; k++) q[k] = pack_bf16(O[chunk_src(4 * i + k)] * sc, O[chunk_src(4 * i + k) + 1] * sc);
                if (early.value && i > 0) {
#pragma unroll
                    for (int k = 0; k < 4; k++) O[4 * (i - 1) + k] = __uint_as_float(q[k]);
                }
                stg_hint(d[(i >> 1) & 1] + (i >> 2) * PAGE + (i & 1) * 1024, q[0], q[1], q[2], q[3], item == 2 ? POL_FIRST : POL_NORMAL);
            }
            if (!early.value) mark_done();
        };
        put_queries(O);
        bar_sync(2 + w, 256);
        wg_fence();
        issue_qk(S, Q, kdesc0);
        wg_commit();
        wg_fence();
        wg_commit();
        wg_commit();
        bar_arrive(3 - w, 256);
        for (;;) {
            const bool kready = mbar_try(sb + BAR_FULL + (nxt & 56), (nxt >> 6) & 1);
            wg_wait<2>();
            reg_fence(S);
            if (ctl & (CTL_HALF | CTL_MASKHI | CTL_SHIFT)) {
                if (ctl & CTL_HALF) mask_half<0>(S, lim, v);
                if (ctl & CTL_MASKHI) mask_half<8>(S, lim, v);
                if (ctl & CTL_SHIFT) shift_rows(S, mc[0], mc[1]);
            }
            float early[4 * EARLY];
#pragma unroll
            for (int j = 0; j < EARLY; j++) {
#pragma unroll
                for (int i = 4 * j; i < 4 * j + 4; i++) early[i] = ex2(S[i]);
                sum[0] = (j ? sum[0] + early[4 * j] : early[4 * j]) + early[4 * j + 1];
                sum[1] = (j ? sum[1] + early[4 * j + 2] : early[4 * j + 2]) + early[4 * j + 3];
            }
            const uint32_t tie = __float_as_uint(sum[0]) & __float_as_uint(sum[1]) & (ctl & 0x80000000u);
            if (lane < 3) mbar_arrive_cluster(empty_rel + tie + (ctl & 56));
            wg_wait<1>();
#pragma unroll
            for (int j = 0; j < EARLY; j++) {
                asm volatile("" : "+r"(Pm[2 * j]), "+r"(Pm[2 * j + 1])::"memory");
                Pm[2 * j] = pack_bf16(early[4 * j], early[4 * j + 1]);
                Pm[2 * j + 1] = pack_bf16(early[4 * j + 2], early[4 * j + 3]);
            }
            exp_groups<EARLY, 8>(S, Pm, sum);
            const bool half = ctl & CTL_HALF;
            if (!half) {
                wg_wait<0>();
                reg_fence(O);
                if (lane < ((ctl >> 16) & 3)) mbar_arrive_cluster(empty_rel + ((ctl >> 16) & 56));
                exp_groups<8, 16>(S, Pm, sum);
            } else {
                asm volatile("wgmma.wait_group.sync.aligned 0;\n" ::: "memory");
                reg_fence(O);
                if (lane < ((ctl >> 16) & 3)) asm volatile("mbarrier.arrive.shared::cluster.b64 _, [%0];\n" ::"r"(empty_rel + ((ctl >> 16) & 56)) : "memory");
            }
            const bool over = !(sum[0] + sum[1] <= SUM_HI);
            if (__any_sync(~0u, over || !kready) || (((ctl & CTL_FIRST) | (nxt & (CTL_SWITCH | CTL_LAST))) != 0)) {
                bool bad = __any_sync(~0u, over);
                if (!kready) wait_block(nxt);
                const bool first = ctl & CTL_FIRST;
                if (first) {
                    uint32_t b0 = __ballot_sync(~0u, sum[0] >= SUM_LO), b1 = __ballot_sync(~0u, sum[1] >= SUM_LO);
                    b0 |= b0 >> 1; b1 |= b1 >> 1;
                    b0 |= b0 >> 2; b1 |= b1 >> 2;
                    bad |= (b0 & b1 & 0x11111111u) != 0x11111111u;
                }
                if (bad) {
                    if (half) {
#pragma unroll
                        for (int i = 32; i < 64; i++) S[i] = -INFINITY;
                    }
                    float d0 = fmaxf(S[0], S[1]), d1 = fmaxf(S[2], S[3]);
#pragma unroll
                    for (int j = 1; j < 16; j++) {
                        d0 = fmaxf(d0, fmaxf(S[4 * j], S[4 * j + 1]));
                        d1 = fmaxf(d1, fmaxf(S[4 * j + 2], S[4 * j + 3]));
                    }
                    d0 = fmaxf(d0, __shfl_xor_sync(~0u, d0, 1));
                    d1 = fmaxf(d1, __shfl_xor_sync(~0u, d1, 1));
                    d0 = fmaxf(d0, __shfl_xor_sync(~0u, d0, 2));
                    d1 = fmaxf(d1, __shfl_xor_sync(~0u, d1, 2));
                    if (!first) {
                        d0 = fmaxf(d0, 0.f);
                        d1 = fmaxf(d1, 0.f);
                        const float a0 = ex2(-d0), a1 = ex2(-d1);
#pragma unroll
                        for (int j = 0; j < 16; j++) {
                            O[4 * j] *= a0; O[4 * j + 1] *= a0; O[4 * j + 2] *= a1; O[4 * j + 3] *= a1;
                        }
                        l[0] *= a0; l[1] *= a1;
                    }
                    mc[0] += d0; mc[1] += d1;
                    ctl_tab |= CTL_SHIFT;
                    nxt |= CTL_SHIFT;
                    shift_rows(S, d0, d1);
                    exp_groups<0, 16>(S, Pm, sum);
                }
                if (ctl & CTL_SWITCH) write_out(std::true_type());
                if (nxt & CTL_LAST) break;
                if (nxt & CTL_SWITCH) {
                    get_queries();
                    nxt &= ~CTL_SHIFT;
                    ctl_tab &= ~CTL_SHIFT;
                }
            }
            ctl = nxt;
            bar_sync(2 + w, 256);
            wg_fence();
            issue_qk(S, Q, kdesc0 + (ctl & 0x3800));
            wg_commit();
            l[0] += sum[0]; l[1] += sum[1];
            nxt = __shfl_sync(~0u, ctl_tab, ++t);
            if (ctl & (CTL_SWITCH | CTL_WOUT)) {
                if (ctl & CTL_SWITCH) {
                    scale[0] = rcp_approx(quad_sum(l[0]));
                    scale[1] = rcp_approx(quad_sum(l[1]));
                    l[0] = l[1] = mc[0] = mc[1] = 0.f;
                    if (w == 1) { release((ctl >> 3) - 2); release((ctl >> 3) + 1); }
                } else {
                    write_out(std::false_type());
                }
            }
            wait_block(ctl >> 16);
            const uint32_t vdesc = vdesc0 + ((ctl >> 16) & 0x3800);
            if (!(ctl & CTL_PVHALF)) {
                wg_fence();
                issue_pv<0>(O, Pm, vdesc, ctl & CTL_PVACC);
                wg_commit();
                issue_pv<1>(O, Pm, vdesc, 1);
                wg_commit();
            } else {
                wg_fence();
                issue_pv<0>(O, Pm, vdesc, ctl & CTL_PVACC);
                wg_commit();
                wg_commit();
            }
            bar_arrive(3 - w, 256);
        }
        g += 36;
        if (w == 0) release(g - 3);
        if (nxt & CTL_WOUT) write_out(std::false_type());
        const uint32_t vdesc = vdesc0 + (nxt & 0x3800);
        if (nxt & CTL_PVHALF) {
            wg_fence();
            issue_pv<0>(O, Pm, vdesc, nxt & CTL_PVACC);
            wg_commit();
        } else {
            wg_fence();
            issue_pv<0>(O, Pm, vdesc, nxt & CTL_PVACC);
            issue_pv<1>(O, Pm, vdesc, 1);
            wg_commit();
        }
        l[0] += sum[0]; l[1] += sum[1];
        ctl_tab = (ctl_tab & ~(0x00780078u | CTL_SHIFT)) | ((ctl_tab + 0x00200020u) & 0x00780078u);
        const float i0 = rcp_approx(quad_sum(l[0])), i1 = rcp_approx(quad_sum(l[1]));
        wg_wait<0>();
        reg_fence(O);
        if (w == 0) release(g - 2);
        release(g - 1);
#pragma unroll
        for (int i = 0; i < 32; i++) {
            const float sc = (i & 4) ? i1 : i0;
            pk[i] = pack_bf16(O[chunk_src(i)] * sc, O[chunk_src(i) + 1] * sc);
        }
        pend = ptr_off(ctx_dst(item == 5, 1), chunk0);
        prow = 0x400;
#pragma unroll
        for (int i = 32; i < 64; i++) pk[i] = 0;
        PROF(3 + 2 * item, w);
        if (w == 0) PROF_GT(3 + 2 * item);
    }

    float acc[64];
    uint32_t slot = 0;
    auto issue_out = [&](int first_acc) {
        wait_full(g);
        const uint64_t da = make_desc(sb + slot + w * 8192, 16), db = make_desc(sb + slot + PAGE, 8192);
        wg_fence();
#pragma unroll
        for (int q = 0; q < 4; q++) wgmma_n128_ss(acc, da + 2 * q, db + 128 * q, q ? 1 : first_acc);
        wg_commit();
        g++;
        slot = slot == SM_REGION - 2 * PAGE ? 0 : slot + 2 * PAGE;
    };
    issue_out(0);
#pragma unroll 1
    for (int kb = 1; kb < 64 - PEEL; kb++) {
        issue_out(1);
        wg_wait<1>();
        release(g - 2);
        if (kb <= 8 && !(kb & 1)) {
            write_part((kb >> 1) - 1);
            if (kb == 8) mark_done();
        }
        if (kb >= 32 - PEEL && ((kb + PEEL) & 3) == 2 * w) {
            uint32_t u0, u1, u2, u3;
            const uint32_t a = stg + ((kb + PEEL) & 16) * 512 + ((kb + PEEL) & 12) * 128 + lane * 16;
            mbar_wait(sb + BAR_G + w * 8, 0);
            lds128(a, u0, u1, u2, u3);
            sts128(a, pack_bf16(silu_f(bf_lo(u0)), silu_f(bf_hi(u0))), pack_bf16(silu_f(bf_lo(u1)), silu_f(bf_hi(u1))),
                   pack_bf16(silu_f(bf_lo(u2)), silu_f(bf_hi(u2))), pack_bf16(silu_f(bf_lo(u3)), silu_f(bf_hi(u3))));
        }
    }
    const uint32_t goff = (out_rows(pair) * 256 + c * 128 + w * 64 + v * 16 + (lane >> 3)) * (DM * 2) +
                          out_cols(pair) * 128 + (((lane & 7) ^ (lane >> 3)) << 4);
    uint32_t xr[32], gr[32];
    {
        const uint8_t* src[2] = {ptr_off(x, goff), ptr_off(x, goff ^ 64)};
#pragma unroll
        for (int i = 0; i < 8; i++) {
            const uint4 t = ldg_hint(src[i & 1] + (i & 3) * (4 * DM * 2) + (i >> 2) * 128, POL_FIRST);
            xr[4 * i] = t.x; xr[4 * i + 1] = t.y; xr[4 * i + 2] = t.z; xr[4 * i + 3] = t.w;
        }
    }
#pragma unroll 1
    for (int i = 0; i < PEEL; i++) {
        if (i == PEEL - STAG && w == 1) bar_sync(4, 256);
        issue_out(1);
        if (i == PEEL - 1 && w == 0) bar_arrive(4, 256);
        wg_wait<1>();
    }
    asm volatile("barrier.cluster.arrive.relaxed.aligned;" ::: "memory");
#pragma unroll
    for (int i = 0; i < 8; i++) lds128(stg + (i >> 2) * 8192 + (i & 3) * 512 + lane * 16, gr[4 * i], gr[4 * i + 1], gr[4 * i + 2], gr[4 * i + 3]);
    uint8_t* dst[2] = {ptr_off(out, goff), ptr_off(out, goff ^ 64)};
    __syncwarp();
    wg_wait<0>();
    reg_fence(acc);
    PROF(14, w);
    if (w == 0) PROF_GT(14);
#pragma unroll
    for (int s = 0; s < 8; s++)
        stmatrix_x4(slab_addr(stg, lane, s), pack_bf16(acc[8 * s], acc[8 * s + 1]), pack_bf16(acc[8 * s + 2], acc[8 * s + 3]),
                    pack_bf16(acc[8 * s + 4], acc[8 * s + 5]), pack_bf16(acc[8 * s + 6], acc[8 * s + 7]));
    __syncwarp();
    uint32_t o[32];
#pragma unroll
    for (int i = 0; i < 8; i++) lds128(stg + (i >> 2) * 8192 + (i & 3) * 512 + lane * 16, o[4 * i], o[4 * i + 1], o[4 * i + 2], o[4 * i + 3]);
#pragma unroll
    for (int i = 0; i < 8; i++) {
#pragma unroll
        for (int k = 0; k < 4; k++) xr[4 * i + k] = bf2_add(xr[4 * i + k], bf2_mul(o[4 * i + k], gr[4 * i + k]));
        __stcg(reinterpret_cast<uint4*>(dst[i & 1] + (i & 3) * (4 * DM * 2) + (i >> 2) * 128), make_uint4(xr[4 * i], xr[4 * i + 1], xr[4 * i + 2], xr[4 * i + 3]));
    }
    PROF(28, w);
}

__global__ void __cluster_dims__(2, 1, 1) __launch_bounds__(384, 1)
fused_kernel(const __grid_constant__ CUtensorMap m_ckv, const __grid_constant__ CUtensorMap m_wuk,
             const __grid_constant__ CUtensorMap m_wuv, const __grid_constant__ CUtensorMap m_wq,
             const __grid_constant__ CUtensorMap m_wo, const __grid_constant__ CUtensorMap m_gate,
             const __grid_constant__ CUtensorMap m_up, const __grid_constant__ CUtensorMap m_down, const Params P) {
    extern __shared__ __align__(1024) uint8_t smem[];
    const uint32_t sb = __shfl_sync(~0u, smem_u32(smem), 0);
    const int tid = threadIdx.x;
    const int cl = blockIdx.x >> 1, c = blockIdx.x & 1;
    const int pair = cl >= 64 ? cl : cl < 4 ? cl * 16 + 15 : cl < 36 ? ((cl - 4) >> 3) * 16 + ((cl - 4) & 7)
                                                                    : ((cl - 36) / 7) * 16 + 8 + (cl - 36) % 7;
    const bool starter = tid == 256 && pair < NMAIN / 2;
    const CUtensorMap* m_wu = c ? &m_wuv : &m_wuk;
    if (tid == 256) {
        mbar_init(sb + BAR_FULL, 1);
        if (starter) {
            asm volatile("fence.mbarrier_init.release.cluster;" ::: "memory");
            mbar_expect_tx(sb + BAR_FULL, 3 * PAGE);
            tma_3d(sb, m_wu, 0, 0, kv_head(pair) * 2, sb + BAR_FULL);
            tma_3d(sb + PAGE, &m_ckv, 0, kv_tokens(pair) * 256, 0, sb + BAR_FULL);
            tma_3d(sb + 2 * PAGE, &m_ckv, 0, kv_tokens(pair) * 256 + 128, 0, sb + BAR_FULL);
        }
#pragma unroll
        for (int i = 1; i < NBAR; i++) mbar_init(sb + SM_BAR + i * 8, (i >> 3) == 1 ? 16 : i >= 25 ? 8 : 1);
        asm volatile("fence.mbarrier_init.release.cluster;" ::: "memory");
    }
    if (starter) {
#pragma unroll 1
        for (int kb = 1; kb < 4; kb++) mbar_expect_tx(sb + BAR_FULL + kb * 8, 3 * PAGE);
        tma_3d(sb + 3 * PAGE, m_wu, 0, 64, kv_head(pair) * 2, sb + BAR_FULL + 8);
    }
    PROF(18, (tid >> 7) & 1);
    __syncthreads();
    cluster_sync();
    PROF(22, (tid >> 7) & 1);
    PROF(19, (tid >> 7) & 1);
    const int warp = __shfl_sync(~0u, tid >> 5, 0), lane = tid & 31;
    auto dump_prof = [&]() {
    };
    if (pair >= NMAIN / 2) {
        if (warp < 8) ffn_cta(smem, sb, blockIdx.x - NMAIN, __ldcg(&g_sync.done) / NCTA, P.w_r);
        else if (tid == 256) ffn_producer(sb, blockIdx.x - NMAIN, &m_gate, &m_up, &m_down);
        __syncwarp();
        PROF(29, tid >> 7);
        cluster_sync();
        if (tid == 0) atomicAdd(&g_sync.done, 1u);
        if (warp < 8) dump_prof();
    } else if (warp < 8) {
        asm volatile("setmaxnreg.inc.sync.aligned.u32 232;");
        consumer(sb, pair, c, P.out, (const uint8_t*)P.x);
        PROF(29, tid >> 7);
        asm volatile("barrier.cluster.wait.aligned;" ::: "memory");
        dump_prof();
    } else {
        asm volatile("setmaxnreg.dec.sync.aligned.u32 40;");
        if (starter) {
#pragma unroll 1
            for (int kb = 1; kb < 4; kb++) {
                if (kb > 1) tma_3d(sb + kb * (3 * PAGE), m_wu, 0, kb * 64, kv_head(pair) * 2, sb + BAR_FULL + kb * 8);
                tma_3d_mc(sb + kb * (3 * PAGE) + (1 + c) * PAGE, &m_ckv, 0, kv_tokens(pair) * 256 + c * 128, kb, sb + BAR_FULL + kb * 8);
            }
        }
        if (warp == 10) {
            sync_helper(sb, lane, pair, c);
        } else if (warp & 1) {
            fetch_helper((warp & 2) ? P.w_uv : P.w_uk, (const uint8_t*)P.x, sb, (warp >> 1) & 1, lane, pair, c);
        } else {
            producer(P, sb, pair, c, &m_ckv, m_wu, &m_wq, &m_wo);
        }
        bar_sync(6, 128);
        if (tid == 256) atomicAdd(&g_sync.done, 1u);
        cluster_sync();
    }
}

typedef CUresult (*EncodeFn)(CUtensorMap*, CUtensorMapDataType, cuuint32_t, void*, const cuuint64_t*, const cuuint64_t*,
                             const cuuint32_t*, const cuuint32_t*, CUtensorMapInterleave, CUtensorMapSwizzle,
                             CUtensorMapL2promotion, CUtensorMapFloatOOBfill);

void make_map_w(EncodeFn fn, CUtensorMap* m, const void* ptr, int rows, int cols, int blocks, int box_rows = 32) {
    cuuint64_t dims[3] = {64, (cuuint64_t)rows, (cuuint64_t)cols / 64};
    cuuint64_t strides[2] = {(cuuint64_t)cols * 2, 128};
    cuuint32_t box[3] = {64, (cuuint32_t)box_rows, (cuuint32_t)blocks};
    cuuint32_t es[3] = {1, 1, 1};
    fn(m, CU_TENSOR_MAP_DATA_TYPE_BFLOAT16, 3, const_cast<void*>(ptr), dims, strides, box, es, CU_TENSOR_MAP_INTERLEAVE_NONE,
       CU_TENSOR_MAP_SWIZZLE_128B, CU_TENSOR_MAP_L2_PROMOTION_L2_256B, CU_TENSOR_MAP_FLOAT_OOB_FILL_NONE);
}

}

extern "C" void kernel_launch(void* const* d_in, const int* in_sizes, int n_in, void* d_out, int out_size) {
    static EncodeFn fn = nullptr;
    if (!fn) {
        void* f = nullptr;
        cudaDriverEntryPointQueryResult qr;
        cudaGetDriverEntryPoint("cuTensorMapEncodeTiled", &f, cudaEnableDefault, &qr);
        fn = (EncodeFn)f;
        cudaFuncSetAttribute(fused_kernel, cudaFuncAttributeMaxDynamicSharedMemorySize, SMEM_BYTES);
    }
    CUtensorMap m_ckv, m_wuk, m_wuv, m_wq, m_wo, m_gate, m_up, m_down;
    make_map_w(fn, &m_gate, d_in[8], DM, FF, FS / 64, 16);
    make_map_w(fn, &m_up, d_in[9], DM, FF, FS / 64, 16);
    make_map_w(fn, &m_down, d_in[10], FF, DM, DM / 64, 16);
    make_map_w(fn, &m_ckv, d_in[1], SEQ, DC, 1, 128);
    make_map_w(fn, &m_wq, d_in[2], DM, NH * 128, 1, 64);
    make_map_w(fn, &m_wuk, d_in[3], DC, NH * 128, 2, 64);
    make_map_w(fn, &m_wuv, d_in[4], DC, NH * 128, 2, 64);
    make_map_w(fn, &m_wo, d_in[5], NH * 128, DM, 1, 64);
    Params P;
    P.x = (const __nv_bfloat16*)d_in[0];
    P.w_r = (const __nv_bfloat16*)d_in[7];
    P.c_kv = (const uint8_t*)d_in[1];
    P.w_uk = (const uint8_t*)d_in[3];
    P.w_uv = (const uint8_t*)d_in[4];
    P.out = (uint8_t*)d_out;
    fused_kernel<<<NCTA, 384, SMEM_BYTES>>>(m_ckv, m_wuk, m_wuv, m_wq, m_wo, m_gate, m_up, m_down, P);
}
```

```cpp
#include <cuda_runtime.h>
#include <cuda_bf16.h>
#include <cuda.h>
#include <stdint.h>
#include <type_traits>

namespace {

constexpr int SEQ = 2048, DM = 1024, NH = 32, DC = 512, FF = 3584;
constexpr int PAGE = 16384;
constexpr int NRING = 12;
constexpr int NCTA = 132, NMAIN = 128;
constexpr uint32_t SM_REGION = NRING * PAGE;
constexpr uint32_t SM_BAR = (NRING + 2) * PAGE;
constexpr uint32_t BAR_FULL = SM_BAR, BAR_EMPTY = SM_BAR + 64;
constexpr uint32_t BAR_DEP = SM_BAR + 128;
constexpr uint32_t BAR_G = SM_BAR + 184;
constexpr uint32_t BAR_DONE = SM_BAR + 200;
constexpr uint32_t BAR_EMPTYL = SM_BAR + 216;
constexpr int NBAR = 35;
constexpr uint32_t SM_PROF = SM_BAR + 320;
constexpr int SMEM_BYTES = SM_PROF + 512;
constexpr uint32_t SPIN_LIMIT = 1u << 16;
constexpr uint32_t POLL_MASK = 7;
constexpr int EARLY = 2;
constexpr int WN = 6;
constexpr int PEEL = 5, STAG = 3;

struct SyncBlock {
    unsigned done;       unsigned pad0[31];
    unsigned ln;         unsigned pad1[31];
    unsigned router;     unsigned pad4[31];
    unsigned ffn_ticket; unsigned pad2[31];
    unsigned ffn_done;   unsigned pad3[31];
    unsigned kv[NH * 8];
    unsigned kvfree[16 * 8];
    unsigned ctx[32 * NH];
};

__device__ __align__(1024) uint8_t g_xn[8 * 16 * 4 * 8192];
__device__ __align__(4096) uint8_t g_kv[16 * 16 * 65536];
__device__ __align__(4096) uint8_t g_ctx[16 * 64 * 16384];
__device__ __align__(16) uint4 g_routed[2 * 128];
__device__ int g_sel[2];
__device__ __align__(16) float g_r[SEQ];
__device__ __align__(16) float g_ypart[4 * 2 * DM];
__device__ SyncBlock g_sync;

__device__ __forceinline__ uint32_t smem_u32(const void* p) { return (uint32_t)__cvta_generic_to_shared(p); }

__device__ __forceinline__ void mbar_init(uint32_t bar, uint32_t count) {
    asm volatile("mbarrier.init.shared::cta.b64 [%0], %1;" ::"r"(bar), "r"(count) : "memory");
}
#define MBAR_WAIT_ASM(HINT, LIMIT)                                                                  \
    asm volatile("{\n.reg .pred p;\n.reg .u32 n;\nmov.u32 n, 0;\n"                                  \
                 "WAIT_LOOP:\n"                                                                     \
                 "mbarrier.try_wait.parity.shared::cta.b64 p, [%0], %1" HINT ";\n"                  \
                 "@p bra WAIT_DONE;\n"                                                              \
                 "add.u32 n, n, 1;\n"                                                               \
                 "setp.lt.u32 p, n, " LIMIT ";\n"                                                   \
                 "@p bra WAIT_LOOP;\n"                                                              \
                 "WAIT_DONE:\n}\n" ::"r"(bar), "r"(parity) : "memory")
__device__ __forceinline__ void mbar_wait(uint32_t bar, uint32_t parity) { MBAR_WAIT_ASM("", "131072"); }
__device__ __forceinline__ void mbar_sleep(uint32_t bar, uint32_t parity) { MBAR_WAIT_ASM(", 2000", "8192"); }
__device__ __forceinline__ bool mbar_try(uint32_t bar, uint32_t parity) {
    uint32_t ok;
    asm volatile("{\n.reg .pred p;\nmbarrier.try_wait.parity.shared::cta.b64 p, [%1], %2;\nselp.u32 %0, 1, 0, p;\n}\n"
                 : "=r"(ok) : "r"(bar), "r"(parity) : "memory");
    return ok;
}
__device__ __forceinline__ bool mbar_test(uint32_t bar, uint32_t parity) {
    uint32_t ok;
    asm volatile("{\n.reg .pred p;\nmbarrier.test_wait.parity.shared::cta.b64 p, [%1], %2;\nselp.u32 %0, 1, 0, p;\n}\n"
                 : "=r"(ok) : "r"(bar), "r"(parity) : "memory");
    return ok;
}
__device__ __forceinline__ bool elect_one() {
    uint32_t ok;
    asm volatile("{\n.reg .pred p;\nelect.sync _|p, 0xffffffff;\nselp.u32 %0, 1, 0, p;\n}\n" : "=r"(ok));
    return ok;
}
__device__ __forceinline__ void mbar_arrive(uint32_t bar) {
    asm volatile("mbarrier.arrive.shared::cta.b64 _, [%0];" ::"r"(bar) : "memory");
}
__device__ __forceinline__ void mbar_expect_tx(uint32_t bar, uint32_t bytes) {
    asm volatile("mbarrier.arrive.expect_tx.shared::cta.b64 _, [%0], %1;" ::"r"(bar), "r"(bytes) : "memory");
}
__device__ __forceinline__ void mbar_arrive_cluster(uint32_t cluster_addr) {
    asm volatile("mbarrier.arrive.shared::cluster.b64 _, [%0];" ::"r"(cluster_addr) : "memory");
}
__device__ __forceinline__ uint32_t mapa(uint32_t addr, uint32_t rank) {
    uint32_t r;
    asm("mapa.shared::cluster.u32 %0, %1, %2;" : "=r"(r) : "r"(addr), "r"(rank));
    return r;
}
__device__ __forceinline__ void tma_3d(uint32_t dst, const CUtensorMap* m, int c0, int c1, int c2, uint32_t bar) {
    asm volatile("cp.async.bulk.tensor.3d.shared::cluster.global.mbarrier::complete_tx::bytes [%0], [%1, {%3, %4, %5}], [%2];"
                 ::"r"(dst), "l"(m), "r"(bar), "r"(c0), "r"(c1), "r"(c2) : "memory");
}
__device__ __forceinline__ void tma_3d_hint(uint32_t dst, const CUtensorMap* m, int c0, int c1, int c2, uint32_t bar, uint64_t pol) {
    asm volatile("cp.async.bulk.tensor.3d.shared::cluster.global.mbarrier::complete_tx::bytes.L2::cache_hint [%0], [%1, {%3, %4, %5}], [%2], %6;"
                 ::"r"(dst), "l"(m), "r"(bar), "r"(c0), "r"(c1), "r"(c2), "l"(pol) : "memory");
}
__device__ __forceinline__ void tma_3d_mc(uint32_t dst, const CUtensorMap* m, int c0, int c1, int c2, uint32_t bar) {
    asm volatile("cp.async.bulk.tensor.3d.shared::cluster.global.mbarrier::complete_tx::bytes.multicast::cluster [%0], [%1, {%3, %4, %5}], [%2], %6;"
                 ::"r"(dst), "l"(m), "r"(bar), "r"(c0), "r"(c1), "r"(c2), "h"((uint16_t)3) : "memory");
}
__device__ __forceinline__ void bulk_load(uint32_t dst, const void* src, uint32_t bytes, uint32_t bar) {
    asm volatile("cp.async.bulk.shared::cluster.global.mbarrier::complete_tx::bytes [%0], [%1], %2, [%3];"
                 ::"r"(dst), "l"(src), "r"(bytes), "r"(bar) : "memory");
}
__device__ __forceinline__ void cp_async16(uint32_t dst, const void* src) {
    asm volatile("cp.async.cg.shared.global [%0], [%1], 16;" ::"r"(dst), "l"(src) : "memory");
}
__device__ __forceinline__ void bulk_load_mc(uint32_t dst, const void* src, uint32_t bytes, uint32_t bar) {
    asm volatile("cp.async.bulk.shared::cluster.global.mbarrier::complete_tx::bytes.multicast::cluster [%0], [%1], %2, [%3], %4;"
                 ::"r"(dst), "l"(src), "r"(bytes), "r"(bar), "h"((uint16_t)3) : "memory");
}
__device__ __forceinline__ void fence_async_smem() { asm volatile("fence.proxy.async.shared::cta;" ::: "memory"); }
__device__ __forceinline__ void prefetch_map(const CUtensorMap* m) {
    asm volatile("prefetch.tensormap [%0];" ::"l"(m) : "memory");
}
__device__ __forceinline__ void red_release(unsigned* p) {
    asm volatile("red.release.gpu.global.add.u32 [%0], 1;" ::"l"(p) : "memory");
}
__device__ __forceinline__ unsigned ld_relaxed(const unsigned* p) {
    unsigned v;
    asm volatile("ld.relaxed.gpu.global.u32 %0, [%1];" : "=r"(v) : "l"(p) : "memory");
    return v;
}
__device__ __forceinline__ void wait_counter(const unsigned* p, unsigned target) {
    for (uint32_t n = 0; (int)(ld_relaxed(p) - target) < 0 && n < SPIN_LIMIT; n++) __nanosleep(100);
    asm volatile("fence.acquire.gpu;" ::: "memory");
    asm volatile("fence.proxy.async.global;" ::: "memory");
}
__device__ __forceinline__ void bar_sync(int id, int n) { asm volatile("bar.sync %0, %1;" ::"r"(id), "r"(n) : "memory"); }
__device__ __forceinline__ void bar_arrive(int id, int n) { asm volatile("bar.arrive %0, %1;" ::"r"(id), "r"(n) : "memory"); }
__device__ __forceinline__ void cluster_sync() {
    asm volatile("barrier.cluster.arrive.relaxed.aligned;\nbarrier.cluster.wait.aligned;" ::: "memory");
}
__device__ __forceinline__ void wg_fence() { asm volatile("wgmma.fence.sync.aligned;" ::: "memory"); }
__device__ __forceinline__ void wg_commit() { asm volatile("wgmma.commit_group.sync.aligned;" ::: "memory"); }
template <int N> __device__ __forceinline__ void wg_wait() { asm volatile("wgmma.wait_group.sync.aligned %0;" ::"n"(N) : "memory"); }
template <int N> __device__ __forceinline__ void reg_fence(float (&a)[N]) {
#pragma unroll
    for (int i = 0; i < N; i++) asm volatile("" : "+f"(a[i])::"memory");
}
template <int N> __device__ __forceinline__ void reg_fence(uint32_t (&a)[N]) {
#pragma unroll
    for (int i = 0; i < N; i++) asm volatile("" : "+r"(a[i])::"memory");
}
__device__ __forceinline__ uint32_t pack_bf16(float lo, float hi) {
    uint32_t r;
    asm("cvt.rn.bf16x2.f32 %0, %1, %2;" : "=r"(r) : "f"(hi), "f"(lo));
    return r;
}
__device__ __forceinline__ float bf_lo(uint32_t v) { return __uint_as_float(v << 16); }
__device__ __forceinline__ float bf_hi(uint32_t v) { return __uint_as_float(v & 0xffff0000u); }
__device__ __forceinline__ float bf_round(float v) { return __bfloat162float(__float2bfloat16_rn(v)); }
__device__ __forceinline__ float ex2(float v) {
    float r;
    asm("ex2.approx.ftz.f32 %0, %1;" : "=f"(r) : "f"(v));
    return r;
}
__device__ __forceinline__ float sqrt_approx(float v) {
    float r;
    asm("sqrt.approx.ftz.f32 %0, %1;" : "=f"(r) : "f"(v));
    return r;
}
__device__ __forceinline__ float rcp_approx(float v) {
    float r;
    asm("rcp.approx.ftz.f32 %0, %1;" : "=f"(r) : "f"(v));
    return r;
}
__device__ __forceinline__ float silu_f(float v) { return v * rcp_approx(1.0f + ex2(v * -1.4426950408889634f)); }
__device__ __forceinline__ void stmatrix_x4(uint32_t addr, uint32_t r0, uint32_t r1, uint32_t r2, uint32_t r3) {
    asm volatile("stmatrix.sync.aligned.m8n8.x4.shared.b16 [%0], {%1, %2, %3, %4};"
                 ::"r"(addr), "r"(r0), "r"(r1), "r"(r2), "r"(r3) : "memory");
}
__device__ __forceinline__ void sts128(uint32_t addr, uint32_t r0, uint32_t r1, uint32_t r2, uint32_t r3) {
    asm volatile("st.shared.v4.b32 [%0], {%1, %2, %3, %4};" ::"r"(addr), "r"(r0), "r"(r1), "r"(r2), "r"(r3) : "memory");
}
__device__ __forceinline__ void lds128(uint32_t addr, uint32_t& r0, uint32_t& r1, uint32_t& r2, uint32_t& r3) {
    asm volatile("ld.shared.v4.b32 {%0, %1, %2, %3}, [%4];" : "=r"(r0), "=r"(r1), "=r"(r2), "=r"(r3) : "r"(addr) : "memory");
}
__device__ __forceinline__ uint32_t bf2_mul(uint32_t a, uint32_t b) {
    uint32_t r;
    asm("mul.rn.bf16x2 %0, %1, %2;" : "=r"(r) : "r"(a), "r"(b));
    return r;
}
__device__ __forceinline__ uint32_t bf2_add(uint32_t a, uint32_t b) {
    uint32_t r;
    asm("add.rn.bf16x2 %0, %1, %2;" : "=r"(r) : "r"(a), "r"(b));
    return r;
}
constexpr uint64_t POL_FIRST = 0x12F0000000000000ull, POL_NORMAL = 0x1000000000000000ull;
__device__ __forceinline__ uint4 ldg_hint(const void* p, uint64_t pol) {
    uint4 v;
    asm volatile("ld.global.cg.L2::cache_hint.v4.u32 {%0, %1, %2, %3}, [%4], %5;" : "=r"(v.x), "=r"(v.y), "=r"(v.z), "=r"(v.w) : "l"(p), "l"(pol));
    return v;
}
__device__ __forceinline__ void stg_hint(void* p, uint32_t r0, uint32_t r1, uint32_t r2, uint32_t r3, uint64_t pol) {
    asm volatile("st.global.cg.L2::cache_hint.v4.u32 [%0], {%1, %2, %3, %4}, %5;" ::"l"(p), "r"(r0), "r"(r1), "r"(r2), "r"(r3), "l"(pol) : "memory");
}

__device__ __forceinline__ uint64_t make_desc(uint32_t addr, uint32_t lbo_bytes) {
    return (uint64_t)((addr & 0x3FFFF) >> 4) | ((uint64_t)(lbo_bytes >> 4) << 16) | ((uint64_t)(1024 >> 4) << 32) | (1ull << 62);
}

__device__ __forceinline__ void wgmma_n256_ss(float (&d)[128], uint64_t da, uint64_t db, int acc) {
    asm volatile(
        "{\n.reg .pred p;\nsetp.ne.b32 p, %130, 0;\n"
        "wgmma.mma_async.sync.aligned.m64n256k16.f32.bf16.bf16 {"
        "%0, %1, %2, %3, %4, %5, %6, %7, %8, %9, %10, %11, %12, %13, %14, %15, "
        "%16, %17, %18, %19, %20, %21, %22, %23, %24, %25, %26, %27, %28, %29, %30, %31, "
        "%32, %33, %34, %35, %36, %37, %38, %39, %40, %41, %42, %43, %44, %45, %46, %47, "
        "%48, %49, %50, %51, %52, %53, %54, %55, %56, %57, %58, %59, %60, %61, %62, %63, "
        "%64, %65, %66, %67, %68, %69, %70, %71, %72, %73, %74, %75, %76, %77, %78, %79, "
        "%80, %81, %82, %83, %84, %85, %86, %87, %88, %89, %90, %91, %92, %93, %94, %95, "
        "%96, %97, %98, %99, %100, %101, %102, %103, %104, %105, %106, %107, %108, %109, %110, %111, "
        "%112, %113, %114, %115, %116, %117, %118, %119, %120, %121, %122, %123, %124, %125, %126, %127"
        "}, %128, %129, p, 1, 1, 1, 0;\n}\n"
        :
        "+f"(d[0]), "+f"(d[1]), "+f"(d[2]), "+f"(d[3]), "+f"(d[4]), "+f"(d[5]), "+f"(d[6]), "+f"(d[7]),
        "+f"(d[8]), "+f"(d[9]), "+f"(d[10]), "+f"(d[11]), "+f"(d[12]), "+f"(d[13]), "+f"(d[14]), "+f"(d[15]),
        "+f"(d[16]), "+f"(d[17]), "+f"(d[18]), "+f"(d[19]), "+f"(d[20]), "+f"(d[21]), "+f"(d[22]), "+f"(d[23]),
        "+f"(d[24]), "+f"(d[25]), "+f"(d[26]), "+f"(d[27]), "+f"(d[28]), "+f"(d[29]), "+f"(d[30]), "+f"(d[31]),
        "+f"(d[32]), "+f"(d[33]), "+f"(d[34]), "+f"(d[35]), "+f"(d[36]), "+f"(d[37]), "+f"(d[38]), "+f"(d[39]),
        "+f"(d[40]), "+f"(d[41]), "+f"(d[42]), "+f"(d[43]), "+f"(d[44]), "+f"(d[45]), "+f"(d[46]), "+f"(d[47]),
        "+f"(d[48]), "+f"(d[49]), "+f"(d[50]), "+f"(d[51]), "+f"(d[52]), "+f"(d[53]), "+f"(d[54]), "+f"(d[55]),
        "+f"(d[56]), "+f"(d[57]), "+f"(d[58]), "+f"(d[59]), "+f"(d[60]), "+f"(d[61]), "+f"(d[62]), "+f"(d[63]),
        "+f"(d[64]), "+f"(d[65]), "+f"(d[66]), "+f"(d[67]), "+f"(d[68]), "+f"(d[69]), "+f"(d[70]), "+f"(d[71]),
        "+f"(d[72]), "+f"(d[73]), "+f"(d[74]), "+f"(d[75]), "+f"(d[76]), "+f"(d[77]), "+f"(d[78]), "+f"(d[79]),
        "+f"(d[80]), "+f"(d[81]), "+f"(d[82]), "+f"(d[83]), "+f"(d[84]), "+f"(d[85]), "+f"(d[86]), "+f"(d[87]),
        "+f"(d[88]), "+f"(d[89]), "+f"(d[90]), "+f"(d[91]), "+f"(d[92]), "+f"(d[93]), "+f"(d[94]), "+f"(d[95]),
        "+f"(d[96]), "+f"(d[97]), "+f"(d[98]), "+f"(d[99]), "+f"(d[100]), "+f"(d[101]), "+f"(d[102]), "+f"(d[103]),
        "+f"(d[104]), "+f"(d[105]), "+f"(d[106]), "+f"(d[107]), "+f"(d[108]), "+f"(d[109]), "+f"(d[110]), "+f"(d[111]),
        "+f"(d[112]), "+f"(d[113]), "+f"(d[114]), "+f"(d[115]), "+f"(d[116]), "+f"(d[117]), "+f"(d[118]), "+f"(d[119]),
        "+f"(d[120]), "+f"(d[121]), "+f"(d[122]), "+f"(d[123]), "+f"(d[124]), "+f"(d[125]), "+f"(d[126]), "+f"(d[127])
        : "l"(da), "l"(db), "r"(acc));
}

__device__ __forceinline__ void wgmma_n192_ss(float* d, uint64_t da, uint64_t db, int acc) {
    asm volatile(
        "{\n.reg .pred p;\nsetp.ne.b32 p, %98, 0;\n"
        "wgmma.mma_async.sync.aligned.m64n192k16.f32.bf16.bf16 {"
        "%0, %1, %2, %3, %4, %5, %6, %7, %8, %9, %10, %11, %12, %13, %14, %15, "
        "%16, %17, %18, %19, %20, %21, %22, %23, %24, %25, %26, %27, %28, %29, %30, %31, "
        "%32, %33, %34, %35, %36, %37, %38, %39, %40, %41, %42, %43, %44, %45, %46, %47, "
        "%48, %49, %50, %51, %52, %53, %54, %55, %56, %57, %58, %59, %60, %61, %62, %63, "
        "%64, %65, %66, %67, %68, %69, %70, %71, %72, %73, %74, %75, %76, %77, %78, %79, "
        "%80, %81, %82, %83, %84, %85, %86, %87, %88, %89, %90, %91, %92, %93, %94, %95"
        "}, %96, %97, p, 1, 1, 1, 0;\n}\n"
        :
        "+f"(d[0]), "+f"(d[1]), "+f"(d[2]), "+f"(d[3]), "+f"(d[4]), "+f"(d[5]), "+f"(d[6]), "+f"(d[7]),
        "+f"(d[8]), "+f"(d[9]), "+f"(d[10]), "+f"(d[11]), "+f"(d[12]), "+f"(d[13]), "+f"(d[14]), "+f"(d[15]),
        "+f"(d[16]), "+f"(d[17]), "+f"(d[18]), "+f"(d[19]), "+f"(d[20]), "+f"(d[21]), "+f"(d[22]), "+f"(d[23]),
        "+f"(d[24]), "+f"(d[25]), "+f"(d[26]), "+f"(d[27]), "+f"(d[28]), "+f"(d[29]), "+f"(d[30]), "+f"(d[31]),
        "+f"(d[32]), "+f"(d[33]), "+f"(d[34]), "+f"(d[35]), "+f"(d[36]), "+f"(d[37]), "+f"(d[38]), "+f"(d[39]),
        "+f"(d[40]), "+f"(d[41]), "+f"(d[42]), "+f"(d[43]), "+f"(d[44]), "+f"(d[45]), "+f"(d[46]), "+f"(d[47]),
        "+f"(d[48]), "+f"(d[49]), "+f"(d[50]), "+f"(d[51]), "+f"(d[52]), "+f"(d[53]), "+f"(d[54]), "+f"(d[55]),
        "+f"(d[56]), "+f"(d[57]), "+f"(d[58]), "+f"(d[59]), "+f"(d[60]), "+f"(d[61]), "+f"(d[62]), "+f"(d[63]),
        "+f"(d[64]), "+f"(d[65]), "+f"(d[66]), "+f"(d[67]), "+f"(d[68]), "+f"(d[69]), "+f"(d[70]), "+f"(d[71]),
        "+f"(d[72]), "+f"(d[73]), "+f"(d[74]), "+f"(d[75]), "+f"(d[76]), "+f"(d[77]), "+f"(d[78]), "+f"(d[79]),
        "+f"(d[80]), "+f"(d[81]), "+f"(d[82]), "+f"(d[83]), "+f"(d[84]), "+f"(d[85]), "+f"(d[86]), "+f"(d[87]),
        "+f"(d[88]), "+f"(d[89]), "+f"(d[90]), "+f"(d[91]), "+f"(d[92]), "+f"(d[93]), "+f"(d[94]), "+f"(d[95])
        : "l"(da), "l"(db), "r"(acc));
}

__device__ __forceinline__ void wgmma_n64_rs_tb(float* d, uint32_t a0, uint32_t a1, uint32_t a2, uint32_t a3, uint32_t db, int acc) {
    asm volatile(
        "{\n.reg .pred p;\n.reg .b64 db;\nsetp.ne.b32 p, %37, 0;\nmov.b64 db, {%36, 0x40000040};\n"
        "wgmma.mma_async.sync.aligned.m64n64k16.f32.bf16.bf16 {"
        "%0, %1, %2, %3, %4, %5, %6, %7, %8, %9, %10, %11, %12, %13, %14, %15, "
        "%16, %17, %18, %19, %20, %21, %22, %23, %24, %25, %26, %27, %28, %29, %30, %31"
        "}, {%32, %33, %34, %35}, db, p, 1, 1, 1;\n}\n"
        :
        "+f"(d[0]), "+f"(d[1]), "+f"(d[2]), "+f"(d[3]), "+f"(d[4]), "+f"(d[5]), "+f"(d[6]), "+f"(d[7]),
        "+f"(d[8]), "+f"(d[9]), "+f"(d[10]), "+f"(d[11]), "+f"(d[12]), "+f"(d[13]), "+f"(d[14]), "+f"(d[15]),
        "+f"(d[16]), "+f"(d[17]), "+f"(d[18]), "+f"(d[19]), "+f"(d[20]), "+f"(d[21]), "+f"(d[22]), "+f"(d[23]),
        "+f"(d[24]), "+f"(d[25]), "+f"(d[26]), "+f"(d[27]), "+f"(d[28]), "+f"(d[29]), "+f"(d[30]), "+f"(d[31])
        : "r"(a0), "r"(a1), "r"(a2), "r"(a3), "r"(db), "r"(acc));
}

template <int TB>
__device__ __forceinline__ void wgmma_n128_rs(float (&d)[64], uint32_t a0, uint32_t a1, uint32_t a2, uint32_t a3, uint32_t db, int acc) {
    asm volatile(
        "{\n.reg .pred p;\n.reg .b64 db;\nsetp.ne.b32 p, %69, 0;\nmov.b64 db, {%68, 0x40000040};\n"
        "wgmma.mma_async.sync.aligned.m64n128k16.f32.bf16.bf16 {"
        "%0, %1, %2, %3, %4, %5, %6, %7, %8, %9, %10, %11, %12, %13, %14, %15, "
        "%16, %17, %18, %19, %20, %21, %22, %23, %24, %25, %26, %27, %28, %29, %30, %31, "
        "%32, %33, %34, %35, %36, %37, %38, %39, %40, %41, %42, %43, %44, %45, %46, %47, "
        "%48, %49, %50, %51, %52, %53, %54, %55, %56, %57, %58, %59, %60, %61, %62, %63"
        "}, {%64, %65, %66, %67}, db, p, 1, 1, %70;\n}\n"
        :
        "+f"(d[0]), "+f"(d[1]), "+f"(d[2]), "+f"(d[3]), "+f"(d[4]), "+f"(d[5]), "+f"(d[6]), "+f"(d[7]),
        "+f"(d[8]), "+f"(d[9]), "+f"(d[10]), "+f"(d[11]), "+f"(d[12]), "+f"(d[13]), "+f"(d[14]), "+f"(d[15]),
        "+f"(d[16]), "+f"(d[17]), "+f"(d[18]), "+f"(d[19]), "+f"(d[20]), "+f"(d[21]), "+f"(d[22]), "+f"(d[23]),
        "+f"(d[24]), "+f"(d[25]), "+f"(d[26]), "+f"(d[27]), "+f"(d[28]), "+f"(d[29]), "+f"(d[30]), "+f"(d[31]),
        "+f"(d[32]), "+f"(d[33]), "+f"(d[34]), "+f"(d[35]), "+f"(d[36]), "+f"(d[37]), "+f"(d[38]), "+f"(d[39]),
        "+f"(d[40]), "+f"(d[41]), "+f"(d[42]), "+f"(d[43]), "+f"(d[44]), "+f"(d[45]), "+f"(d[46]), "+f"(d[47]),
        "+f"(d[48]), "+f"(d[49]), "+f"(d[50]), "+f"(d[51]), "+f"(d[52]), "+f"(d[53]), "+f"(d[54]), "+f"(d[55]),
        "+f"(d[56]), "+f"(d[57]), "+f"(d[58]), "+f"(d[59]), "+f"(d[60]), "+f"(d[61]), "+f"(d[62]), "+f"(d[63])
        : "r"(a0), "r"(a1), "r"(a2), "r"(a3), "r"(db), "r"(acc), "n"(TB));
}

__device__ __forceinline__ void wgmma_n128_ss(float* d, uint64_t da, uint64_t db, int acc) {
    asm volatile(
        "{\n.reg .pred p;\nsetp.ne.b32 p, %66, 0;\n"
        "wgmma.mma_async.sync.aligned.m64n128k16.f32.bf16.bf16 {"
        "%0, %1, %2, %3, %4, %5, %6, %7, %8, %9, %10, %11, %12, %13, %14, %15, "
        "%16, %17, %18, %19, %20, %21, %22, %23, %24, %25, %26, %27, %28, %29, %30, %31, "
        "%32, %33, %34, %35, %36, %37, %38, %39, %40, %41, %42, %43, %44, %45, %46, %47, "
        "%48, %49, %50, %51, %52, %53, %54, %55, %56, %57, %58, %59, %60, %61, %62, %63"
        "}, %64, %65, p, 1, 1, 0, 1;\n}\n"
        :
        "+f"(d[0]), "+f"(d[1]), "+f"(d[2]), "+f"(d[3]), "+f"(d[4]), "+f"(d[5]), "+f"(d[6]), "+f"(d[7]),
        "+f"(d[8]), "+f"(d[9]), "+f"(d[10]), "+f"(d[11]), "+f"(d[12]), "+f"(d[13]), "+f"(d[14]), "+f"(d[15]),
        "+f"(d[16]), "+f"(d[17]), "+f"(d[18]), "+f"(d[19]), "+f"(d[20]), "+f"(d[21]), "+f"(d[22]), "+f"(d[23]),
        "+f"(d[24]), "+f"(d[25]), "+f"(d[26]), "+f"(d[27]), "+f"(d[28]), "+f"(d[29]), "+f"(d[30]), "+f"(d[31]),
        "+f"(d[32]), "+f"(d[33]), "+f"(d[34]), "+f"(d[35]), "+f"(d[36]), "+f"(d[37]), "+f"(d[38]), "+f"(d[39]),
        "+f"(d[40]), "+f"(d[41]), "+f"(d[42]), "+f"(d[43]), "+f"(d[44]), "+f"(d[45]), "+f"(d[46]), "+f"(d[47]),
        "+f"(d[48]), "+f"(d[49]), "+f"(d[50]), "+f"(d[51]), "+f"(d[52]), "+f"(d[53]), "+f"(d[54]), "+f"(d[55]),
        "+f"(d[56]), "+f"(d[57]), "+f"(d[58]), "+f"(d[59]), "+f"(d[60]), "+f"(d[61]), "+f"(d[62]), "+f"(d[63])
        : "l"(da), "l"(db), "r"(acc));
}

__device__ __forceinline__ void wgmma_n8_ta(float* d, uint64_t da, uint64_t db) {
    asm volatile("wgmma.mma_async.sync.aligned.m64n8k16.f32.bf16.bf16 {%0, %1, %2, %3}, %4, %5, 1, 1, 1, 1, 0;\n"
                 : "+f"(d[0]), "+f"(d[1]), "+f"(d[2]), "+f"(d[3]) : "l"(da), "l"(db));
}

#define PROF(slot, role)
#undef PROF_GT
#define PROF_GT(slot)

struct Params {
    const __nv_bfloat16* x;
    const __nv_bfloat16* w_r;
    const uint8_t *c_kv, *w_uk, *w_uv;
    uint8_t* out;
};
__device__ __forceinline__ void lsu_prefetch(const void* p) { asm volatile("prefetch.global.L2 [%0];" ::"l"(p) : "memory"); }

template <typename T>
__device__ __forceinline__ T* ptr_off(T* base, uint32_t off) {
    uint32_t lo, hi;
    asm("mov.b64 {%0, %1}, %2;" : "=r"(lo), "=r"(hi) : "l"(base));
    asm("add.cc.u32 %0, %0, %2;\naddc.u32 %1, %1, 0;" : "+r"(lo), "+r"(hi) : "r"(off));
    T* r;
    asm("mov.b64 %0, {%1, %2};" : "=l"(r) : "r"(lo), "r"(hi));
    return r;
}
__device__ __forceinline__ int kv_head(int pair) { return pair & 7; }
__device__ __forceinline__ int kv_tokens(int pair) { return ((pair >> 3) & 1) * 4 + (pair >> 4); }
__device__ __forceinline__ int out_rows(int pair) { return pair & 7; }
__device__ __forceinline__ int out_cols(int pair) { return (pair >> 4) * 4 + ((pair >> 3) & 1) * 2; }
__device__ __forceinline__ int attn_rowblock(int pair, int seg) {
    int j = pair & 3, hl = pair >> 2;
    return (((hl & 1) | (j == 0)) ^ seg) ? j : 7 - j;
}
__device__ __forceinline__ int outproj_head(int i, int ib) {
    if (i < 16) return i;
    return 16 + 2 * (i & 7) + ((ib < 4) ^ ((i >> 3) & 1));
}

__device__ __forceinline__ void pin_value(uint32_t& v) { asm volatile("" : "+r"(v)); }
__device__ __forceinline__ void pin_value(int& v) { asm volatile("" : "+r"(v)); }
__device__ __forceinline__ void pin_value(const uint8_t*& v) { asm volatile("" : "+l"(v)); }

__device__ __forceinline__ void producer(const Params& P, uint32_t sb, int pair, int c,
                                         const CUtensorMap* m_ckv, const CUtensorMap* m_wu,
                                         const CUtensorMap* m_wq, const CUtensorMap* m_wo) {
    const int hl = pair >> 2;
    const int ibA = attn_rowblock(pair, 0), nA = 2 * ibA + 2;
    const int ib = out_rows(pair), mi = 2 * ib + c, nb = out_cols(pair);
    const bool leader = elect_one();
    uint32_t g = 4, tail = 0;
    if (leader) prefetch_map(m_wq);
    auto wait_released = [&](uint32_t need) {
#pragma unroll 1
        for (; tail <= need; tail++) mbar_wait(sb + BAR_EMPTY + (tail & 7) * 8, (tail >> 3) & 1);
    };
    auto wait_released_here = [&](uint32_t need) {
#pragma unroll 1
        for (; tail < need; tail++) mbar_wait(sb + BAR_EMPTY + (tail & 7) * 8, (tail >> 3) & 1);
        if (tail == need) mbar_wait(sb + BAR_EMPTYL + (need & 7) * 8, (need >> 3) & 1);
    };
    auto wait_released_peer = [&](uint32_t need) {
        if (tail == need) {
            uint32_t eb = sb + BAR_EMPTY + (need & 7) * 8, ep = (need >> 3) & 1;
            tail++;
            mbar_wait(eb, ep);
        }
    };
    auto full_bar = [&]() { return sb + BAR_FULL + (g & 7) * 8; };
    auto pin = [](auto&... v) { (pin_value(v), ...); };
#pragma unroll 1
    for (int rnd = 0; rnd < 2; rnd++) {
#pragma unroll 1
        for (int i = rnd ? 0 : 4; i < 16; i++) {
            int kb = i & 7, h2 = (kv_head(pair) + (i & 8) + rnd * 16) * 2, krow = kb * 64;
            uint32_t pg = sb + (i & 3) * (3 * PAGE), pb = pg + (1 + c) * PAGE, bar = full_bar();
            pin(kb, h2, krow, pg, pb, bar);
            const uint32_t need = g - 4 - (i < 2);
            wait_released_here(need);
            if (leader) {
                mbar_expect_tx(bar, 3 * PAGE);
                tma_3d(pg, m_wu, 0, krow, h2, bar);
            }
            wait_released_peer(need);
            if (leader) {
                tma_3d_mc(pb, m_ckv, 0, kv_tokens(pair) * 256 + c * 128, kb, bar);
                if (rnd == 1 && i == 3) asm volatile("red.relaxed.gpu.global.add.u32 [%0], 1;" ::"l"(ptr_off(g_sync.kvfree, hl * 32)) : "memory");
            }
            g++;
        }
        mbar_sleep(sb + BAR_DEP, 0);
        const uint8_t* xa = ptr_off(g_xn, ibA * (16 * 32768) + c * PAGE);
        const uint8_t* xb = ptr_off(g_xn, (7 - ibA) * (16 * 32768) + (1 - c) * PAGE);
#pragma unroll 1
        for (int kb = 0; kb < DM / 64; kb++) {
            uint32_t pg = sb + (kb & 3) * (3 * PAGE), pw = pg + 2 * PAGE + c * 8192, bar = full_bar(), p2 = pg + PAGE;
            int krow = kb * 64;
            pin(pg, pw, p2, bar, krow);
            wait_released_here(g - 4);
            if (leader) {
                mbar_expect_tx(bar, 3 * PAGE);
                bulk_load(pg, xa, PAGE, bar);
            }
            wait_released_peer(g - 4);
            if (leader) {
                tma_3d_mc(pw, m_wq, 0, krow, (rnd * 16 + hl) * 2 + c, bar);
                bulk_load(p2, xb, PAGE, bar);
            }
            g++;
            xa += 32768;
            xb += 32768;
        }
        mbar_sleep(sb + BAR_DEP + 8 + rnd * 16, 0);
        if (rnd == 1 && leader) prefetch_map(m_wo);
        uint32_t pg = sb + c * PAGE;
#pragma unroll 1
        for (int j = 0; j < 36; j++) {
            const bool isk = j == 0 || ((j & 1) && j != 35);
            const int t = isk ? (j + 1) >> 1 : (j - 1) >> 1;
            const uint8_t* src = ptr_off(g_kv, (hl * 16 + (t >= nA ? t - nA : t)) * 65536 + (isk ? 0 : 32768) + c * PAGE);
            uint32_t bar = full_bar(), need = g - 6 + (j < 2) + (j < 5);
            pin(src, bar, need);
            wait_released(need);
            if (leader) {
                mbar_expect_tx(bar, 2 * PAGE);
                bulk_load_mc(pg, src, PAGE, bar);
            }
            g++;
            if (rnd == 0 && j >= 22 && j < 34) {
                const int cta = pair * 2 + c, i = j - 22;
                const uint32_t l = (threadIdx.x & 31) * 128;
                if (i < 8) lsu_prefetch(ptr_off(i & 1 ? P.w_uv : P.w_uk, cta * 32768 + (i >> 1) * 8192 + 4096 + l));
                else lsu_prefetch(ptr_off(P.c_kv, cta * 16384 + (i - 8) * 4096 + l));
            }
            pg = pg >= sb + SM_REGION - 2 * PAGE ? pg - (SM_REGION - 2 * PAGE) : pg + 2 * PAGE;
        }
    }
    uint32_t pg = sb;
#pragma unroll 1
    for (int i = 0; i < 64; i++) {
        if ((i & 15) == 0 && i != 16) mbar_sleep(sb + BAR_DEP + 32 + (i >> 1) - (i ? 8 : 0), 0);
        const int kb = outproj_head(i >> 1, ib) * 2 + (i & 1);
        const uint8_t* src = ptr_off(g_ctx, (mi * 64 + kb) * PAGE);
        uint32_t bar = full_bar(), pw = pg + PAGE + c * 8192;
        int krow = kb * 64;
        pin(src, bar, pw, krow);
        wait_released_here(g - 6);
        if (leader) {
            mbar_expect_tx(bar, 2 * PAGE);
            bulk_load(pg, src, PAGE, bar);
        }
        wait_released_peer(g - 6);
        if (leader) tma_3d_mc(pw, m_wo, 0, krow, nb + c, bar);
        g++;
        pg = pg == sb + SM_REGION - 2 * PAGE ? sb : pg + 2 * PAGE;
    }
}

__device__ __forceinline__ uint32_t xn_block(int row64, int kb) {
    return (((row64 >> 2) * 16 + kb) * 4 + ((row64 & 1) * 2 + (((row64 >> 1) & 1) ^ 1))) * 8192;
}
__device__ __forceinline__ uint32_t image_offset(int row, int ch) {
    return xn_block(row >> 6, ch >> 3) + (row & 63) * 128 + (((ch & 7) ^ (row & 7)) << 4);
}
__device__ __forceinline__ uint32_t bf2_sub(uint32_t a, uint32_t b) {
    uint32_t r;
    asm("sub.rn.bf16x2 %0, %1, %2;" : "=r"(r) : "r"(a), "r"(b));
    return r;
}
__device__ __forceinline__ uint32_t bf2_fma(uint32_t a, uint32_t b, uint32_t c) {
    uint32_t r;
    asm("fma.rn.bf16x2 %0, %1, %2, %3;" : "=r"(r) : "r"(a), "r"(b), "r"(c));
    return r;
}
template <int N0, int N>
__device__ __forceinline__ void ln_sums(const uint32_t (&u)[N], float& sum, float& sq) {
    float s0 = 0.f, s1 = 0.f, q0 = 0.f, q1 = 0.f;
#pragma unroll
    for (int k = N0; k < N0 + 16; k++) {
        const float a = bf_lo(u[k]), b = bf_hi(u[k]);
        s0 += a; s1 += b;
        q0 = fmaf(a, a, q0); q1 = fmaf(b, b, q1);
    }
    sum = s0 + s1;
    sq = q0 + q1;
}
__device__ __forceinline__ void ln_finish(float sum, float sq, uint32_t& mean2, uint32_t& rhi2, uint32_t& rlo2) {
    const float ms = sum * (1.0f / DM);
    const float var = fmaxf(fmaf(-ms, ms, sq * (1.0f / DM)), 0.f);
    const float rden = rcp_approx(bf_round(sqrt_approx(bf_round(bf_round(var) + 1e-5f))));
    const float rhi = bf_round(rden);
    mean2 = pack_bf16(ms, ms);
    rhi2 = pack_bf16(rhi, rhi);
    rlo2 = pack_bf16(rden - rhi, rden - rhi);
}
template <int N0, int N>
__device__ __forceinline__ void ln_apply(uint32_t (&u)[N], uint32_t mean2, uint32_t rhi2, uint32_t rlo2, uint8_t* dst) {
#pragma unroll
    for (int i = 0; i < 4; i++) {
        uint32_t o[4];
#pragma unroll
        for (int k = 0; k < 4; k++) {
            const uint32_t d = bf2_sub(u[N0 + 4 * i + k], mean2);
            o[k] = bf2_fma(d, rhi2, bf2_mul(d, rlo2));
        }
#pragma unroll
        for (int k = 0; k < 4; k++) u[N0 + 4 * i + k] = o[k];
        __stcg(reinterpret_cast<uint4*>(dst + i * 131072), make_uint4(o[0], o[1], o[2], o[3]));
    }
}
__device__ __forceinline__ int query_rowblock(int pair, int c, int w, int seg) {
    const int qA = (w ? 0 : 2) + c;
    return 4 * attn_rowblock(pair, seg) + (seg ? 3 - qA : qA);
}

__device__ __noinline__ void fetch_helper(const uint8_t* w_u, const uint8_t* x, uint32_t sb, int w, int lane, int pair, int c) {
    const uint32_t page = sb + SM_REGION + w * PAGE + lane * 16;
    mbar_sleep(sb + BAR_FULL + 5 * 8, 0);
#pragma unroll 1
    for (int i = 0; i < 2; i++) {
        lsu_prefetch(ptr_off(w_u, ((pair * 2 + c) * 4 + i * 2 + (lane >> 4)) * 8192 + 2048 + (lane & 15) * 128));
        __nanosleep(300);
    }
    const unsigned e1 = __ldcg(&g_sync.done) / NCTA + 1;
#pragma unroll 1
    for (int e = 1; e <= 7; e += 2) mbar_sleep(sb + BAR_DONE + 8, (e >> 1) & 1);
    const int rb = out_rows(pair) * 4 + c * 2 + w, kb0 = out_cols(pair);
    const uint8_t* src = ptr_off(g_xn, xn_block(rb, kb0) + lane * 16);
#pragma unroll 1
    for (int i = 0; i < 32; i += 4) {
#pragma unroll
        for (int k = 0; k < 4; k++) cp_async16(page + (i + k) * 512, src + (i + k) * 512 + (i >> 4) * (32768 - 8192));
        __nanosleep(200);
    }
#pragma unroll 1
    for (int i = 0; i < 4; i++) lsu_prefetch(ptr_off(x, (rb * 64 + i * 16 + (lane >> 1)) * (DM * 2) + kb0 * 128 + (lane & 1) * 128));
    wait_counter(&g_sync.ffn_done, e1);
    const int r = __ldcg(ptr_off(g_sel, (lane >> 4) * 4)) - rb * 64, ch = lane & 15;
    const uint4 t = __ldcg(ptr_off(g_routed, ((lane >> 4) * 128 + kb0 * 8 + ch) * 16));
    asm volatile("cp.async.wait_all;" ::: "memory");
    __syncwarp();
    if (r >= 0 && r < 64)
        sts128(sb + SM_REGION + w * PAGE + (ch >> 3) * 8192 + r * 128 + (((ch & 7) ^ (r & 7)) << 4), t.x, t.y, t.z, t.w);
    __syncwarp();
    if (lane == 0) mbar_arrive(sb + BAR_G + w * 8);
    PROF(20, 2);
}

__device__ __noinline__ void sync_helper(uint32_t sb, int lane, int pair, int c) {
    const unsigned e1 = __ldcg(&g_sync.done) / NCTA + 1;
    const int ib = out_rows(pair);
    int e = 0, b = 0;
#pragma unroll 1
    for (uint32_t n = 0; (e < 9 || b < 7) && n < SPIN_LIMIT; n++) {
        if (e < 9 && __all_sync(~0u, mbar_test(sb + BAR_DONE + (e & 1) * 8, (e >> 1) & 1))) {
            const int rnd = e > 4, ev = (e - 1) & 3;
            unsigned* flag = e == 0 ? &g_sync.ln
                           : ev < 2 ? ptr_off(g_sync.kv, (rnd * 16 + kv_head(pair) + 8 * ev) * 32)
                                    : ptr_off(g_sync.ctx, (query_rowblock(pair, c, lane & 1, ev & 1) * NH + rnd * 16 + (pair >> 2)) * 4);
            asm volatile("fence.proxy.async.global;\nfence.release.gpu;" ::: "memory");
            if (lane < ((e == 0 || ev < 2) ? 1 : 2)) asm volatile("red.relaxed.gpu.global.add.u32 [%0], 1;" ::"l"(flag) : "memory");
            PROF(10 + e, 2);
            e++;
        }
        if (b < 7 && e > 0 && (b < 4 || (n & POLL_MASK) == 0)) {
            const int i = b == 4 ? lane >> 1 : 8 * b - 24 + ((lane >> 1) & 7);
            const unsigned* cnt = b == 0 ? &g_sync.ln
                                : b == 2 ? ptr_off(g_sync.kvfree, (kv_head(pair) + 8 * (lane & 1)) * 32)
                                : b < 4 ? ptr_off(g_sync.kv, ((b >> 1) * 16 + (pair >> 2)) * 32)
                                        : ptr_off(g_sync.ctx, ((4 * ib + 2 * c + (lane & 1)) * NH + outproj_head(i & 31, ib)) * 4);
            if (__all_sync(~0u, (int)(ld_relaxed(cnt) - e1 * (b == 0 ? NMAIN : b == 2 ? 8 : b < 4 ? 16 : 1)) >= 0)) {
                asm volatile("fence.acquire.gpu;\nfence.proxy.async.global;" ::: "memory");
                __syncwarp();
                if (lane == 0) mbar_arrive(sb + BAR_DEP + b * 8);
                PROF(1 + b, 2);
                b++;
            }
        }
        __nanosleep(150);
    }
}

__device__ __forceinline__ unsigned long long block_max_key(unsigned long long k, unsigned long long* red, int tid) {
#pragma unroll
    for (int o = 16; o; o >>= 1) {
        unsigned long long t = __shfl_xor_sync(~0u, k, o);
        k = t > k ? t : k;
    }
    bar_sync(1, 256);
    if ((tid & 31) == 0) red[tid >> 5] = k;
    bar_sync(1, 256);
    k = red[0];
#pragma unroll
    for (int i = 1; i < 8; i++) k = red[i] > k ? red[i] : k;
    return k;
}

constexpr int FS = FF / 4;
constexpr int FSTAGE = 32768, FNST = 6;
constexpr int FN1 = 2 * (DM / 16), FN2 = FS / 16;

__device__ __forceinline__ void ffn_producer(uint32_t sb, int s, const CUtensorMap* m_gate, const CUtensorMap* m_up,
                                             const CUtensorMap* m_down) {
    wait_counter(&g_sync.ln, (__ldcg(&g_sync.done) / NCTA + 1) * NMAIN);
    int slot = 0, ph = 1;
#pragma unroll 1
    for (int st = 0; st < FN1 + FN2; st++) {
        mbar_sleep(sb + BAR_EMPTY + slot * 8, ph);
        const uint32_t bar = sb + BAR_FULL + slot * 8;
        const bool up = st < FN1;
        mbar_expect_tx(bar, up ? FS * 32 : DM * 32);
        tma_3d_hint(sb + slot * FSTAGE, up ? ((st & 1) ? m_up : m_gate) : m_down, 0,
                    up ? (st >> 1) * 16 : s * FS + (st - FN1) * 16, up ? s * (FS / 64) : 0, bar, POL_FIRST);
        if (++slot == FNST) { slot = 0; ph ^= 1; }
    }
}

__device__ __forceinline__ void ffn_cta(uint8_t* smem, uint32_t sb, int s, unsigned epoch, const __nv_bfloat16* w_r) {
    const int tid = threadIdx.x, lane = tid & 31;
    const int warp = __shfl_sync(~0u, tid >> 5, 0), w = warp >> 2;
    constexpr uint32_t XB = FNST * FSTAGE, HB = XB + 16384, AUX = HB + 14336;
    unsigned long long* red = reinterpret_cast<unsigned long long*>(smem + AUX);
    unsigned* flag = reinterpret_cast<unsigned*>(smem + AUX + 128);
    const unsigned e1 = epoch + 1;
    for (int i = tid; i < (16384 + 14336) / 16; i += 256) reinterpret_cast<uint4*>(smem + XB)[i] = make_uint4(0, 0, 0, 0);
    {
        float wf[32];
#pragma unroll
        for (int i = 0; i < 4; i++) {
            const uint4 t = __ldg(reinterpret_cast<const uint4*>(w_r) + lane + 32 * i);
            const uint32_t tu[4] = {t.x, t.y, t.z, t.w};
#pragma unroll
            for (int k = 0; k < 4; k++) { wf[8 * i + 2 * k] = bf_lo(tu[k]); wf[8 * i + 2 * k + 1] = bf_hi(tu[k]); }
        }
        if (tid == 0) wait_counter(&g_sync.ln, e1 * NMAIN);
        bar_sync(1, 256);
#pragma unroll 1
        for (int r0 = s * (SEQ / 4) + warp * (SEQ / 32); r0 < s * (SEQ / 4) + (warp + 1) * (SEQ / 32); r0 += 4) {
            uint4 t[4][4];
#pragma unroll
            for (int r = 0; r < 4; r++)
#pragma unroll
                for (int i = 0; i < 4; i++) t[r][i] = __ldcg(reinterpret_cast<const uint4*>(g_xn + image_offset(r0 + r, lane) + i * 131072));
            float acc[4];
#pragma unroll
            for (int r = 0; r < 4; r++) {
                float a = 0.f, b = 0.f;
#pragma unroll
                for (int i = 0; i < 4; i++) {
                    const uint32_t tu[4] = {t[r][i].x, t[r][i].y, t[r][i].z, t[r][i].w};
#pragma unroll
                    for (int k = 0; k < 4; k++) {
                        a = fmaf(bf_lo(tu[k]), wf[8 * i + 2 * k], a);
                        b = fmaf(bf_hi(tu[k]), wf[8 * i + 2 * k + 1], b);
                    }
                }
                acc[r] = a + b;
            }
#pragma unroll
            for (int o = 16; o; o >>= 1)
#pragma unroll
                for (int r = 0; r < 4; r++) acc[r] += __shfl_xor_sync(~0u, acc[r], o);
            if (lane < 4) __stcg(&g_r[r0 + lane], bf_round(lane == 0 ? acc[0] : lane == 1 ? acc[1] : lane == 2 ? acc[2] : acc[3]));
        }
        __threadfence();
        bar_sync(1, 256);
        if (tid == 0) {
            red_release(&g_sync.router);
            wait_counter(&g_sync.router, e1 * 4);
        }
        bar_sync(1, 256);
    }
    unsigned long long keys[8];
    unsigned long long best = 0;
#pragma unroll
    for (int i = 0; i < 8; i++) {
        int idx = tid + 256 * i;
        uint32_t b = __float_as_uint(__ldcg(&g_r[idx]) + 0.0f);
        b = (b & 0x80000000u) ? ~b : (b | 0x80000000u);
        keys[i] = ((unsigned long long)b << 32) | (unsigned)(SEQ - 1 - idx);
        best = keys[i] > best ? keys[i] : best;
    }
    const unsigned long long k0 = block_max_key(best, red, tid);
    best = 0;
#pragma unroll
    for (int i = 0; i < 8; i++) best = (keys[i] != k0 && keys[i] > best) ? keys[i] : best;
    const unsigned long long k1 = block_max_key(best, red, tid);
    const int row = SEQ - 1 - (int)((w ? k1 : k0) & 0xffffffffu);
    const int ch = tid & 127;
    const uint4 xrow = __ldcg(reinterpret_cast<const uint4*>(g_xn + image_offset(row, ch)));
    *reinterpret_cast<uint4*>(smem + XB + (ch >> 3) * 1024 + w * 128 + (((ch & 7) ^ w) << 4)) = xrow;
    fence_async_smem();
    bar_sync(1, 256);
    PROF(20, tid >> 7);
    int slot = 0, ph = 0, prev = 0;
    auto next_stage = [&](bool has_prev) {
        wg_commit();
        wg_wait<1>();
        if (has_prev && lane < 2) mbar_arrive(sb + BAR_EMPTY + prev * 8);
        prev = slot;
        if (++slot == FNST) { slot = 0; ph ^= 1; }
    };
    {
        float ag[28], au[28];
#pragma unroll
        for (int i = 0; i < 28; i++) ag[i] = au[i] = 0.f;
#pragma unroll 1
        for (int ks = 0; ks < DM / 16; ks++) {
            const uint64_t db = make_desc(sb + XB + (ks >> 2) * 1024 + (ks & 3) * 32, 16);
            mbar_wait(sb + BAR_FULL + slot * 8, ph);
            uint64_t da = make_desc(sb + slot * FSTAGE + w * (7 * 2048), 16);
            wg_fence();
#pragma unroll
            for (int b = 0; b < 7; b++) wgmma_n8_ta(ag + 4 * b, da + b * 128, db);
            next_stage(ks > 0);
            mbar_wait(sb + BAR_FULL + slot * 8, ph);
            da = make_desc(sb + slot * FSTAGE + w * (7 * 2048), 16);
            wg_fence();
#pragma unroll
            for (int b = 0; b < 7; b++) wgmma_n8_ta(au + 4 * b, da + b * 128, db);
            next_stage(true);
        }
        wg_wait<0>();
        reg_fence(ag);
        reg_fence(au);
        if ((lane & 3) == 0) {
#pragma unroll
            for (int i = 0; i < 28; i++) {
                const int f = (warp & 3) * 16 + (lane >> 2) + (i & 2) * 4, tok = i & 1;
                const float h = bf_round(silu_f(bf_round(ag[i]))) * bf_round(au[i]);
                *reinterpret_cast<__nv_bfloat16*>(smem + HB + (w * 7 + (i >> 2)) * 1024 + tok * 128 + (((f >> 3) ^ tok) << 4) + (f & 7) * 2) =
                    __float2bfloat16_rn(h);
            }
        }
    }
    fence_async_smem();
    bar_sync(1, 256);
    PROF(21, tid >> 7);
    {
        float ay[32];
#pragma unroll
        for (int i = 0; i < 32; i++) ay[i] = 0.f;
#pragma unroll 1
        for (int ks = 0; ks < FN2; ks++) {
            const uint64_t db = make_desc(sb + HB + (ks >> 2) * 1024 + (ks & 3) * 32, 16);
            mbar_wait(sb + BAR_FULL + slot * 8, ph);
            const uint64_t da = make_desc(sb + slot * FSTAGE + w * (8 * 2048), 16);
            wg_fence();
#pragma unroll
            for (int b = 0; b < 8; b++) wgmma_n8_ta(ay + 4 * b, da + b * 128, db);
            next_stage(true);
        }
        wg_wait<0>();
        reg_fence(ay);
        if ((lane & 3) == 0) {
#pragma unroll
            for (int i = 0; i < 32; i++)
                g_ypart[(s * 2 + (i & 1)) * DM + (w * 8 + (i >> 2)) * 64 + (warp & 3) * 16 + (lane >> 2) + (i & 2) * 4] = ay[i];
        }
    }
    PROF(23, tid >> 7);
    __threadfence();
    bar_sync(1, 256);
    if (tid == 0) {
        *flag = atomicAdd(&g_sync.ffn_ticket, 1u) == epoch * 4 + 3;
        __threadfence();
    }
    bar_sync(1, 256);
    if (*flag) {
        const float sg = bf_round(__fdividef(1.0f, 1.0f + __expf(-__ldcg(&g_r[row]))));
        const uint32_t xu[4] = {xrow.x, xrow.y, xrow.z, xrow.w};
        uint32_t o[4];
#pragma unroll
        for (int k = 0; k < 4; k++) {
            float y0 = 0.f, y1 = 0.f;
#pragma unroll
            for (int q = 0; q < 4; q++) {
                const float2 y = __ldcg(reinterpret_cast<const float2*>(&g_ypart[(q * 2 + w) * DM + ch * 8 + 2 * k]));
                y0 += y.x; y1 += y.y;
            }
            o[k] = pack_bf16(bf_lo(xu[k]) + bf_round(bf_round(y0) * sg), bf_hi(xu[k]) + bf_round(bf_round(y1) * sg));
        }
        g_routed[w * 128 + ch] = make_uint4(o[0], o[1], o[2], o[3]);
        if (ch == 0) g_sel[w] = row;
        bar_sync(1, 256);
        if (tid == 0) red_release(&g_sync.ffn_done);
    }
}

__device__ __forceinline__ uint32_t slab_addr(uint32_t stg, int lane, int s) {
    const int row = ((lane >> 3) & 1) * 8 + (lane & 7);
    const int chunk = 2 * (s & 3) + (lane >> 4);
    return stg + row * 128 + (s >> 2) * 8192 + ((chunk ^ (lane & 7)) << 4);
}

constexpr float SM_SCALE = 0.08838834764831845f * 1.4426950408889634f;
constexpr float SUM_HI = 1048576.f, SUM_LO = 1.0f / 1048576.f;

template <int I0, int I1, int J0>
__device__ __forceinline__ void mask_range(float (&S)[64], float limf) {
#pragma unroll
    for (int i = I0; i < I1; i++) {
        const int j = i >> 2;
        float t;
        asm("add.sat.f32 %0, %1, %2;" : "=f"(t) : "f"((float)(32 * (j >> 2) + 2 * (j & 3) + (i & 1) - (i & 2) * 4)), "f"(-limf));
        S[4 * J0 + i] = fmaf(t, -1e30f, S[4 * J0 + i]);
    }
}
template <int J0>
__device__ __forceinline__ void mask_half(float (&S)[64], float limf, int v) {
    asm volatile("" : "+f"(limf));
    if (v < 2) {
        mask_range<0, 16, J0>(S, limf);
#pragma unroll
        for (int i = 16; i < 32; i++) S[4 * J0 + i] = -1e30f;
    } else {
        mask_range<16, 32, J0>(S, limf);
    }
}
__device__ __forceinline__ void issue_qk(float (&S)[64], const uint32_t (&Q)[32], uint32_t d0) {
#pragma unroll
    for (int s = 0; s < 8; s++)
        wgmma_n128_rs<1>(S, Q[4 * s], Q[4 * s + 1], Q[4 * s + 2], Q[4 * s + 3], d0 + s * 128, s > 0);
}
__device__ __forceinline__ void issue_qk_half(float (&T)[32], const uint32_t (&Q)[32], uint32_t d0) {
#pragma unroll
    for (int s = 0; s < 8; s++) wgmma_n64_rs_tb(T, Q[4 * s], Q[4 * s + 1], Q[4 * s + 2], Q[4 * s + 3], d0 + s * 128, s > 0);
}
template <int H>
__device__ __forceinline__ void issue_pv(float (&O)[64], const uint32_t (&Pm)[32], uint32_t d0, int acc) {
#pragma unroll
    for (int s = 4 * H; s < 4 * H + 4; s++)
        wgmma_n128_rs<0>(O, Pm[4 * s], Pm[4 * s + 1], Pm[4 * s + 2], Pm[4 * s + 3], d0 + H * (PAGE >> 4) + (s & 3) * 2, s > 0 ? 1 : acc);
}
template <int J0, int J1>
__device__ __forceinline__ void exp_groups(const float (&S)[64], uint32_t (&Pm)[32], float (&sum)[2]) {
#pragma unroll
    for (int i = 2 * J0; i < 2 * J1; i++) asm volatile("" : "+r"(Pm[i])::"memory");
#pragma unroll
    for (int j = J0; j < J1; j++) {
        const float e0 = ex2(S[4 * j]), e1 = ex2(S[4 * j + 1]), e2 = ex2(S[4 * j + 2]), e3 = ex2(S[4 * j + 3]);
        sum[0] = (j ? sum[0] + e0 : e0) + e1;
        sum[1] = (j ? sum[1] + e2 : e2) + e3;
        Pm[2 * j] = pack_bf16(e0, e1);
        Pm[2 * j + 1] = pack_bf16(e2, e3);
    }
}
__device__ __forceinline__ void shift_rows(float (&S)[64], float d0, float d1) {
#pragma unroll
    for (int j = 0; j < 16; j++) {
        S[4 * j] -= d0; S[4 * j + 1] -= d0; S[4 * j + 2] -= d1; S[4 * j + 3] -= d1;
    }
}
__device__ constexpr int chunk_src(int i) { return 4 * (4 * (i >> 3) + (i & 3)) + 2 * ((i >> 2) & 1); }
enum : uint32_t { CTL_FIRST = 1, CTL_SWITCH = 2, CTL_LAST = 4, CTL_HALF = 128, CTL_MASKHI = 256, CTL_WOUT = 512, CTL_PVHALF = 1024, CTL_PVACC = 16384,
                  CTL_SHIFT = 32768 };
__device__ __forceinline__ float quad_sum(float v) {
    v += __shfl_xor_sync(~0u, v, 1);
    return v + __shfl_xor_sync(~0u, v, 2);
}

__device__ __forceinline__ void store_part(uint8_t* base, uint32_t row_bits, int p, const uint32_t (&pk)[64], uint64_t pol) {
    asm volatile("{\n.reg .b64 d0, d1;\nxor.b64 d0, %0, %1;\nxor.b64 d1, d0, 64;\n"
                 "TS: .branchtargets P0, P1, P2, P3, P4, P5, P6, P7;\n"
                 "brx.idx.uni %2, TS;\n"
                 "P0:\n st.global.cg.L2::cache_hint.v4.u32 [d0 + 0], {%3, %4, %5, %6}, %67;\n st.global.cg.L2::cache_hint.v4.u32 [d1 + 0], {%11, %12, %13, %14}, %67;\n bra.uni DONE;\n"
                 "P1:\n st.global.cg.L2::cache_hint.v4.u32 [d0 + 0], {%7, %8, %9, %10}, %67;\n st.global.cg.L2::cache_hint.v4.u32 [d1 + 0], {%15, %16, %17, %18}, %67;\n bra.uni DONE;\n"
                 "P2:\n st.global.cg.L2::cache_hint.v4.u32 [d0 + 16384], {%19, %20, %21, %22}, %67;\n st.global.cg.L2::cache_hint.v4.u32 [d1 + 16384], {%27, %28, %29, %30}, %67;\n bra.uni DONE;\n"
                 "P3:\n st.global.cg.L2::cache_hint.v4.u32 [d0 + 16384], {%23, %24, %25, %26}, %67;\n st.global.cg.L2::cache_hint.v4.u32 [d1 + 16384], {%31, %32, %33, %34}, %67;\n bra.uni DONE;\n"
                 "P4:\n st.global.cg.L2::cache_hint.v4.u32 [d0 + 65536], {%35, %36, %37, %38}, %67;\n st.global.cg.L2::cache_hint.v4.u32 [d1 + 65536], {%43, %44, %45, %46}, %67;\n bra.uni DONE;\n"
                 "P5:\n st.global.cg.L2::cache_hint.v4.u32 [d0 + 65536], {%39, %40, %41, %42}, %67;\n st.global.cg.L2::cache_hint.v4.u32 [d1 + 65536], {%47, %48, %49, %50}, %67;\n bra.uni DONE;\n"
                 "P6:\n st.global.cg.L2::cache_hint.v4.u32 [d0 + 81920], {%51, %52, %53, %54}, %67;\n st.global.cg.L2::cache_hint.v4.u32 [d1 + 81920], {%59, %60, %61, %62}, %67;\n bra.uni DONE;\n"
                 "P7:\n st.global.cg.L2::cache_hint.v4.u32 [d0 + 81920], {%55, %56, %57, %58}, %67;\n st.global.cg.L2::cache_hint.v4.u32 [d1 + 81920], {%63, %64, %65, %66}, %67;\n bra.uni DONE;\n"
                 "DONE:\n}\n"
                 ::"l"(base), "l"((uint64_t)((p & 1) ? row_bits : 0)), "r"(p), "r"(pk[0]), "r"(pk[1]), "r"(pk[2]), "r"(pk[3]), "r"(pk[4]), "r"(pk[5]), "r"(pk[6]), "r"(pk[7]), "r"(pk[8]), "r"(pk[9]), "r"(pk[10]), "r"(pk[11]), "r"(pk[12]), "r"(pk[13]), "r"(pk[14]), "r"(pk[15]), "r"(pk[16]), "r"(pk[17]), "r"(pk[18]), "r"(pk[19]), "r"(pk[20]), "r"(pk[21]), "r"(pk[22]), "r"(pk[23]), "r"(pk[24]), "r"(pk[25]), "r"(pk[26]), "r"(pk[27]), "r"(pk[28]), "r"(pk[29]), "r"(pk[30]), "r"(pk[31]), "r"(pk[32]), "r"(pk[33]), "r"(pk[34]), "r"(pk[35]), "r"(pk[36]), "r"(pk[37]), "r"(pk[38]), "r"(pk[39]), "r"(pk[40]), "r"(pk[41]), "r"(pk[42]), "r"(pk[43]), "r"(pk[44]), "r"(pk[45]), "r"(pk[46]), "r"(pk[47]), "r"(pk[48]), "r"(pk[49]), "r"(pk[50]), "r"(pk[51]), "r"(pk[52]), "r"(pk[53]), "r"(pk[54]), "r"(pk[55]), "r"(pk[56]), "r"(pk[57]), "r"(pk[58]), "r"(pk[59]), "r"(pk[60]), "r"(pk[61]), "r"(pk[62]), "r"(pk[63]), "l"(pol)
                 : "memory");
}

__device__ __forceinline__ void store_part4(uint8_t* d0, int p, const uint32_t (&pk)[64]) {
    asm volatile("{\n.reg .b64 d1;\nxor.b64 d1, %0, 64;\n"
                 "TS: .branchtargets P0, P1, P2, P3;\n"
                 "brx.idx.uni %1, TS;\n"
                 "P0:\n st.global.cg.v4.u32 [%0 + 0], {%2, %3, %4, %5};\n st.global.cg.v4.u32 [d1 + 0], {%10, %11, %12, %13};\n bra.uni DONE;\n"
                 "P1:\n st.global.cg.v4.u32 [%0 + 1024], {%6, %7, %8, %9};\n st.global.cg.v4.u32 [d1 + 1024], {%14, %15, %16, %17};\n bra.uni DONE;\n"
                 "P2:\n st.global.cg.v4.u32 [%0 + 16384], {%18, %19, %20, %21};\n st.global.cg.v4.u32 [d1 + 16384], {%26, %27, %28, %29};\n bra.uni DONE;\n"
                 "P3:\n st.global.cg.v4.u32 [%0 + 17408], {%22, %23, %24, %25};\n st.global.cg.v4.u32 [d1 + 17408], {%30, %31, %32, %33};\n bra.uni DONE;\n"
                 "DONE:\n}\n"
                 ::"l"(d0), "r"(p), "r"(pk[0]), "r"(pk[1]), "r"(pk[2]), "r"(pk[3]), "r"(pk[4]), "r"(pk[5]), "r"(pk[6]), "r"(pk[7]), "r"(pk[8]), "r"(pk[9]), "r"(pk[10]), "r"(pk[11]), "r"(pk[12]), "r"(pk[13]), "r"(pk[14]), "r"(pk[15]), "r"(pk[16]), "r"(pk[17]), "r"(pk[18]), "r"(pk[19]), "r"(pk[20]), "r"(pk[21]), "r"(pk[22]), "r"(pk[23]), "r"(pk[24]), "r"(pk[25]), "r"(pk[26]), "r"(pk[27]), "r"(pk[28]), "r"(pk[29]), "r"(pk[30]), "r"(pk[31])
                 : "memory");
}

__device__ __forceinline__ void consumer(uint32_t sb, int pair, int c, uint8_t* out, const uint8_t* x) {
    const int tid = threadIdx.x;
    const int warp = __shfl_sync(~0u, tid >> 5, 0);
    const int w = warp >> 2, v = warp & 3;
    const int lane = __shfl_sync(~0u, tid & 31, tid & 31);

    const uint32_t empty_rel = lane == 2 ? mapa(sb + BAR_EMPTYL, c) : mapa(sb + BAR_EMPTY, lane & 1);
    auto release = [&](uint32_t grp) {
        if (lane < 3) mbar_arrive_cluster(empty_rel + (grp & 7) * 8);
    };
    auto wait_full = [&](uint32_t grp) { mbar_wait(sb + BAR_FULL + (grp & 7) * 8, (grp >> 3) & 1); };

    uint32_t g = 0;
    const uint32_t stg = sb + SM_REGION + w * PAGE + v * 2048;
    const uint32_t chunk0 = (lane >> 2) * 128 + (((lane & 3) ^ (lane >> 2)) << 4);
    uint32_t ndone = 0;
    auto mark_done = [&]() {
        __syncwarp();
        if (lane == 0) mbar_arrive(sb + BAR_DONE + (ndone & 1) * 8);
        ndone++;
    };
    auto ctx_dst = [&](int rnd, int seg) {
        const int rb = query_rowblock(pair, c, w, seg);
        return ptr_off(g_ctx, ((rb >> 1) * 64 + (rnd * 16 + (pair >> 2)) * 2) * PAGE + (rb & 1) * 8192 + v * 2048);
    };

    uint32_t ctl_tab;
    {
        const int t = lane, firstB = 2 * attn_rowblock(pair, 0) + 2 - w;
        auto is_half = [&](int u) { return (u == firstB - 1 || u == 16) && c == (u >= firstB); };
        auto block = [&](int u) { return u + (w == 1 && u >= firstB); };
        auto place = [](int j) { return ((j & 15) << 3) | ((j - (j * 43 >> 8) * 6) << 11); };
        const int jv = min(2 * block(t - 1) + 2, 35), jk = t == 17 ? jv : max(2 * block(t) - 1, 0);
        const bool diag = t == firstB - 1 || t == 16;
        ctl_tab = ((t == 0 || t == firstB) ? CTL_FIRST : 0) | (t == firstB ? CTL_SWITCH : 0) | (t == 17 ? CTL_LAST : 0) |
                  (diag ? (is_half(t) ? CTL_HALF : CTL_MASKHI) : 0) | (t == firstB + 1 ? CTL_WOUT : 0) |
                  (is_half(t - 1) ? CTL_PVHALF : 0) | ((t == 1 || t == firstB + 1) ? 0 : CTL_PVACC) |
                  place(jk) | ((place(jv) | (t ? 3 : 0)) << 16);
    }

    uint32_t pk[64];
#pragma unroll
    for (int i = 0; i < 64; i++) pk[i] = 0;
    uint8_t* pend = nullptr;
    uint32_t prow = 0x400;
    auto write_part = [&](int p, uint64_t pol = POL_NORMAL) { store_part(pend, prow, p, pk, pol); };
    if (w == 1) bar_arrive(2, 256);

    for (int item = 0; item < 6; item++) {
        if ((0x1B >> item) & 1) {
            constexpr int nk = DC / 64;
            float acc[128];
            auto issue_kblock = [&](int first_acc) {
                wait_full(g);
                const uint32_t pg = sb + (g & 3) * (3 * PAGE);
                const uint64_t da = make_desc(pg + w * 8192, 16), db = make_desc(pg + PAGE, 16);
                wg_fence();
                wgmma_n256_ss(acc, da, db, first_acc);
                wgmma_n256_ss(acc, da + 128, db + 2, 1);
                wgmma_n256_ss(acc, da + 256, db + 4, 1);
                wgmma_n256_ss(acc, da + 384, db + 6, 1);
                wg_commit();
                g++;
            };
            if (item == 0) PROF(17, w);
            issue_kblock(0);
            if (item == 0) PROF(1, w);
            if (item == 0 && w == 0) PROF_GT(1);
            const int nparts = item == 0 ? 0 : (item == 3 ? 4 : 8);
            const int ln_row = (pair * 2 + c) * 16 + warp * 2;
            if (item == 0) {
                const uint8_t* src = ptr_off(x, ln_row * (DM * 2) + lane * 16);
#pragma unroll
                for (int i = 0; i < 8; i++) {
                    const uint4 t = __ldcg(reinterpret_cast<const uint4*>(src + i * 512));
                    pk[4 * i] = t.x; pk[4 * i + 1] = t.y; pk[4 * i + 2] = t.z; pk[4 * i + 3] = t.w;
                }
            }
#pragma unroll 1
            for (int kb = 1; kb < nk; kb++) {
                if (kb == nk - 1 && w == 1) bar_sync(4, 256);
                issue_kblock(1);
                if (kb == nk - 1 && w == 0) bar_arrive(4, 256);
                wg_wait<1>();
                release(g - 2);
                if (kb <= nparts) {
                    if (item == 4 && kb == 1) mbar_wait(sb + BAR_DEP + 16, 0);
                    write_part(kb - 1, item == 3 ? POL_FIRST : POL_NORMAL);
                    if (kb == nk - 1) write_part(nk - 1);
                    if (kb == nparts || kb == nk - 1) mark_done();
                }
                if (g <= 8) {
                    float s[2], q[2];
                    if (g == 4) {
                        ln_sums<0>(pk, s[0], q[0]);
                        pk[32] = __float_as_uint(s[0]); pk[33] = __float_as_uint(q[0]);
                    }
                    if (g == 5) {
                        ln_sums<16>(pk, s[1], q[1]);
                        pk[34] = __float_as_uint(s[1]); pk[35] = __float_as_uint(q[1]);
                    }
                    if (g == 6) {
#pragma unroll
                        for (int r = 0; r < 2; r++) { s[r] = __uint_as_float(pk[32 + 2 * r]); q[r] = __uint_as_float(pk[33 + 2 * r]); }
                        const bool hi = lane & 16, od = lane & 8;
                        float a = hi ? s[1] : s[0], b = hi ? q[1] : q[0];
                        a += __shfl_xor_sync(~0u, hi ? s[0] : s[1], 16);
                        b += __shfl_xor_sync(~0u, hi ? q[0] : q[1], 16);
                        float t = od ? b : a;
                        t += __shfl_xor_sync(~0u, od ? a : b, 8);
#pragma unroll
                        for (int o = 4; o; o >>= 1) t += __shfl_xor_sync(~0u, t, o);
#pragma unroll
                        for (int r = 0; r < 2; r++) {
                            s[r] = __shfl_sync(~0u, t, 16 * r);
                            q[r] = __shfl_sync(~0u, t, 16 * r + 8);
                        }
                        ln_finish(s[0], q[0], pk[36], pk[37], pk[38]);
                        ln_finish(s[1], q[1], pk[39], pk[40], pk[41]);
                    }
                    if (g == 7) ln_apply<0>(pk, pk[36], pk[37], pk[38], ptr_off(g_xn, image_offset(ln_row, lane)));
                    if (g == 8) {
                        ln_apply<16>(pk, pk[39], pk[40], pk[41], ptr_off(g_xn, image_offset(ln_row + 1, lane)));
                        mark_done();
                    }
                }
            }
            wg_wait<0>();
            reg_fence(acc);
            release(g - 1);
            PROF(2 + 2 * item, w);
            if (w == 0) PROF_GT(2 + 2 * item);
#pragma unroll
            for (int i = 0; i < 64; i++) pk[i] = pack_bf16(acc[chunk_src(i)], acc[chunk_src(i) + 1]);
            const uint32_t vrow = (v >> 1) * 32 + (lane >> 3) * 8 + (v & 1) * 4 + ((lane >> 2) & 1);
            pend = ptr_off(g_kv, ((kv_head(pair) + (item == 1 || item == 4 ? 8 : 0)) * 16 + kv_tokens(pair) * 2) * 65536 + w * 8192 +
                                     (c ? 32768 + vrow * 128 + (((lane & 3) ^ (vrow & 7)) << 4) : v * 2048 + chunk0));
            prow = c ? 0x120 : 0x400;
            PROF(3 + 2 * item, w);
            continue;
        }

        float O[64], S[64];
        auto issue_q = [&](int first_acc) {
            wait_full(g);
            const uint32_t pg = sb + (g & 3) * (3 * PAGE);
            const uint64_t da = make_desc(pg + w * 8192, 16), db = make_desc(pg + 2 * PAGE, 8192);
            const uint64_t dab = make_desc(pg + PAGE + (1 - w) * 8192, 16);
            wg_fence();
#pragma unroll
            for (int q = 0; q < 4; q++) wgmma_n128_ss(S, da + 2 * q, db + 128 * q, q ? 1 : first_acc);
            wg_commit();
#pragma unroll
            for (int q = 0; q < 4; q++) wgmma_n128_ss(O, dab + 2 * q, db + 128 * q, q ? 1 : first_acc);
            wg_commit();
            g++;
        };
        issue_q(0);
#pragma unroll 1
        for (int kb = 1; kb < DM / 64; kb++) {
            if (kb == DM / 64 - 2 && w == 1) bar_sync(4, 256);
            issue_q(1);
            if (kb == DM / 64 - 1 && w == 0) bar_arrive(4, 256);
            wg_wait<2>();
            release(g - 2);
            if (kb <= 8) {
                write_part(kb - 1);
                if (kb == 8) mark_done();
            }
        }
        uint32_t Q[32], Pm[32];
#pragma unroll
        for (int i = 0; i < 32; i++) Pm[i] = pk[i];
        float lim = (float)(v * 16 + (lane >> 2) - 8 * (lane & 3));
        float mc[2] = {0.f, 0.f}, l[2] = {0.f, 0.f}, scale[2] = {0.f, 0.f}, sum[2];
        uint32_t ctl = __shfl_sync(~0u, ctl_tab, 0), nxt = __shfl_sync(~0u, ctl_tab, 1);
        int t = 1;
        asm volatile("" : "+f"(lim), "+f"(mc[0]), "+f"(mc[1]), "+f"(l[0]), "+f"(l[1]), "+r"(ctl), "+r"(nxt), "+r"(t));
        wg_wait<1>();
        reg_fence(S);
#pragma unroll
        for (int i = 0; i < 32; i++) Q[i] = pack_bf16(S[2 * i] * SM_SCALE, S[2 * i + 1] * SM_SCALE);
        reg_fence(Q);
        wait_full(g);
        wg_wait<0>();
        reg_fence(O);
        release(g - 1);
        PROF(2 + 2 * item, w);
        if (w == 0) PROF_GT(2 + 2 * item);

        const uint32_t qaddr = stg + lane * 16;
        auto put_queries = [&](const float (&A)[64]) {
#pragma unroll
            for (int i = 0; i < 8; i++)
                sts128(qaddr + (i >> 2) * 8192 + (i & 3) * 512, pack_bf16(A[8 * i] * SM_SCALE, A[8 * i + 1] * SM_SCALE), pack_bf16(A[8 * i + 2] * SM_SCALE, A[8 * i + 3] * SM_SCALE),
                       pack_bf16(A[8 * i + 4] * SM_SCALE, A[8 * i + 5] * SM_SCALE), pack_bf16(A[8 * i + 6] * SM_SCALE, A[8 * i + 7] * SM_SCALE));
        };
        auto get_queries = [&]() {
#pragma unroll
            for (int i = 0; i < 8; i++) lds128(qaddr + (i >> 2) * 8192 + (i & 3) * 512, Q[4 * i], Q[4 * i + 1], Q[4 * i + 2], Q[4 * i + 3]);
        };
        const uint32_t kdesc0 = (uint32_t)make_desc(sb, PAGE), vdesc0 = (uint32_t)make_desc(sb, 16);
        auto wait_block = [&](uint32_t word) { mbar_wait(sb + BAR_FULL + (word & 56), (word >> 6) & 1); };
        auto write_out = [&](auto early) {
            uint8_t* dst = ctx_dst(item == 5, 0);
            uint8_t* d[2] = {ptr_off(dst, chunk0), ptr_off(dst, chunk0 ^ 64)};
#pragma unroll
            for (int i = early.value ? 0 : WN; i < (early.value ? WN : 8); i++) {
                const float sc = scale[i & 1];
                uint32_t q[4];
#pragma unroll
                for (int k = 0; k < 4; k++) q[k] = pack_bf16(O[chunk_src(4 * i + k)] * sc, O[chunk_src(4 * i + k) + 1] * sc);
                if (early.value && i > 0) {
#pragma unroll
                    for (int k = 0; k < 4; k++) O[4 * (i - 1) + k] = __uint_as_float(q[k]);
                }
                stg_hint(d[(i >> 1) & 1] + (i >> 2) * PAGE + (i & 1) * 1024, q[0], q[1], q[2], q[3], item == 2 ? POL_FIRST : POL_NORMAL);
            }
            if (!early.value) mark_done();
        };
        put_queries(O);
        bar_sync(2 + w, 256);
        if (!(ctl & CTL_HALF)) {
            wg_fence();
            issue_qk(S, Q, kdesc0);
            wg_commit();
            wg_fence();
            wg_commit();
            wg_commit();
            bar_arrive(3 - w, 256);
            wg_wait<2>();
            reg_fence(S);
        } else {
            float T[32];
            wg_fence();
            issue_qk_half(T, Q, kdesc0);
            wg_commit();
            wg_fence();
            wg_commit();
            wg_commit();
            bar_arrive(3 - w, 256);
            wg_wait<2>();
            reg_fence(T);
#pragma unroll
            for (int i = 0; i < 32; i++) S[i] = T[i];
        }
        for (;;) {
            const bool kready = mbar_try(sb + BAR_FULL + (nxt & 56), (nxt >> 6) & 1);
            if (ctl & (CTL_HALF | CTL_MASKHI | CTL_SHIFT)) {
                if (ctl & CTL_HALF) mask_half<0>(S, lim, v);
                if (ctl & CTL_MASKHI) mask_half<8>(S, lim, v);
                if (ctl & CTL_SHIFT) shift_rows(S, mc[0], mc[1]);
            }
            float early[4 * EARLY];
#pragma unroll
            for (int j = 0; j < EARLY; j++) {
#pragma unroll
                for (int i = 4 * j; i < 4 * j + 4; i++) early[i] = ex2(S[i]);
                sum[0] = (j ? sum[0] + early[4 * j] : early[4 * j]) + early[4 * j + 1];
                sum[1] = (j ? sum[1] + early[4 * j + 2] : early[4 * j + 2]) + early[4 * j + 3];
            }
            const uint32_t tie = __float_as_uint(sum[0]) & __float_as_uint(sum[1]) & (ctl & 0x80000000u);
            if (lane < 3) mbar_arrive_cluster(empty_rel + tie + (ctl & 56));
            wg_wait<1>();
#pragma unroll
            for (int j = 0; j < EARLY; j++) {
                asm volatile("" : "+r"(Pm[2 * j]), "+r"(Pm[2 * j + 1])::"memory");
                Pm[2 * j] = pack_bf16(early[4 * j], early[4 * j + 1]);
                Pm[2 * j + 1] = pack_bf16(early[4 * j + 2], early[4 * j + 3]);
            }
            exp_groups<EARLY, 8>(S, Pm, sum);
            const bool half = ctl & CTL_HALF;
            if (!half) {
                wg_wait<0>();
                reg_fence(O);
                if (lane < ((ctl >> 16) & 3)) mbar_arrive_cluster(empty_rel + ((ctl >> 16) & 56));
                exp_groups<8, 16>(S, Pm, sum);
            } else {
                asm volatile("wgmma.wait_group.sync.aligned 0;\n" ::: "memory");
                reg_fence(O);
                if (lane < ((ctl >> 16) & 3)) asm volatile("mbarrier.arrive.shared::cluster.b64 _, [%0];\n" ::"r"(empty_rel + ((ctl >> 16) & 56)) : "memory");
            }
            const bool over = !(sum[0] + sum[1] <= SUM_HI);
            if (__any_sync(~0u, over || !kready) || (((ctl & CTL_FIRST) | (nxt & (CTL_SWITCH | CTL_LAST | CTL_HALF))) != 0)) {
                bool bad = __any_sync(~0u, over);
                if (!kready) wait_block(nxt);
                const bool first = ctl & CTL_FIRST;
                if (first) {
                    uint32_t b0 = __ballot_sync(~0u, sum[0] >= SUM_LO), b1 = __ballot_sync(~0u, sum[1] >= SUM_LO);
                    b0 |= b0 >> 1; b1 |= b1 >> 1;
                    b0 |= b0 >> 2; b1 |= b1 >> 2;
                    bad |= (b0 & b1 & 0x11111111u) != 0x11111111u;
                }
                if (bad) {
                    float d0 = fmaxf(S[0], S[1]), d1 = fmaxf(S[2], S[3]);
#pragma unroll
                    for (int j = 1; j < 8; j++) {
                        d0 = fmaxf(d0, fmaxf(S[4 * j], S[4 * j + 1]));
                        d1 = fmaxf(d1, fmaxf(S[4 * j + 2], S[4 * j + 3]));
                    }
                    if (!half) {
#pragma unroll
                        for (int j = 8; j < 16; j++) {
                            d0 = fmaxf(d0, fmaxf(S[4 * j], S[4 * j + 1]));
                            d1 = fmaxf(d1, fmaxf(S[4 * j + 2], S[4 * j + 3]));
                        }
                    }
                    d0 = fmaxf(d0, __shfl_xor_sync(~0u, d0, 1));
                    d1 = fmaxf(d1, __shfl_xor_sync(~0u, d1, 1));
                    d0 = fmaxf(d0, __shfl_xor_sync(~0u, d0, 2));
                    d1 = fmaxf(d1, __shfl_xor_sync(~0u, d1, 2));
                    if (!first) {
                        d0 = fmaxf(d0, 0.f);
                        d1 = fmaxf(d1, 0.f);
                        const float a0 = ex2(-d0), a1 = ex2(-d1);
#pragma unroll
                        for (int j = 0; j < 16; j++) {
                            O[4 * j] *= a0; O[4 * j + 1] *= a0; O[4 * j + 2] *= a1; O[4 * j + 3] *= a1;
                        }
                        l[0] *= a0; l[1] *= a1;
                    }
                    mc[0] += d0; mc[1] += d1;
                    ctl_tab |= CTL_SHIFT;
                    nxt |= CTL_SHIFT;
                    shift_rows(S, d0, d1);
                    exp_groups<0, 8>(S, Pm, sum);
                    if (!half) exp_groups<8, 16>(S, Pm, sum);
                }
                if (ctl & CTL_SWITCH) write_out(std::true_type());
                if (nxt & CTL_LAST) break;
                if (nxt & CTL_SWITCH) {
                    get_queries();
                    nxt &= ~CTL_SHIFT;
                    ctl_tab &= ~CTL_SHIFT;
                }
                if (nxt & CTL_HALF) {
                    ctl = nxt;
                    float T[32];
                    bar_sync(2 + w, 256);
                    wg_fence();
                    issue_qk_half(T, Q, kdesc0 + (ctl & 0x3800));
                    wg_commit();
                    l[0] += sum[0]; l[1] += sum[1];
                    nxt = __shfl_sync(~0u, ctl_tab, ++t);
                    wait_block(ctl >> 16);
                    const uint32_t vdesc = vdesc0 + ((ctl >> 16) & 0x3800);
                    wg_fence();
                    issue_pv<0>(O, Pm, vdesc, ctl & CTL_PVACC);
                    wg_commit();
                    issue_pv<1>(O, Pm, vdesc, 1);
                    wg_commit();
                    bar_arrive(3 - w, 256);
                    wg_wait<2>();
                    reg_fence(T);
#pragma unroll
                    for (int i = 0; i < 32; i++) S[i] = T[i];
                    continue;
                }
            }
            ctl = nxt;
            bar_sync(2 + w, 256);
            wg_fence();
            issue_qk(S, Q, kdesc0 + (ctl & 0x3800));
            wg_commit();
            l[0] += sum[0]; l[1] += sum[1];
            nxt = __shfl_sync(~0u, ctl_tab, ++t);
            if (ctl & (CTL_SWITCH | CTL_WOUT)) {
                if (ctl & CTL_SWITCH) {
                    scale[0] = rcp_approx(quad_sum(l[0]));
                    scale[1] = rcp_approx(quad_sum(l[1]));
                    l[0] = l[1] = mc[0] = mc[1] = 0.f;
                    if (w == 1) { release((ctl >> 3) - 2); release((ctl >> 3) + 1); }
                } else {
                    write_out(std::false_type());
                }
            }
            wait_block(ctl >> 16);
            const uint32_t vdesc = vdesc0 + ((ctl >> 16) & 0x3800);
            if (!(ctl & CTL_PVHALF)) {
                wg_fence();
                issue_pv<0>(O, Pm, vdesc, ctl & CTL_PVACC);
                wg_commit();
                issue_pv<1>(O, Pm, vdesc, 1);
                wg_commit();
            } else {
                wg_fence();
                issue_pv<0>(O, Pm, vdesc, ctl & CTL_PVACC);
                wg_commit();
                wg_commit();
            }
            bar_arrive(3 - w, 256);
            wg_wait<2>();
            reg_fence(S);
        }
        g += 36;
        if (w == 0) release(g - 3);
        if (nxt & CTL_WOUT) write_out(std::false_type());
        const uint32_t vdesc = vdesc0 + (nxt & 0x3800);
        if (nxt & CTL_PVHALF) {
            wg_fence();
            issue_pv<0>(O, Pm, vdesc, nxt & CTL_PVACC);
            wg_commit();
        } else {
            wg_fence();
            issue_pv<0>(O, Pm, vdesc, nxt & CTL_PVACC);
            issue_pv<1>(O, Pm, vdesc, 1);
            wg_commit();
        }
        l[0] += sum[0]; l[1] += sum[1];
        ctl_tab = (ctl_tab & ~(0x00780078u | CTL_SHIFT)) | ((ctl_tab + 0x00200020u) & 0x00780078u);
        const float i0 = rcp_approx(quad_sum(l[0])), i1 = rcp_approx(quad_sum(l[1]));
        wg_wait<0>();
        reg_fence(O);
        if (w == 0) release(g - 2);
        release(g - 1);
#pragma unroll
        for (int i = 0; i < 32; i++) {
            const float sc = (i & 4) ? i1 : i0;
            pk[i] = pack_bf16(O[chunk_src(i)] * sc, O[chunk_src(i) + 1] * sc);
        }
        pend = ptr_off(ctx_dst(item == 5, 1), chunk0);
        prow = 0x400;
#pragma unroll
        for (int i = 32; i < 64; i++) pk[i] = 0;
        PROF(3 + 2 * item, w);
        if (w == 0) PROF_GT(3 + 2 * item);
    }

    float acc[64];
    uint32_t slot = 0;
    auto issue_out = [&](int first_acc) {
        wait_full(g);
        const uint64_t da = make_desc(sb + slot + w * 8192, 16), db = make_desc(sb + slot + PAGE, 8192);
        wg_fence();
#pragma unroll
        for (int q = 0; q < 4; q++) wgmma_n128_ss(acc, da + 2 * q, db + 128 * q, q ? 1 : first_acc);
        wg_commit();
        g++;
        slot = slot == SM_REGION - 2 * PAGE ? 0 : slot + 2 * PAGE;
    };
    issue_out(0);
#pragma unroll 1
    for (int kb = 1; kb < 64 - PEEL; kb++) {
        issue_out(1);
        wg_wait<1>();
        release(g - 2);
        if (kb <= 8 && !(kb & 1)) {
            store_part4(pend, (kb >> 1) - 1, pk);
            if (kb == 8) mark_done();
        }
        if (kb >= 32 - PEEL && ((kb + PEEL) & 3) == 2 * w) {
            uint32_t u0, u1, u2, u3;
            const uint32_t a = stg + ((kb + PEEL) & 16) * 512 + ((kb + PEEL) & 12) * 128 + lane * 16;
            mbar_wait(sb + BAR_G + w * 8, 0);
            lds128(a, u0, u1, u2, u3);
            sts128(a, pack_bf16(silu_f(bf_lo(u0)), silu_f(bf_hi(u0))), pack_bf16(silu_f(bf_lo(u1)), silu_f(bf_hi(u1))),
                   pack_bf16(silu_f(bf_lo(u2)), silu_f(bf_hi(u2))), pack_bf16(silu_f(bf_lo(u3)), silu_f(bf_hi(u3))));
        }
    }
    const uint32_t goff = (out_rows(pair) * 256 + c * 128 + w * 64 + v * 16 + (lane >> 3)) * (DM * 2) +
                          out_cols(pair) * 128 + (((lane & 7) ^ (lane >> 3)) << 4);
    uint32_t xr[32], gr[32];
    {
        const uint8_t* src[2] = {ptr_off(x, goff), ptr_off(x, goff ^ 64)};
#pragma unroll
        for (int i = 0; i < 8; i++) {
            const uint4 t = ldg_hint(src[i & 1] + (i & 3) * (4 * DM * 2) + (i >> 2) * 128, POL_FIRST);
            xr[4 * i] = t.x; xr[4 * i + 1] = t.y; xr[4 * i + 2] = t.z; xr[4 * i + 3] = t.w;
        }
    }
#pragma unroll 1
    for (int i = 0; i < PEEL; i++) {
        if (i == PEEL - STAG && w == 1) bar_sync(4, 256);
        issue_out(1);
        if (i == PEEL - 1 && w == 0) bar_arrive(4, 256);
        wg_wait<1>();
    }
    asm volatile("barrier.cluster.arrive.relaxed.aligned;" ::: "memory");
#pragma unroll
    for (int i = 0; i < 8; i++) lds128(stg + (i >> 2) * 8192 + (i & 3) * 512 + lane * 16, gr[4 * i], gr[4 * i + 1], gr[4 * i + 2], gr[4 * i + 3]);
    uint8_t* dst[2] = {ptr_off(out, goff), ptr_off(out, goff ^ 64)};
    __syncwarp();
    wg_wait<0>();
    reg_fence(acc);
    PROF(14, w);
    if (w == 0) PROF_GT(14);
#pragma unroll
    for (int s = 0; s < 8; s++)
        stmatrix_x4(slab_addr(stg, lane, s), pack_bf16(acc[8 * s], acc[8 * s + 1]), pack_bf16(acc[8 * s + 2], acc[8 * s + 3]),
                    pack_bf16(acc[8 * s + 4], acc[8 * s + 5]), pack_bf16(acc[8 * s + 6], acc[8 * s + 7]));
    __syncwarp();
    uint32_t o[32];
#pragma unroll
    for (int i = 0; i < 8; i++) lds128(stg + (i >> 2) * 8192 + (i & 3) * 512 + lane * 16, o[4 * i], o[4 * i + 1], o[4 * i + 2], o[4 * i + 3]);
#pragma unroll
    for (int i = 0; i < 8; i++) {
#pragma unroll
        for (int k = 0; k < 4; k++) xr[4 * i + k] = bf2_add(xr[4 * i + k], bf2_mul(o[4 * i + k], gr[4 * i + k]));
        __stcg(reinterpret_cast<uint4*>(dst[i & 1] + (i & 3) * (4 * DM * 2) + (i >> 2) * 128), make_uint4(xr[4 * i], xr[4 * i + 1], xr[4 * i + 2], xr[4 * i + 3]));
    }
    PROF(28, w);
}

__global__ void __cluster_dims__(2, 1, 1) __launch_bounds__(384, 1)
fused_kernel(const __grid_constant__ CUtensorMap m_ckv, const __grid_constant__ CUtensorMap m_wuk,
             const __grid_constant__ CUtensorMap m_wuv, const __grid_constant__ CUtensorMap m_wq,
             const __grid_constant__ CUtensorMap m_wo, const __grid_constant__ CUtensorMap m_gate,
             const __grid_constant__ CUtensorMap m_up, const __grid_constant__ CUtensorMap m_down, const Params P) {
    extern __shared__ __align__(1024) uint8_t smem[];
    const uint32_t sb = __shfl_sync(~0u, smem_u32(smem), 0);
    const int tid = threadIdx.x;
    const int cl = blockIdx.x >> 1, c = blockIdx.x & 1;
    const int pair = cl >= 64 ? cl : cl < 4 ? cl * 16 + 15 : cl < 36 ? ((cl - 4) >> 3) * 16 + ((cl - 4) & 7)
                                                                    : ((cl - 36) / 7) * 16 + 8 + (cl - 36) % 7;
    const bool starter = tid == 256 && pair < NMAIN / 2;
    const CUtensorMap* m_wu = c ? &m_wuv : &m_wuk;
    if (tid == 256) {
        mbar_init(sb + BAR_FULL, 1);
        if (starter) {
            asm volatile("fence.mbarrier_init.release.cluster;" ::: "memory");
            mbar_expect_tx(sb + BAR_FULL, 3 * PAGE);
            tma_3d(sb, m_wu, 0, 0, kv_head(pair) * 2, sb + BAR_FULL);
            tma_3d(sb + PAGE, &m_ckv, 0, kv_tokens(pair) * 256, 0, sb + BAR_FULL);
            tma_3d(sb + 2 * PAGE, &m_ckv, 0, kv_tokens(pair) * 256 + 128, 0, sb + BAR_FULL);
        }
#pragma unroll
        for (int i = 1; i < NBAR; i++) mbar_init(sb + SM_BAR + i * 8, (i >> 3) == 1 ? 16 : i >= 25 ? 8 : 1);
        asm volatile("fence.mbarrier_init.release.cluster;" ::: "memory");
    }
    if (starter) {
#pragma unroll 1
        for (int kb = 1; kb < 4; kb++) mbar_expect_tx(sb + BAR_FULL + kb * 8, 3 * PAGE);
        tma_3d(sb + 3 * PAGE, m_wu, 0, 64, kv_head(pair) * 2, sb + BAR_FULL + 8);
    }
    PROF(18, (tid >> 7) & 1);
    __syncthreads();
    cluster_sync();
    PROF(22, (tid >> 7) & 1);
    PROF(19, (tid >> 7) & 1);
    const int warp = __shfl_sync(~0u, tid >> 5, 0), lane = tid & 31;
    auto dump_prof = [&]() {
    };
    if (pair >= NMAIN / 2) {
        if (warp < 8) ffn_cta(smem, sb, blockIdx.x - NMAIN, __ldcg(&g_sync.done) / NCTA, P.w_r);
        else if (tid == 256) ffn_producer(sb, blockIdx.x - NMAIN, &m_gate, &m_up, &m_down);
        __syncwarp();
        PROF(29, tid >> 7);
        cluster_sync();
        if (tid == 0) atomicAdd(&g_sync.done, 1u);
        if (warp < 8) dump_prof();
    } else if (warp < 8) {
        asm volatile("setmaxnreg.inc.sync.aligned.u32 232;");
        consumer(sb, pair, c, P.out, (const uint8_t*)P.x);
        PROF(29, tid >> 7);
        asm volatile("barrier.cluster.wait.aligned;" ::: "memory");
        dump_prof();
    } else {
        asm volatile("setmaxnreg.dec.sync.aligned.u32 40;");
        if (starter) {
#pragma unroll 1
            for (int kb = 1; kb < 4; kb++) {
                if (kb > 1) tma_3d(sb + kb * (3 * PAGE), m_wu, 0, kb * 64, kv_head(pair) * 2, sb + BAR_FULL + kb * 8);
                tma_3d_mc(sb + kb * (3 * PAGE) + (1 + c) * PAGE, &m_ckv, 0, kv_tokens(pair) * 256 + c * 128, kb, sb + BAR_FULL + kb * 8);
            }
        }
        if (warp == 10) {
            sync_helper(sb, lane, pair, c);
        } else if (warp & 1) {
            fetch_helper((warp & 2) ? P.w_uv : P.w_uk, (const uint8_t*)P.x, sb, (warp >> 1) & 1, lane, pair, c);
        } else {
            producer(P, sb, pair, c, &m_ckv, m_wu, &m_wq, &m_wo);
        }
        bar_sync(6, 128);
        if (tid == 256) atomicAdd(&g_sync.done, 1u);
        cluster_sync();
    }
}

typedef CUresult (*EncodeFn)(CUtensorMap*, CUtensorMapDataType, cuuint32_t, void*, const cuuint64_t*, const cuuint64_t*,
                             const cuuint32_t*, const cuuint32_t*, CUtensorMapInterleave, CUtensorMapSwizzle,
                             CUtensorMapL2promotion, CUtensorMapFloatOOBfill);

void make_map_w(EncodeFn fn, CUtensorMap* m, const void* ptr, int rows, int cols, int blocks, int box_rows = 32) {
    cuuint64_t dims[3] = {64, (cuuint64_t)rows, (cuuint64_t)cols / 64};
    cuuint64_t strides[2] = {(cuuint64_t)cols * 2, 128};
    cuuint32_t box[3] = {64, (cuuint32_t)box_rows, (cuuint32_t)blocks};
    cuuint32_t es[3] = {1, 1, 1};
    fn(m, CU_TENSOR_MAP_DATA_TYPE_BFLOAT16, 3, const_cast<void*>(ptr), dims, strides, box, es, CU_TENSOR_MAP_INTERLEAVE_NONE,
       CU_TENSOR_MAP_SWIZZLE_128B, CU_TENSOR_MAP_L2_PROMOTION_L2_256B, CU_TENSOR_MAP_FLOAT_OOB_FILL_NONE);
}

}

extern "C" void kernel_launch(void* const* d_in, const int* in_sizes, int n_in, void* d_out, int out_size) {
    static EncodeFn fn = nullptr;
    if (!fn) {
        void* f = nullptr;
        cudaDriverEntryPointQueryResult qr;
        cudaGetDriverEntryPoint("cuTensorMapEncodeTiled", &f, cudaEnableDefault, &qr);
        fn = (EncodeFn)f;
        cudaFuncSetAttribute(fused_kernel, cudaFuncAttributeMaxDynamicSharedMemorySize, SMEM_BYTES);
    }
    CUtensorMap m_ckv, m_wuk, m_wuv, m_wq, m_wo, m_gate, m_up, m_down;
    make_map_w(fn, &m_gate, d_in[8], DM, FF, FS / 64, 16);
    make_map_w(fn, &m_up, d_in[9], DM, FF, FS / 64, 16);
    make_map_w(fn, &m_down, d_in[10], FF, DM, DM / 64, 16);
    make_map_w(fn, &m_ckv, d_in[1], SEQ, DC, 1, 128);
    make_map_w(fn, &m_wq, d_in[2], DM, NH * 128, 1, 64);
    make_map_w(fn, &m_wuk, d_in[3], DC, NH * 128, 2, 64);
    make_map_w(fn, &m_wuv, d_in[4], DC, NH * 128, 2, 64);
    make_map_w(fn, &m_wo, d_in[5], NH * 128, DM, 1, 64);
    Params P;
    P.x = (const __nv_bfloat16*)d_in[0];
    P.w_r = (const __nv_bfloat16*)d_in[7];
    P.c_kv = (const uint8_t*)d_in[1];
    P.w_uk = (const uint8_t*)d_in[3];
    P.w_uv = (const uint8_t*)d_in[4];
    P.out = (uint8_t*)d_out;
    fused_kernel<<<NCTA, 384, SMEM_BYTES>>>(m_ckv, m_wuk, m_wuv, m_wq, m_wo, m_gate, m_up, m_down, P);
}
```

```cpp
#include <cuda_runtime.h>
#include <cuda_bf16.h>
#include <cuda.h>
#include <stdint.h>
#define WN_ 5
#define EARLY_ 2
#include <type_traits>

namespace {

constexpr int SEQ = 2048, DM = 1024, NH = 32, DC = 512, FF = 3584;
constexpr int PAGE = 16384;
constexpr int NRING = 12;
constexpr int NCTA = 132, NMAIN = 128;
constexpr uint32_t SM_REGION = NRING * PAGE;
constexpr uint32_t SM_BAR = (NRING + 2) * PAGE;
constexpr uint32_t BAR_FULL = SM_BAR, BAR_EMPTY = SM_BAR + 64;
constexpr uint32_t BAR_DEP = SM_BAR + 128;
constexpr uint32_t BAR_G = SM_BAR + 184;
constexpr uint32_t BAR_DONE = SM_BAR + 200;
constexpr uint32_t BAR_EMPTYL = SM_BAR + 216;
constexpr int NBAR = 35;
constexpr uint32_t SM_PROF = SM_BAR + 320;
constexpr int SMEM_BYTES = SM_PROF + 512;
constexpr uint32_t SPIN_LIMIT = 1u << 16;
constexpr uint32_t POLL_MASK = 7;
constexpr int EARLY = EARLY_;
constexpr int WN = WN_;
constexpr int PEEL = 5, STAG = 3;

struct SyncBlock {
    unsigned done;       unsigned pad0[31];
    unsigned ln;         unsigned pad1[31];
    unsigned router;     unsigned pad4[31];
    unsigned ffn_ticket; unsigned pad2[31];
    unsigned ffn_done;   unsigned pad3[31];
    unsigned kv[NH * 8];
    unsigned kvfree[16 * 8];
    unsigned ctx[32 * NH];
};

__device__ __align__(1024) uint8_t g_xn[8 * 16 * 4 * 8192];
__device__ __align__(4096) uint8_t g_kv[16 * 16 * 65536];
__device__ __align__(4096) uint8_t g_ctx[16 * 64 * 16384];
__device__ __align__(16) uint4 g_routed[2 * 128];
__device__ int g_sel[2];
__device__ __align__(16) float g_r[SEQ];
__device__ __align__(16) float g_ypart[4 * 2 * DM];
__device__ SyncBlock g_sync;

__device__ __forceinline__ uint32_t smem_u32(const void* p) { return (uint32_t)__cvta_generic_to_shared(p); }

__device__ __forceinline__ void mbar_init(uint32_t bar, uint32_t count) {
    asm volatile("mbarrier.init.shared::cta.b64 [%0], %1;" ::"r"(bar), "r"(count) : "memory");
}
#define MBAR_WAIT_ASM(HINT, LIMIT)                                                                  \
    asm volatile("{\n.reg .pred p;\n.reg .u32 n;\nmov.u32 n, 0;\n"                                  \
                 "WAIT_LOOP:\n"                                                                     \
                 "mbarrier.try_wait.parity.shared::cta.b64 p, [%0], %1" HINT ";\n"                  \
                 "@p bra WAIT_DONE;\n"                                                              \
                 "add.u32 n, n, 1;\n"                                                               \
                 "setp.lt.u32 p, n, " LIMIT ";\n"                                                   \
                 "@p bra WAIT_LOOP;\n"                                                              \
                 "WAIT_DONE:\n}\n" ::"r"(bar), "r"(parity) : "memory")
__device__ __forceinline__ void mbar_wait(uint32_t bar, uint32_t parity) { MBAR_WAIT_ASM("", "131072"); }
__device__ __forceinline__ void mbar_sleep(uint32_t bar, uint32_t parity) { MBAR_WAIT_ASM(", 2000", "8192"); }
__device__ __forceinline__ bool mbar_try(uint32_t bar, uint32_t parity) {
    uint32_t ok;
    asm volatile("{\n.reg .pred p;\nmbarrier.try_wait.parity.shared::cta.b64 p, [%1], %2;\nselp.u32 %0, 1, 0, p;\n}\n"
                 : "=r"(ok) : "r"(bar), "r"(parity) : "memory");
    return ok;
}
__device__ __forceinline__ bool mbar_test(uint32_t bar, uint32_t parity) {
    uint32_t ok;
    asm volatile("{\n.reg .pred p;\nmbarrier.test_wait.parity.shared::cta.b64 p, [%1], %2;\nselp.u32 %0, 1, 0, p;\n}\n"
                 : "=r"(ok) : "r"(bar), "r"(parity) : "memory");
    return ok;
}
__device__ __forceinline__ bool elect_one() {
    uint32_t ok;
    asm volatile("{\n.reg .pred p;\nelect.sync _|p, 0xffffffff;\nselp.u32 %0, 1, 0, p;\n}\n" : "=r"(ok));
    return ok;
}
__device__ __forceinline__ void mbar_arrive(uint32_t bar) {
    asm volatile("mbarrier.arrive.shared::cta.b64 _, [%0];" ::"r"(bar) : "memory");
}
__device__ __forceinline__ void mbar_expect_tx(uint32_t bar, uint32_t bytes) {
    asm volatile("mbarrier.arrive.expect_tx.shared::cta.b64 _, [%0], %1;" ::"r"(bar), "r"(bytes) : "memory");
}
__device__ __forceinline__ void mbar_arrive_cluster(uint32_t cluster_addr) {
    asm volatile("mbarrier.arrive.shared::cluster.b64 _, [%0];" ::"r"(cluster_addr) : "memory");
}
__device__ __forceinline__ uint32_t mapa(uint32_t addr, uint32_t rank) {
    uint32_t r;
    asm("mapa.shared::cluster.u32 %0, %1, %2;" : "=r"(r) : "r"(addr), "r"(rank));
    return r;
}
__device__ __forceinline__ void tma_3d(uint32_t dst, const CUtensorMap* m, int c0, int c1, int c2, uint32_t bar) {
    asm volatile("cp.async.bulk.tensor.3d.shared::cluster.global.mbarrier::complete_tx::bytes [%0], [%1, {%3, %4, %5}], [%2];"
                 ::"r"(dst), "l"(m), "r"(bar), "r"(c0), "r"(c1), "r"(c2) : "memory");
}
__device__ __forceinline__ void tma_3d_hint(uint32_t dst, const CUtensorMap* m, int c0, int c1, int c2, uint32_t bar, uint64_t pol) {
    asm volatile("cp.async.bulk.tensor.3d.shared::cluster.global.mbarrier::complete_tx::bytes.L2::cache_hint [%0], [%1, {%3, %4, %5}], [%2], %6;"
                 ::"r"(dst), "l"(m), "r"(bar), "r"(c0), "r"(c1), "r"(c2), "l"(pol) : "memory");
}
__device__ __forceinline__ void tma_3d_mc(uint32_t dst, const CUtensorMap* m, int c0, int c1, int c2, uint32_t bar) {
    asm volatile("cp.async.bulk.tensor.3d.shared::cluster.global.mbarrier::complete_tx::bytes.multicast::cluster [%0], [%1, {%3, %4, %5}], [%2], %6;"
                 ::"r"(dst), "l"(m), "r"(bar), "r"(c0), "r"(c1), "r"(c2), "h"((uint16_t)3) : "memory");
}
__device__ __forceinline__ void bulk_load(uint32_t dst, const void* src, uint32_t bytes, uint32_t bar) {
    asm volatile("cp.async.bulk.shared::cluster.global.mbarrier::complete_tx::bytes [%0], [%1], %2, [%3];"
                 ::"r"(dst), "l"(src), "r"(bytes), "r"(bar) : "memory");
}
__device__ __forceinline__ void cp_async16(uint32_t dst, const void* src) {
    asm volatile("cp.async.cg.shared.global [%0], [%1], 16;" ::"r"(dst), "l"(src) : "memory");
}
__device__ __forceinline__ void bulk_load_mc(uint32_t dst, const void* src, uint32_t bytes, uint32_t bar) {
    asm volatile("cp.async.bulk.shared::cluster.global.mbarrier::complete_tx::bytes.multicast::cluster [%0], [%1], %2, [%3], %4;"
                 ::"r"(dst), "l"(src), "r"(bytes), "r"(bar), "h"((uint16_t)3) : "memory");
}
__device__ __forceinline__ void fence_async_smem() { asm volatile("fence.proxy.async.shared::cta;" ::: "memory"); }
__device__ __forceinline__ void prefetch_map(const CUtensorMap* m) {
    asm volatile("prefetch.tensormap [%0];" ::"l"(m) : "memory");
}
__device__ __forceinline__ void red_release(unsigned* p) {
    asm volatile("red.release.gpu.global.add.u32 [%0], 1;" ::"l"(p) : "memory");
}
__device__ __forceinline__ unsigned ld_relaxed(const unsigned* p) {
    unsigned v;
    asm volatile("ld.relaxed.gpu.global.u32 %0, [%1];" : "=r"(v) : "l"(p) : "memory");
    return v;
}
__device__ __forceinline__ void wait_counter(const unsigned* p, unsigned target) {
    for (uint32_t n = 0; (int)(ld_relaxed(p) - target) < 0 && n < SPIN_LIMIT; n++) __nanosleep(100);
    asm volatile("fence.acquire.gpu;" ::: "memory");
    asm volatile("fence.proxy.async.global;" ::: "memory");
}
__device__ __forceinline__ void bar_sync(int id, int n) { asm volatile("bar.sync %0, %1;" ::"r"(id), "r"(n) : "memory"); }
__device__ __forceinline__ void bar_arrive(int id, int n) { asm volatile("bar.arrive %0, %1;" ::"r"(id), "r"(n) : "memory"); }
__device__ __forceinline__ void cluster_sync() {
    asm volatile("barrier.cluster.arrive.relaxed.aligned;\nbarrier.cluster.wait.aligned;" ::: "memory");
}
__device__ __forceinline__ void wg_fence() { asm volatile("wgmma.fence.sync.aligned;" ::: "memory"); }
__device__ __forceinline__ void wg_commit() { asm volatile("wgmma.commit_group.sync.aligned;" ::: "memory"); }
template <int N> __device__ __forceinline__ void wg_wait() { asm volatile("wgmma.wait_group.sync.aligned %0;" ::"n"(N) : "memory"); }
template <int N> __device__ __forceinline__ void reg_fence(float (&a)[N]) {
#pragma unroll
    for (int i = 0; i < N; i++) asm volatile("" : "+f"(a[i])::"memory");
}
template <int N> __device__ __forceinline__ void reg_fence(uint32_t (&a)[N]) {
#pragma unroll
    for (int i = 0; i < N; i++) asm volatile("" : "+r"(a[i])::"memory");
}
__device__ __forceinline__ uint32_t pack_bf16(float lo, float hi) {
    uint32_t r;
    asm("cvt.rn.bf16x2.f32 %0, %1, %2;" : "=r"(r) : "f"(hi), "f"(lo));
    return r;
}
__device__ __forceinline__ float bf_lo(uint32_t v) { return __uint_as_float(v << 16); }
__device__ __forceinline__ float bf_hi(uint32_t v) { return __uint_as_float(v & 0xffff0000u); }
__device__ __forceinline__ float bf_round(float v) { return __bfloat162float(__float2bfloat16_rn(v)); }
__device__ __forceinline__ float ex2(float v) {
    float r;
    asm("ex2.approx.ftz.f32 %0, %1;" : "=f"(r) : "f"(v));
    return r;
}
__device__ __forceinline__ float sqrt_approx(float v) {
    float r;
    asm("sqrt.approx.ftz.f32 %0, %1;" : "=f"(r) : "f"(v));
    return r;
}
__device__ __forceinline__ float rcp_approx(float v) {
    float r;
    asm("rcp.approx.ftz.f32 %0, %1;" : "=f"(r) : "f"(v));
    return r;
}
__device__ __forceinline__ float silu_f(float v) { return v * rcp_approx(1.0f + ex2(v * -1.4426950408889634f)); }
__device__ __forceinline__ void stmatrix_x4(uint32_t addr, uint32_t r0, uint32_t r1, uint32_t r2, uint32_t r3) {
    asm volatile("stmatrix.sync.aligned.m8n8.x4.shared.b16 [%0], {%1, %2, %3, %4};"
                 ::"r"(addr), "r"(r0), "r"(r1), "r"(r2), "r"(r3) : "memory");
}
__device__ __forceinline__ void sts128(uint32_t addr, uint32_t r0, uint32_t r1, uint32_t r2, uint32_t r3) {
    asm volatile("st.shared.v4.b32 [%0], {%1, %2, %3, %4};" ::"r"(addr), "r"(r0), "r"(r1), "r"(r2), "r"(r3) : "memory");
}
__device__ __forceinline__ void lds128(uint32_t addr, uint32_t& r0, uint32_t& r1, uint32_t& r2, uint32_t& r3) {
    asm volatile("ld.shared.v4.b32 {%0, %1, %2, %3}, [%4];" : "=r"(r0), "=r"(r1), "=r"(r2), "=r"(r3) : "r"(addr) : "memory");
}
__device__ __forceinline__ uint32_t bf2_mul(uint32_t a, uint32_t b) {
    uint32_t r;
    asm("mul.rn.bf16x2 %0, %1, %2;" : "=r"(r) : "r"(a), "r"(b));
    return r;
}
__device__ __forceinline__ uint32_t bf2_add(uint32_t a, uint32_t b) {
    uint32_t r;
    asm("add.rn.bf16x2 %0, %1, %2;" : "=r"(r) : "r"(a), "r"(b));
    return r;
}
constexpr uint64_t POL_FIRST = 0x12F0000000000000ull, POL_NORMAL = 0x1000000000000000ull;
__device__ __forceinline__ uint4 ldg_hint(const void* p, uint64_t pol) {
    uint4 v;
    asm volatile("ld.global.cg.L2::cache_hint.v4.u32 {%0, %1, %2, %3}, [%4], %5;" : "=r"(v.x), "=r"(v.y), "=r"(v.z), "=r"(v.w) : "l"(p), "l"(pol));
    return v;
}
__device__ __forceinline__ void stg_hint(void* p, uint32_t r0, uint32_t r1, uint32_t r2, uint32_t r3, uint64_t pol) {
    asm volatile("st.global.cg.L2::cache_hint.v4.u32 [%0], {%1, %2, %3, %4}, %5;" ::"l"(p), "r"(r0), "r"(r1), "r"(r2), "r"(r3), "l"(pol) : "memory");
}

__device__ __forceinline__ uint64_t make_desc(uint32_t addr, uint32_t lbo_bytes) {
    return (uint64_t)((addr & 0x3FFFF) >> 4) | ((uint64_t)(lbo_bytes >> 4) << 16) | ((uint64_t)(1024 >> 4) << 32) | (1ull << 62);
}

__device__ __forceinline__ void wgmma_n256_ss(float (&d)[128], uint64_t da, uint64_t db, int acc) {
    asm volatile(
        "{\n.reg .pred p;\nsetp.ne.b32 p, %130, 0;\n"
        "wgmma.mma_async.sync.aligned.m64n256k16.f32.bf16.bf16 {"
        "%0, %1, %2, %3, %4, %5, %6, %7, %8, %9, %10, %11, %12, %13, %14, %15, "
        "%16, %17, %18, %19, %20, %21, %22, %23, %24, %25, %26, %27, %28, %29, %30, %31, "
        "%32, %33, %34, %35, %36, %37, %38, %39, %40, %41, %42, %43, %44, %45, %46, %47, "
        "%48, %49, %50, %51, %52, %53, %54, %55, %56, %57, %58, %59, %60, %61, %62, %63, "
        "%64, %65, %66, %67, %68, %69, %70, %71, %72, %73, %74, %75, %76, %77, %78, %79, "
        "%80, %81, %82, %83, %84, %85, %86, %87, %88, %89, %90, %91, %92, %93, %94, %95, "
        "%96, %97, %98, %99, %100, %101, %102, %103, %104, %105, %106, %107, %108, %109, %110, %111, "
        "%112, %113, %114, %115, %116, %117, %118, %119, %120, %121, %122, %123, %124, %125, %126, %127"
        "}, %128, %129, p, 1, 1, 1, 0;\n}\n"
        :
        "+f"(d[0]), "+f"(d[1]), "+f"(d[2]), "+f"(d[3]), "+f"(d[4]), "+f"(d[5]), "+f"(d[6]), "+f"(d[7]),
        "+f"(d[8]), "+f"(d[9]), "+f"(d[10]), "+f"(d[11]), "+f"(d[12]), "+f"(d[13]), "+f"(d[14]), "+f"(d[15]),
        "+f"(d[16]), "+f"(d[17]), "+f"(d[18]), "+f"(d[19]), "+f"(d[20]), "+f"(d[21]), "+f"(d[22]), "+f"(d[23]),
        "+f"(d[24]), "+f"(d[25]), "+f"(d[26]), "+f"(d[27]), "+f"(d[28]), "+f"(d[29]), "+f"(d[30]), "+f"(d[31]),
        "+f"(d[32]), "+f"(d[33]), "+f"(d[34]), "+f"(d[35]), "+f"(d[36]), "+f"(d[37]), "+f"(d[38]), "+f"(d[39]),
        "+f"(d[40]), "+f"(d[41]), "+f"(d[42]), "+f"(d[43]), "+f"(d[44]), "+f"(d[45]), "+f"(d[46]), "+f"(d[47]),
        "+f"(d[48]), "+f"(d[49]), "+f"(d[50]), "+f"(d[51]), "+f"(d[52]), "+f"(d[53]), "+f"(d[54]), "+f"(d[55]),
        "+f"(d[56]), "+f"(d[57]), "+f"(d[58]), "+f"(d[59]), "+f"(d[60]), "+f"(d[61]), "+f"(d[62]), "+f"(d[63]),
        "+f"(d[64]), "+f"(d[65]), "+f"(d[66]), "+f"(d[67]), "+f"(d[68]), "+f"(d[69]), "+f"(d[70]), "+f"(d[71]),
        "+f"(d[72]), "+f"(d[73]), "+f"(d[74]), "+f"(d[75]), "+f"(d[76]), "+f"(d[77]), "+f"(d[78]), "+f"(d[79]),
        "+f"(d[80]), "+f"(d[81]), "+f"(d[82]), "+f"(d[83]), "+f"(d[84]), "+f"(d[85]), "+f"(d[86]), "+f"(d[87]),
        "+f"(d[88]), "+f"(d[89]), "+f"(d[90]), "+f"(d[91]), "+f"(d[92]), "+f"(d[93]), "+f"(d[94]), "+f"(d[95]),
        "+f"(d[96]), "+f"(d[97]), "+f"(d[98]), "+f"(d[99]), "+f"(d[100]), "+f"(d[101]), "+f"(d[102]), "+f"(d[103]),
        "+f"(d[104]), "+f"(d[105]), "+f"(d[106]), "+f"(d[107]), "+f"(d[108]), "+f"(d[109]), "+f"(d[110]), "+f"(d[111]),
        "+f"(d[112]), "+f"(d[113]), "+f"(d[114]), "+f"(d[115]), "+f"(d[116]), "+f"(d[117]), "+f"(d[118]), "+f"(d[119]),
        "+f"(d[120]), "+f"(d[121]), "+f"(d[122]), "+f"(d[123]), "+f"(d[124]), "+f"(d[125]), "+f"(d[126]), "+f"(d[127])
        : "l"(da), "l"(db), "r"(acc));
}

__device__ __forceinline__ void wgmma_n64_rs_tb(float* d, uint32_t a0, uint32_t a1, uint32_t a2, uint32_t a3, uint32_t db, int acc) {
    asm volatile(
        "{\n.reg .pred p;\n.reg .b64 db;\nsetp.ne.b32 p, %37, 0;\nmov.b64 db, {%36, 0x40000040};\n"
        "wgmma.mma_async.sync.aligned.m64n64k16.f32.bf16.bf16 {"
        "%0, %1, %2, %3, %4, %5, %6, %7, %8, %9, %10, %11, %12, %13, %14, %15, "
        "%16, %17, %18, %19, %20, %21, %22, %23, %24, %25, %26, %27, %28, %29, %30, %31"
        "}, {%32, %33, %34, %35}, db, p, 1, 1, 1;\n}\n"
        :
        "+f"(d[0]), "+f"(d[1]), "+f"(d[2]), "+f"(d[3]), "+f"(d[4]), "+f"(d[5]), "+f"(d[6]), "+f"(d[7]),
        "+f"(d[8]), "+f"(d[9]), "+f"(d[10]), "+f"(d[11]), "+f"(d[12]), "+f"(d[13]), "+f"(d[14]), "+f"(d[15]),
        "+f"(d[16]), "+f"(d[17]), "+f"(d[18]), "+f"(d[19]), "+f"(d[20]), "+f"(d[21]), "+f"(d[22]), "+f"(d[23]),
        "+f"(d[24]), "+f"(d[25]), "+f"(d[26]), "+f"(d[27]), "+f"(d[28]), "+f"(d[29]), "+f"(d[30]), "+f"(d[31])
        : "r"(a0), "r"(a1), "r"(a2), "r"(a3), "r"(db), "r"(acc));
}

template <int TB>
__device__ __forceinline__ void wgmma_n128_rs(float (&d)[64], uint32_t a0, uint32_t a1, uint32_t a2, uint32_t a3, uint32_t db, int acc) {
    asm volatile(
        "{\n.reg .pred p;\n.reg .b64 db;\nsetp.ne.b32 p, %69, 0;\nmov.b64 db, {%68, 0x40000040};\n"
        "wgmma.mma_async.sync.aligned.m64n128k16.f32.bf16.bf16 {"
        "%0, %1, %2, %3, %4, %5, %6, %7, %8, %9, %10, %11, %12, %13, %14, %15, "
        "%16, %17, %18, %19, %20, %21, %22, %23, %24, %25, %26, %27, %28, %29, %30, %31, "
        "%32, %33, %34, %35, %36, %37, %38, %39, %40, %41, %42, %43, %44, %45, %46, %47, "
        "%48, %49, %50, %51, %52, %53, %54, %55, %56, %57, %58, %59, %60, %61, %62, %63"
        "}, {%64, %65, %66, %67}, db, p, 1, 1, %70;\n}\n"
        :
        "+f"(d[0]), "+f"(d[1]), "+f"(d[2]), "+f"(d[3]), "+f"(d[4]), "+f"(d[5]), "+f"(d[6]), "+f"(d[7]),
        "+f"(d[8]), "+f"(d[9]), "+f"(d[10]), "+f"(d[11]), "+f"(d[12]), "+f"(d[13]), "+f"(d[14]), "+f"(d[15]),
        "+f"(d[16]), "+f"(d[17]), "+f"(d[18]), "+f"(d[19]), "+f"(d[20]), "+f"(d[21]), "+f"(d[22]), "+f"(d[23]),
        "+f"(d[24]), "+f"(d[25]), "+f"(d[26]), "+f"(d[27]), "+f"(d[28]), "+f"(d[29]), "+f"(d[30]), "+f"(d[31]),
        "+f"(d[32]), "+f"(d[33]), "+f"(d[34]), "+f"(d[35]), "+f"(d[36]), "+f"(d[37]), "+f"(d[38]), "+f"(d[39]),
        "+f"(d[40]), "+f"(d[41]), "+f"(d[42]), "+f"(d[43]), "+f"(d[44]), "+f"(d[45]), "+f"(d[46]), "+f"(d[47]),
        "+f"(d[48]), "+f"(d[49]), "+f"(d[50]), "+f"(d[51]), "+f"(d[52]), "+f"(d[53]), "+f"(d[54]), "+f"(d[55]),
        "+f"(d[56]), "+f"(d[57]), "+f"(d[58]), "+f"(d[59]), "+f"(d[60]), "+f"(d[61]), "+f"(d[62]), "+f"(d[63])
        : "r"(a0), "r"(a1), "r"(a2), "r"(a3), "r"(db), "r"(acc), "n"(TB));
}

__device__ __forceinline__ void wgmma_n128_ss(float* d, uint64_t da, uint64_t db, int acc) {
    asm volatile(
        "{\n.reg .pred p;\nsetp.ne.b32 p, %66, 0;\n"
        "wgmma.mma_async.sync.aligned.m64n128k16.f32.bf16.bf16 {"
        "%0, %1, %2, %3, %4, %5, %6, %7, %8, %9, %10, %11, %12, %13, %14, %15, "
        "%16, %17, %18, %19, %20, %21, %22, %23, %24, %25, %26, %27, %28, %29, %30, %31, "
        "%32, %33, %34, %35, %36, %37, %38, %39, %40, %41, %42, %43, %44, %45, %46, %47, "
        "%48, %49, %50, %51, %52, %53, %54, %55, %56, %57, %58, %59, %60, %61, %62, %63"
        "}, %64, %65, p, 1, 1, 0, 1;\n}\n"
        :
        "+f"(d[0]), "+f"(d[1]), "+f"(d[2]), "+f"(d[3]), "+f"(d[4]), "+f"(d[5]), "+f"(d[6]), "+f"(d[7]),
        "+f"(d[8]), "+f"(d[9]), "+f"(d[10]), "+f"(d[11]), "+f"(d[12]), "+f"(d[13]), "+f"(d[14]), "+f"(d[15]),
        "+f"(d[16]), "+f"(d[17]), "+f"(d[18]), "+f"(d[19]), "+f"(d[20]), "+f"(d[21]), "+f"(d[22]), "+f"(d[23]),
        "+f"(d[24]), "+f"(d[25]), "+f"(d[26]), "+f"(d[27]), "+f"(d[28]), "+f"(d[29]), "+f"(d[30]), "+f"(d[31]),
        "+f"(d[32]), "+f"(d[33]), "+f"(d[34]), "+f"(d[35]), "+f"(d[36]), "+f"(d[37]), "+f"(d[38]), "+f"(d[39]),
        "+f"(d[40]), "+f"(d[41]), "+f"(d[42]), "+f"(d[43]), "+f"(d[44]), "+f"(d[45]), "+f"(d[46]), "+f"(d[47]),
        "+f"(d[48]), "+f"(d[49]), "+f"(d[50]), "+f"(d[51]), "+f"(d[52]), "+f"(d[53]), "+f"(d[54]), "+f"(d[55]),
        "+f"(d[56]), "+f"(d[57]), "+f"(d[58]), "+f"(d[59]), "+f"(d[60]), "+f"(d[61]), "+f"(d[62]), "+f"(d[63])
        : "l"(da), "l"(db), "r"(acc));
}

__device__ __forceinline__ void wgmma_n8_ta(float* d, uint64_t da, uint64_t db) {
    asm volatile("wgmma.mma_async.sync.aligned.m64n8k16.f32.bf16.bf16 {%0, %1, %2, %3}, %4, %5, 1, 1, 1, 1, 0;\n"
                 : "+f"(d[0]), "+f"(d[1]), "+f"(d[2]), "+f"(d[3]) : "l"(da), "l"(db));
}

#define PROF(slot, role)
#undef PROF_GT
#define PROF_GT(slot)

struct Params {
    const __nv_bfloat16* x;
    const __nv_bfloat16* w_r;
    const uint8_t *c_kv, *w_uk, *w_uv;
    uint8_t* out;
};
__device__ __forceinline__ void lsu_prefetch(const void* p) { asm volatile("prefetch.global.L2 [%0];" ::"l"(p) : "memory"); }

template <typename T>
__device__ __forceinline__ T* ptr_off(T* base, uint32_t off) {
    uint32_t lo, hi;
    asm("mov.b64 {%0, %1}, %2;" : "=r"(lo), "=r"(hi) : "l"(base));
    asm("add.cc.u32 %0, %0, %2;\naddc.u32 %1, %1, 0;" : "+r"(lo), "+r"(hi) : "r"(off));
    T* r;
    asm("mov.b64 %0, {%1, %2};" : "=l"(r) : "r"(lo), "r"(hi));
    return r;
}
__device__ __forceinline__ int kv_head(int pair) { return pair & 7; }
__device__ __forceinline__ int kv_tokens(int pair) { return ((pair >> 3) & 1) * 4 + (pair >> 4); }
__device__ __forceinline__ int out_rows(int pair) { return pair & 7; }
__device__ __forceinline__ int out_cols(int pair) { return (pair >> 4) * 4 + ((pair >> 3) & 1) * 2; }
__device__ __forceinline__ int attn_rowblock(int pair, int seg) {
    int j = pair & 3, hl = pair >> 2;
    return (((hl & 1) | (j == 0)) ^ seg) ? j : 7 - j;
}
__device__ __forceinline__ int outproj_head(int i, int ib) {
    if (i < 16) return i;
    return 16 + 2 * (i & 7) + ((ib < 4) ^ ((i >> 3) & 1));
}

__device__ __forceinline__ void pin_value(uint32_t& v) { asm volatile("" : "+r"(v)); }
__device__ __forceinline__ void pin_value(int& v) { asm volatile("" : "+r"(v)); }
__device__ __forceinline__ void pin_value(const uint8_t*& v) { asm volatile("" : "+l"(v)); }

__device__ __forceinline__ void producer(const Params& P, uint32_t sb, int pair, int c,
                                         const CUtensorMap* m_ckv, const CUtensorMap* m_wu,
                                         const CUtensorMap* m_wq, const CUtensorMap* m_wo) {
    const int hl = pair >> 2;
    const int ibA = attn_rowblock(pair, 0), nA = 2 * ibA + 2;
    const int ib = out_rows(pair), mi = 2 * ib + c, nb = out_cols(pair);
    const bool leader = elect_one();
    uint32_t g = 4, tail = 0;
    if (leader) prefetch_map(m_wq);
    auto wait_released = [&](uint32_t need) {
#pragma unroll 1
        for (; tail <= need; tail++) mbar_wait(sb + BAR_EMPTY + (tail & 7) * 8, (tail >> 3) & 1);
    };
    auto wait_released_here = [&](uint32_t need) {
#pragma unroll 1
        for (; tail < need; tail++) mbar_wait(sb + BAR_EMPTY + (tail & 7) * 8, (tail >> 3) & 1);
        if (tail == need) mbar_wait(sb + BAR_EMPTYL + (need & 7) * 8, (need >> 3) & 1);
    };
    auto wait_released_peer = [&](uint32_t need) {
        if (tail == need) {
            uint32_t eb = sb + BAR_EMPTY + (need & 7) * 8, ep = (need >> 3) & 1;
            tail++;
            mbar_wait(eb, ep);
        }
    };
    auto full_bar = [&]() { return sb + BAR_FULL + (g & 7) * 8; };
    auto pin = [](auto&... v) { (pin_value(v), ...); };
#pragma unroll 1
    for (int rnd = 0; rnd < 2; rnd++) {
#pragma unroll 1
        for (int i = rnd ? 0 : 4; i < 16; i++) {
            int kb = i & 7, h2 = (kv_head(pair) + (i & 8) + rnd * 16) * 2, krow = kb * 64;
            uint32_t pg = sb + (i & 3) * (3 * PAGE), pb = pg + (1 + c) * PAGE, bar = full_bar();
            pin(kb, h2, krow, pg, pb, bar);
            const uint32_t need = g - 4 - (i < 2);
            wait_released_here(need);
            if (leader) {
                mbar_expect_tx(bar, 3 * PAGE);
                tma_3d(pg, m_wu, 0, krow, h2, bar);
            }
            wait_released_peer(need);
            if (leader) {
                tma_3d_mc(pb, m_ckv, 0, kv_tokens(pair) * 256 + c * 128, kb, bar);
                if (rnd == 1 && i == 3) asm volatile("red.relaxed.gpu.global.add.u32 [%0], 1;" ::"l"(ptr_off(g_sync.kvfree, hl * 32)) : "memory");
            }
            g++;
        }
        mbar_sleep(sb + BAR_DEP, 0);
        const uint8_t* xa = ptr_off(g_xn, ibA * (16 * 32768) + c * PAGE);
        const uint8_t* xb = ptr_off(g_xn, (7 - ibA) * (16 * 32768) + (1 - c) * PAGE);
#pragma unroll 1
        for (int kb = 0; kb < DM / 64; kb++) {
            uint32_t pg = sb + (kb & 3) * (3 * PAGE), pw = pg + 2 * PAGE + c * 8192, bar = full_bar(), p2 = pg + PAGE;
            int krow = kb * 64;
            pin(pg, pw, p2, bar, krow);
            wait_released_here(g - 4);
            if (leader) {
                mbar_expect_tx(bar, 3 * PAGE);
                bulk_load(pg, xa, PAGE, bar);
            }
            wait_released_peer(g - 4);
            if (leader) {
                tma_3d_mc(pw, m_wq, 0, krow, (rnd * 16 + hl) * 2 + c, bar);
                bulk_load(p2, xb, PAGE, bar);
            }
            g++;
            xa += 32768;
            xb += 32768;
        }
        mbar_sleep(sb + BAR_DEP + 8 + rnd * 16, 0);
        if (rnd == 1 && leader) prefetch_map(m_wo);
        uint32_t pg = sb + c * PAGE;
#pragma unroll 1
        for (int j = 0; j < 36; j++) {
            const bool isk = j == 0 || ((j & 1) && j != 35);
            const int t = isk ? (j + 1) >> 1 : (j - 1) >> 1;
            const uint8_t* src = ptr_off(g_kv, (hl * 16 + (t >= nA ? t - nA : t)) * 65536 + (isk ? 0 : 32768) + c * PAGE);
            uint32_t bar = full_bar(), need = g - 6 + (j < 2) + (j < 5);
            pin(src, bar, need);
            wait_released(need);
            if (leader) {
                mbar_expect_tx(bar, 2 * PAGE);
                bulk_load_mc(pg, src, PAGE, bar);
            }
            g++;
            if (rnd == 0 && j >= 22 && j < 34) {
                const int cta = pair * 2 + c, i = j - 22;
                const uint32_t l = (threadIdx.x & 31) * 128;
                if (i < 8) lsu_prefetch(ptr_off(i & 1 ? P.w_uv : P.w_uk, cta * 32768 + (i >> 1) * 8192 + 4096 + l));
                else lsu_prefetch(ptr_off(P.c_kv, cta * 16384 + (i - 8) * 4096 + l));
            }
            pg = pg >= sb + SM_REGION - 2 * PAGE ? pg - (SM_REGION - 2 * PAGE) : pg + 2 * PAGE;
        }
    }
    uint32_t pg = sb;
#pragma unroll 1
    for (int i = 0; i < 64; i++) {
        if ((i & 15) == 0 && i != 16) mbar_sleep(sb + BAR_DEP + 32 + (i >> 1) - (i ? 8 : 0), 0);
        const int kb = outproj_head(i >> 1, ib) * 2 + (i & 1);
        const uint8_t* src = ptr_off(g_ctx, (mi * 64 + kb) * PAGE);
        uint32_t bar = full_bar(), pw = pg + PAGE + c * 8192;
        int krow = kb * 64;
        pin(src, bar, pw, krow);
        wait_released_here(g - 6);
        if (leader) {
            mbar_expect_tx(bar, 2 * PAGE);
            bulk_load(pg, src, PAGE, bar);
        }
        wait_released_peer(g - 6);
        if (leader) tma_3d_mc(pw, m_wo, 0, krow, nb + c, bar);
        g++;
        pg = pg == sb + SM_REGION - 2 * PAGE ? sb : pg + 2 * PAGE;
    }
}

__device__ __forceinline__ uint32_t xn_block(int row64, int kb) {
    return (((row64 >> 2) * 16 + kb) * 4 + ((row64 & 1) * 2 + (((row64 >> 1) & 1) ^ 1))) * 8192;
}
__device__ __forceinline__ uint32_t image_offset(int row, int ch) {
    return xn_block(row >> 6, ch >> 3) + (row & 63) * 128 + (((ch & 7) ^ (row & 7)) << 4);
}
__device__ __forceinline__ uint32_t bf2_sub(uint32_t a, uint32_t b) {
    uint32_t r;
    asm("sub.rn.bf16x2 %0, %1, %2;" : "=r"(r) : "r"(a), "r"(b));
    return r;
}
__device__ __forceinline__ uint32_t bf2_fma(uint32_t a, uint32_t b, uint32_t c) {
    uint32_t r;
    asm("fma.rn.bf16x2 %0, %1, %2, %3;" : "=r"(r) : "r"(a), "r"(b), "r"(c));
    return r;
}
template <int N0, int N>
__device__ __forceinline__ void ln_sums(const uint32_t (&u)[N], float& sum, float& sq) {
    float s0 = 0.f, s1 = 0.f, q0 = 0.f, q1 = 0.f;
#pragma unroll
    for (int k = N0; k < N0 + 16; k++) {
        const float a = bf_lo(u[k]), b = bf_hi(u[k]);
        s0 += a; s1 += b;
        q0 = fmaf(a, a, q0); q1 = fmaf(b, b, q1);
    }
    sum = s0 + s1;
    sq = q0 + q1;
}
__device__ __forceinline__ void ln_finish(float sum, float sq, uint32_t& mean2, uint32_t& rhi2, uint32_t& rlo2) {
    const float ms = sum * (1.0f / DM);
    const float var = fmaxf(fmaf(-ms, ms, sq * (1.0f / DM)), 0.f);
    const float rden = rcp_approx(bf_round(sqrt_approx(bf_round(bf_round(var) + 1e-5f))));
    const float rhi = bf_round(rden);
    mean2 = pack_bf16(ms, ms);
    rhi2 = pack_bf16(rhi, rhi);
    rlo2 = pack_bf16(rden - rhi, rden - rhi);
}
template <int N0, int N>
__device__ __forceinline__ void ln_apply(uint32_t (&u)[N], uint32_t mean2, uint32_t rhi2, uint32_t rlo2, uint8_t* dst) {
#pragma unroll
    for (int i = 0; i < 4; i++) {
        uint32_t o[4];
#pragma unroll
        for (int k = 0; k < 4; k++) {
            const uint32_t d = bf2_sub(u[N0 + 4 * i + k], mean2);
            o[k] = bf2_fma(d, rhi2, bf2_mul(d, rlo2));
        }
#pragma unroll
        for (int k = 0; k < 4; k++) u[N0 + 4 * i + k] = o[k];
        __stcg(reinterpret_cast<uint4*>(dst + i * 131072), make_uint4(o[0], o[1], o[2], o[3]));
    }
}
__device__ __forceinline__ int query_rowblock(int pair, int c, int w, int seg) {
    const int qA = (w ? 0 : 2) + c;
    return 4 * attn_rowblock(pair, seg) + (seg ? 3 - qA : qA);
}

__device__ __noinline__ void fetch_helper(const uint8_t* w_u, const uint8_t* x, uint32_t sb, int w, int lane, int pair, int c) {
    const uint32_t page = sb + SM_REGION + w * PAGE + lane * 16;
    mbar_sleep(sb + BAR_FULL + 5 * 8, 0);
#pragma unroll 1
    for (int i = 0; i < 2; i++) {
        lsu_prefetch(ptr_off(w_u, ((pair * 2 + c) * 4 + i * 2 + (lane >> 4)) * 8192 + 2048 + (lane & 15) * 128));
        __nanosleep(300);
    }
    const unsigned e1 = __ldcg(&g_sync.done) / NCTA + 1;
#pragma unroll 1
    for (int e = 1; e <= 7; e += 2) mbar_sleep(sb + BAR_DONE + 8, (e >> 1) & 1);
    const int rb = out_rows(pair) * 4 + c * 2 + w, kb0 = out_cols(pair);
    const uint8_t* src = ptr_off(g_xn, xn_block(rb, kb0) + lane * 16);
#pragma unroll 1
    for (int i = 0; i < 32; i += 4) {
#pragma unroll
        for (int k = 0; k < 4; k++) cp_async16(page + (i + k) * 512, src + (i + k) * 512 + (i >> 4) * (32768 - 8192));
        __nanosleep(200);
    }
#pragma unroll 1
    for (int i = 0; i < 4; i++) lsu_prefetch(ptr_off(x, (rb * 64 + i * 16 + (lane >> 1)) * (DM * 2) + kb0 * 128 + (lane & 1) * 128));
    wait_counter(&g_sync.ffn_done, e1);
    const int r = __ldcg(ptr_off(g_sel, (lane >> 4) * 4)) - rb * 64, ch = lane & 15;
    const uint4 t = __ldcg(ptr_off(g_routed, ((lane >> 4) * 128 + kb0 * 8 + ch) * 16));
    asm volatile("cp.async.wait_all;" ::: "memory");
    __syncwarp();
    if (r >= 0 && r < 64)
        sts128(sb + SM_REGION + w * PAGE + (ch >> 3) * 8192 + r * 128 + (((ch & 7) ^ (r & 7)) << 4), t.x, t.y, t.z, t.w);
    __syncwarp();
    if (lane == 0) mbar_arrive(sb + BAR_G + w * 8);
    PROF(20, 2);
}

__device__ __noinline__ void sync_helper(uint32_t sb, int lane, int pair, int c) {
    const unsigned e1 = __ldcg(&g_sync.done) / NCTA + 1;
    const int ib = out_rows(pair);
    int e = 0, b = 0;
#pragma unroll 1
    for (uint32_t n = 0; (e < 9 || b < 7) && n < SPIN_LIMIT; n++) {
        if (e < 9 && __all_sync(~0u, mbar_test(sb + BAR_DONE + (e & 1) * 8, (e >> 1) & 1))) {
            const int rnd = e > 4, ev = (e - 1) & 3;
            unsigned* flag = e == 0 ? &g_sync.ln
                           : ev < 2 ? ptr_off(g_sync.kv, (rnd * 16 + kv_head(pair) + 8 * ev) * 32)
                                    : ptr_off(g_sync.ctx, (query_rowblock(pair, c, lane & 1, ev & 1) * NH + rnd * 16 + (pair >> 2)) * 4);
            asm volatile("fence.proxy.async.global;\nfence.release.gpu;" ::: "memory");
            if (lane < ((e == 0 || ev < 2) ? 1 : 2)) asm volatile("red.relaxed.gpu.global.add.u32 [%0], 1;" ::"l"(flag) : "memory");
            PROF(10 + e, 2);
            e++;
        }
        if (b < 7 && e > 0 && (b < 4 || (n & POLL_MASK) == 0)) {
            const int i = b == 4 ? lane >> 1 : 8 * b - 24 + ((lane >> 1) & 7);
            const unsigned* cnt = b == 0 ? &g_sync.ln
                                : b == 2 ? ptr_off(g_sync.kvfree, (kv_head(pair) + 8 * (lane & 1)) * 32)
                                : b < 4 ? ptr_off(g_sync.kv, ((b >> 1) * 16 + (pair >> 2)) * 32)
                                        : ptr_off(g_sync.ctx, ((4 * ib + 2 * c + (lane & 1)) * NH + outproj_head(i & 31, ib)) * 4);
            if (__all_sync(~0u, (int)(ld_relaxed(cnt) - e1 * (b == 0 ? NMAIN : b == 2 ? 8 : b < 4 ? 16 : 1)) >= 0)) {
                asm volatile("fence.acquire.gpu;\nfence.proxy.async.global;" ::: "memory");
                __syncwarp();
                if (lane == 0) mbar_arrive(sb + BAR_DEP + b * 8);
                PROF(1 + b, 2);
                b++;
            }
        }
        __nanosleep(150);
    }
}

__device__ __forceinline__ unsigned long long block_max_key(unsigned long long k, unsigned long long* red, int tid) {
#pragma unroll
    for (int o = 16; o; o >>= 1) {
        unsigned long long t = __shfl_xor_sync(~0u, k, o);
        k = t > k ? t : k;
    }
    bar_sync(1, 256);
    if ((tid & 31) == 0) red[tid >> 5] = k;
    bar_sync(1, 256);
    k = red[0];
#pragma unroll
    for (int i = 1; i < 8; i++) k = red[i] > k ? red[i] : k;
    return k;
}

constexpr int FS = FF / 4;
constexpr int FSTAGE = 32768, FNST = 6;
constexpr int FN1 = 2 * (DM / 16), FN2 = FS / 16;

__device__ __forceinline__ void ffn_producer(uint32_t sb, int s, const CUtensorMap* m_gate, const CUtensorMap* m_up,
                                             const CUtensorMap* m_down) {
    wait_counter(&g_sync.ln, (__ldcg(&g_sync.done) / NCTA + 1) * NMAIN);
    int slot = 0, ph = 1;
#pragma unroll 1
    for (int st = 0; st < FN1 + FN2; st++) {
        mbar_sleep(sb + BAR_EMPTY + slot * 8, ph);
        const uint32_t bar = sb + BAR_FULL + slot * 8;
        const bool up = st < FN1;
        mbar_expect_tx(bar, up ? FS * 32 : DM * 32);
        tma_3d_hint(sb + slot * FSTAGE, up ? ((st & 1) ? m_up : m_gate) : m_down, 0,
                    up ? (st >> 1) * 16 : s * FS + (st - FN1) * 16, up ? s * (FS / 64) : 0, bar, POL_FIRST);
        if (++slot == FNST) { slot = 0; ph ^= 1; }
    }
}

__device__ __forceinline__ void ffn_cta(uint8_t* smem, uint32_t sb, int s, unsigned epoch, const __nv_bfloat16* w_r) {
    const int tid = threadIdx.x, lane = tid & 31;
    const int warp = __shfl_sync(~0u, tid >> 5, 0), w = warp >> 2;
    constexpr uint32_t XB = FNST * FSTAGE, HB = XB + 16384, AUX = HB + 14336;
    unsigned long long* red = reinterpret_cast<unsigned long long*>(smem + AUX);
    unsigned* flag = reinterpret_cast<unsigned*>(smem + AUX + 128);
    const unsigned e1 = epoch + 1;
    for (int i = tid; i < (16384 + 14336) / 16; i += 256) reinterpret_cast<uint4*>(smem + XB)[i] = make_uint4(0, 0, 0, 0);
    {
        float wf[32];
#pragma unroll
        for (int i = 0; i < 4; i++) {
            const uint4 t = __ldg(reinterpret_cast<const uint4*>(w_r) + lane + 32 * i);
            const uint32_t tu[4] = {t.x, t.y, t.z, t.w};
#pragma unroll
            for (int k = 0; k < 4; k++) { wf[8 * i + 2 * k] = bf_lo(tu[k]); wf[8 * i + 2 * k + 1] = bf_hi(tu[k]); }
        }
        if (tid == 0) wait_counter(&g_sync.ln, e1 * NMAIN);
        bar_sync(1, 256);
#pragma unroll 1
        for (int r0 = s * (SEQ / 4) + warp * (SEQ / 32); r0 < s * (SEQ / 4) + (warp + 1) * (SEQ / 32); r0 += 4) {
            uint4 t[4][4];
#pragma unroll
            for (int r = 0; r < 4; r++)
#pragma unroll
                for (int i = 0; i < 4; i++) t[r][i] = __ldcg(reinterpret_cast<const uint4*>(g_xn + image_offset(r0 + r, lane) + i * 131072));
            float acc[4];
#pragma unroll
            for (int r = 0; r < 4; r++) {
                float a = 0.f, b = 0.f;
#pragma unroll
                for (int i = 0; i < 4; i++) {
                    const uint32_t tu[4] = {t[r][i].x, t[r][i].y, t[r][i].z, t[r][i].w};
#pragma unroll
                    for (int k = 0; k < 4; k++) {
                        a = fmaf(bf_lo(tu[k]), wf[8 * i + 2 * k], a);
                        b = fmaf(bf_hi(tu[k]), wf[8 * i + 2 * k + 1], b);
                    }
                }
                acc[r] = a + b;
            }
#pragma unroll
            for (int o = 16; o; o >>= 1)
#pragma unroll
                for (int r = 0; r < 4; r++) acc[r] += __shfl_xor_sync(~0u, acc[r], o);
            if (lane < 4) __stcg(&g_r[r0 + lane], bf_round(lane == 0 ? acc[0] : lane == 1 ? acc[1] : lane == 2 ? acc[2] : acc[3]));
        }
        __threadfence();
        bar_sync(1, 256);
        if (tid == 0) {
            red_release(&g_sync.router);
            wait_counter(&g_sync.router, e1 * 4);
        }
        bar_sync(1, 256);
    }
    unsigned long long keys[8];
    unsigned long long best = 0;
#pragma unroll
    for (int i = 0; i < 8; i++) {
        int idx = tid + 256 * i;
        uint32_t b = __float_as_uint(__ldcg(&g_r[idx]) + 0.0f);
        b = (b & 0x80000000u) ? ~b : (b | 0x80000000u);
        keys[i] = ((unsigned long long)b << 32) | (unsigned)(SEQ - 1 - idx);
        best = keys[i] > best ? keys[i] : best;
    }
    const unsigned long long k0 = block_max_key(best, red, tid);
    best = 0;
#pragma unroll
    for (int i = 0; i < 8; i++) best = (keys[i] != k0 && keys[i] > best) ? keys[i] : best;
    const unsigned long long k1 = block_max_key(best, red, tid);
    const int row = SEQ - 1 - (int)((w ? k1 : k0) & 0xffffffffu);
    const int ch = tid & 127;
    const uint4 xrow = __ldcg(reinterpret_cast<const uint4*>(g_xn + image_offset(row, ch)));
    *reinterpret_cast<uint4*>(smem + XB + (ch >> 3) * 1024 + w * 128 + (((ch & 7) ^ w) << 4)) = xrow;
    fence_async_smem();
    bar_sync(1, 256);
    PROF(20, tid >> 7);
    int slot = 0, ph = 0, prev = 0;
    auto next_stage = [&](bool has_prev) {
        wg_commit();
        wg_wait<1>();
        if (has_prev && lane < 2) mbar_arrive(sb + BAR_EMPTY + prev * 8);
        prev = slot;
        if (++slot == FNST) { slot = 0; ph ^= 1; }
    };
    {
        float ag[28], au[28];
#pragma unroll
        for (int i = 0; i < 28; i++) ag[i] = au[i] = 0.f;
#pragma unroll 1
        for (int ks = 0; ks < DM / 16; ks++) {
            const uint64_t db = make_desc(sb + XB + (ks >> 2) * 1024 + (ks & 3) * 32, 16);
            mbar_wait(sb + BAR_FULL + slot * 8, ph);
            uint64_t da = make_desc(sb + slot * FSTAGE + w * (7 * 2048), 16);
            wg_fence();
#pragma unroll
            for (int b = 0; b < 7; b++) wgmma_n8_ta(ag + 4 * b, da + b * 128, db);
            next_stage(ks > 0);
            mbar_wait(sb + BAR_FULL + slot * 8, ph);
            da = make_desc(sb + slot * FSTAGE + w * (7 * 2048), 16);
            wg_fence();
#pragma unroll
            for (int b = 0; b < 7; b++) wgmma_n8_ta(au + 4 * b, da + b * 128, db);
            next_stage(true);
        }
        wg_wait<0>();
        reg_fence(ag);
        reg_fence(au);
        if ((lane & 3) == 0) {
#pragma unroll
            for (int i = 0; i < 28; i++) {
                const int f = (warp & 3) * 16 + (lane >> 2) + (i & 2) * 4, tok = i & 1;
                const float h = bf_round(silu_f(bf_round(ag[i]))) * bf_round(au[i]);
                *reinterpret_cast<__nv_bfloat16*>(smem + HB + (w * 7 + (i >> 2)) * 1024 + tok * 128 + (((f >> 3) ^ tok) << 4) + (f & 7) * 2) =
                    __float2bfloat16_rn(h);
            }
        }
    }
    fence_async_smem();
    bar_sync(1, 256);
    PROF(21, tid >> 7);
    {
        float ay[32];
#pragma unroll
        for (int i = 0; i < 32; i++) ay[i] = 0.f;
#pragma unroll 1
        for (int ks = 0; ks < FN2; ks++) {
            const uint64_t db = make_desc(sb + HB + (ks >> 2) * 1024 + (ks & 3) * 32, 16);
            mbar_wait(sb + BAR_FULL + slot * 8, ph);
            const uint64_t da = make_desc(sb + slot * FSTAGE + w * (8 * 2048), 16);
            wg_fence();
#pragma unroll
            for (int b = 0; b < 8; b++) wgmma_n8_ta(ay + 4 * b, da + b * 128, db);
            next_stage(true);
        }
        wg_wait<0>();
        reg_fence(ay);
        if ((lane & 3) == 0) {
#pragma unroll
            for (int i = 0; i < 32; i++)
                g_ypart[(s * 2 + (i & 1)) * DM + (w * 8 + (i >> 2)) * 64 + (warp & 3) * 16 + (lane >> 2) + (i & 2) * 4] = ay[i];
        }
    }
    PROF(23, tid >> 7);
    __threadfence();
    bar_sync(1, 256);
    if (tid == 0) {
        *flag = atomicAdd(&g_sync.ffn_ticket, 1u) == epoch * 4 + 3;
        __threadfence();
    }
    bar_sync(1, 256);
    if (*flag) {
        const float sg = bf_round(__fdividef(1.0f, 1.0f + __expf(-__ldcg(&g_r[row]))));
        const uint32_t xu[4] = {xrow.x, xrow.y, xrow.z, xrow.w};
        uint32_t o[4];
#pragma unroll
        for (int k = 0; k < 4; k++) {
            float y0 = 0.f, y1 = 0.f;
#pragma unroll
            for (int q = 0; q < 4; q++) {
                const float2 y = __ldcg(reinterpret_cast<const float2*>(&g_ypart[(q * 2 + w) * DM + ch * 8 + 2 * k]));
                y0 += y.x; y1 += y.y;
            }
            o[k] = pack_bf16(bf_lo(xu[k]) + bf_round(bf_round(y0) * sg), bf_hi(xu[k]) + bf_round(bf_round(y1) * sg));
        }
        g_routed[w * 128 + ch] = make_uint4(o[0], o[1], o[2], o[3]);
        if (ch == 0) g_sel[w] = row;
        bar_sync(1, 256);
        if (tid == 0) red_release(&g_sync.ffn_done);
    }
}

__device__ __forceinline__ uint32_t slab_addr(uint32_t stg, int lane, int s) {
    const int row = ((lane >> 3) & 1) * 8 + (lane & 7);
    const int chunk = 2 * (s & 3) + (lane >> 4);
    return stg + row * 128 + (s >> 2) * 8192 + ((chunk ^ (lane & 7)) << 4);
}

constexpr float SM_SCALE = 0.08838834764831845f * 1.4426950408889634f;
constexpr float SUM_HI = 1048576.f, SUM_LO = 1.0f / 1048576.f;

template <int I0, int I1, int J0>
__device__ __forceinline__ void mask_range(float (&S)[64], float limf) {
#pragma unroll
    for (int i = I0; i < I1; i++) {
        const int j = i >> 2;
        float t;
        asm("add.sat.f32 %0, %1, %2;" : "=f"(t) : "f"((float)(32 * (j >> 2) + 2 * (j & 3) + (i & 1) - (i & 2) * 4)), "f"(-limf));
        S[4 * J0 + i] = fmaf(t, -1e30f, S[4 * J0 + i]);
    }
}
template <int J0>
__device__ __forceinline__ void mask_half(float (&S)[64], float limf, int v) {
    asm volatile("" : "+f"(limf));
    if (v < 2) {
        mask_range<0, 16, J0>(S, limf);
#pragma unroll
        for (int i = 16; i < 32; i++) S[4 * J0 + i] = -1e30f;
    } else {
        mask_range<16, 32, J0>(S, limf);
    }
}
__device__ __forceinline__ void issue_qk(float (&S)[64], const uint32_t (&Q)[32], uint32_t d0) {
#pragma unroll
    for (int s = 0; s < 8; s++)
        wgmma_n128_rs<1>(S, Q[4 * s], Q[4 * s + 1], Q[4 * s + 2], Q[4 * s + 3], d0 + s * 128, s > 0);
}
__device__ __forceinline__ void issue_qk_half(float (&T)[32], const uint32_t (&Q)[32], uint32_t d0) {
#pragma unroll
    for (int s = 0; s < 8; s++) wgmma_n64_rs_tb(T, Q[4 * s], Q[4 * s + 1], Q[4 * s + 2], Q[4 * s + 3], d0 + s * 128, s > 0);
}
template <int H>
__device__ __forceinline__ void issue_pv(float (&O)[64], const uint32_t (&Pm)[32], uint32_t d0, int acc) {
#pragma unroll
    for (int s = 4 * H; s < 4 * H + 4; s++)
        wgmma_n128_rs<0>(O, Pm[4 * s], Pm[4 * s + 1], Pm[4 * s + 2], Pm[4 * s + 3], d0 + H * (PAGE >> 4) + (s & 3) * 2, s > 0 ? 1 : acc);
}
template <int J0, int J1>
__device__ __forceinline__ void exp_groups(const float (&S)[64], uint32_t (&Pm)[32], float (&sum)[2]) {
#pragma unroll
    for (int i = 2 * J0; i < 2 * J1; i++) asm volatile("" : "+r"(Pm[i])::"memory");
#pragma unroll
    for (int j = J0; j < J1; j++) {
        const float e0 = ex2(S[4 * j]), e1 = ex2(S[4 * j + 1]), e2 = ex2(S[4 * j + 2]), e3 = ex2(S[4 * j + 3]);
        sum[0] = (j ? sum[0] + e0 : e0) + e1;
        sum[1] = (j ? sum[1] + e2 : e2) + e3;
        Pm[2 * j] = pack_bf16(e0, e1);
        Pm[2 * j + 1] = pack_bf16(e2, e3);
    }
}
__device__ __forceinline__ void shift_rows(float (&S)[64], float d0, float d1) {
#pragma unroll
    for (int j = 0; j < 16; j++) {
        S[4 * j] -= d0; S[4 * j + 1] -= d0; S[4 * j + 2] -= d1; S[4 * j + 3] -= d1;
    }
}
__device__ constexpr int chunk_src(int i) { return 4 * (4 * (i >> 3) + (i & 3)) + 2 * ((i >> 2) & 1); }
enum : uint32_t { CTL_FIRST = 1, CTL_SWITCH = 2, CTL_LAST = 4, CTL_HALF = 128, CTL_MASKHI = 256, CTL_WOUT = 512, CTL_PVHALF = 1024, CTL_PVACC = 16384,
                  CTL_SHIFT = 32768 };
__device__ __forceinline__ float quad_sum(float v) {
    v += __shfl_xor_sync(~0u, v, 1);
    return v + __shfl_xor_sync(~0u, v, 2);
}

__device__ __forceinline__ void store_part(uint8_t* base, uint32_t row_bits, int p, const uint32_t (&pk)[64], uint64_t pol) {
    asm volatile("{\n.reg .b64 d0, d1;\nxor.b64 d0, %0, %1;\nxor.b64 d1, d0, 64;\n"
                 "TS: .branchtargets P0, P1, P2, P3, P4, P5, P6, P7;\n"
                 "brx.idx.uni %2, TS;\n"
                 "P0:\n st.global.cg.L2::cache_hint.v4.u32 [d0 + 0], {%3, %4, %5, %6}, %67;\n st.global.cg.L2::cache_hint.v4.u32 [d1 + 0], {%11, %12, %13, %14}, %67;\n bra.uni DONE;\n"
                 "P1:\n st.global.cg.L2::cache_hint.v4.u32 [d0 + 0], {%7, %8, %9, %10}, %67;\n st.global.cg.L2::cache_hint.v4.u32 [d1 + 0], {%15, %16, %17, %18}, %67;\n bra.uni DONE;\n"
                 "P2:\n st.global.cg.L2::cache_hint.v4.u32 [d0 + 16384], {%19, %20, %21, %22}, %67;\n st.global.cg.L2::cache_hint.v4.u32 [d1 + 16384], {%27, %28, %29, %30}, %67;\n bra.uni DONE;\n"
                 "P3:\n st.global.cg.L2::cache_hint.v4.u32 [d0 + 16384], {%23, %24, %25, %26}, %67;\n st.global.cg.L2::cache_hint.v4.u32 [d1 + 16384], {%31, %32, %33, %34}, %67;\n bra.uni DONE;\n"
                 "P4:\n st.global.cg.L2::cache_hint.v4.u32 [d0 + 65536], {%35, %36, %37, %38}, %67;\n st.global.cg.L2::cache_hint.v4.u32 [d1 + 65536], {%43, %44, %45, %46}, %67;\n bra.uni DONE;\n"
                 "P5:\n st.global.cg.L2::cache_hint.v4.u32 [d0 + 65536], {%39, %40, %41, %42}, %67;\n st.global.cg.L2::cache_hint.v4.u32 [d1 + 65536], {%47, %48, %49, %50}, %67;\n bra.uni DONE;\n"
                 "P6:\n st.global.cg.L2::cache_hint.v4.u32 [d0 + 81920], {%51, %52, %53, %54}, %67;\n st.global.cg.L2::cache_hint.v4.u32 [d1 + 81920], {%59, %60, %61, %62}, %67;\n bra.uni DONE;\n"
                 "P7:\n st.global.cg.L2::cache_hint.v4.u32 [d0 + 81920], {%55, %56, %57, %58}, %67;\n st.global.cg.L2::cache_hint.v4.u32 [d1 + 81920], {%63, %64, %65, %66}, %67;\n bra.uni DONE;\n"
                 "DONE:\n}\n"
                 ::"l"(base), "l"((uint64_t)((p & 1) ? row_bits : 0)), "r"(p), "r"(pk[0]), "r"(pk[1]), "r"(pk[2]), "r"(pk[3]), "r"(pk[4]), "r"(pk[5]), "r"(pk[6]), "r"(pk[7]), "r"(pk[8]), "r"(pk[9]), "r"(pk[10]), "r"(pk[11]), "r"(pk[12]), "r"(pk[13]), "r"(pk[14]), "r"(pk[15]), "r"(pk[16]), "r"(pk[17]), "r"(pk[18]), "r"(pk[19]), "r"(pk[20]), "r"(pk[21]), "r"(pk[22]), "r"(pk[23]), "r"(pk[24]), "r"(pk[25]), "r"(pk[26]), "r"(pk[27]), "r"(pk[28]), "r"(pk[29]), "r"(pk[30]), "r"(pk[31]), "r"(pk[32]), "r"(pk[33]), "r"(pk[34]), "r"(pk[35]), "r"(pk[36]), "r"(pk[37]), "r"(pk[38]), "r"(pk[39]), "r"(pk[40]), "r"(pk[41]), "r"(pk[42]), "r"(pk[43]), "r"(pk[44]), "r"(pk[45]), "r"(pk[46]), "r"(pk[47]), "r"(pk[48]), "r"(pk[49]), "r"(pk[50]), "r"(pk[51]), "r"(pk[52]), "r"(pk[53]), "r"(pk[54]), "r"(pk[55]), "r"(pk[56]), "r"(pk[57]), "r"(pk[58]), "r"(pk[59]), "r"(pk[60]), "r"(pk[61]), "r"(pk[62]), "r"(pk[63]), "l"(pol)
                 : "memory");
}

__device__ __forceinline__ void store_part4(uint8_t* d0, int p, const uint32_t (&pk)[64]) {
    asm volatile("{\n.reg .b64 d1;\nxor.b64 d1, %0, 64;\n"
                 "TS: .branchtargets P0, P1, P2, P3;\n"
                 "brx.idx.uni %1, TS;\n"
                 "P0:\n st.global.cg.v4.u32 [%0 + 0], {%2, %3, %4, %5};\n st.global.cg.v4.u32 [d1 + 0], {%10, %11, %12, %13};\n bra.uni DONE;\n"
                 "P1:\n st.global.cg.v4.u32 [%0 + 1024], {%6, %7, %8, %9};\n st.global.cg.v4.u32 [d1 + 1024], {%14, %15, %16, %17};\n bra.uni DONE;\n"
                 "P2:\n st.global.cg.v4.u32 [%0 + 16384], {%18, %19, %20, %21};\n st.global.cg.v4.u32 [d1 + 16384], {%26, %27, %28, %29};\n bra.uni DONE;\n"
                 "P3:\n st.global.cg.v4.u32 [%0 + 17408], {%22, %23, %24, %25};\n st.global.cg.v4.u32 [d1 + 17408], {%30, %31, %32, %33};\n bra.uni DONE;\n"
                 "DONE:\n}\n"
                 ::"l"(d0), "r"(p), "r"(pk[0]), "r"(pk[1]), "r"(pk[2]), "r"(pk[3]), "r"(pk[4]), "r"(pk[5]), "r"(pk[6]), "r"(pk[7]), "r"(pk[8]), "r"(pk[9]), "r"(pk[10]), "r"(pk[11]), "r"(pk[12]), "r"(pk[13]), "r"(pk[14]), "r"(pk[15]), "r"(pk[16]), "r"(pk[17]), "r"(pk[18]), "r"(pk[19]), "r"(pk[20]), "r"(pk[21]), "r"(pk[22]), "r"(pk[23]), "r"(pk[24]), "r"(pk[25]), "r"(pk[26]), "r"(pk[27]), "r"(pk[28]), "r"(pk[29]), "r"(pk[30]), "r"(pk[31])
                 : "memory");
}

__device__ __forceinline__ void consumer(uint32_t sb, int pair, int c, uint8_t* out, const uint8_t* x) {
    const int tid = threadIdx.x;
    const int warp = __shfl_sync(~0u, tid >> 5, 0);
    const int w = warp >> 2, v = warp & 3;
    const int lane = __shfl_sync(~0u, tid & 31, tid & 31);

    const uint32_t empty_rel = lane == 2 ? mapa(sb + BAR_EMPTYL, c) : mapa(sb + BAR_EMPTY, lane & 1);
    auto release = [&](uint32_t grp) {
        if (lane < 3) mbar_arrive_cluster(empty_rel + (grp & 7) * 8);
    };
    auto wait_full = [&](uint32_t grp) { mbar_wait(sb + BAR_FULL + (grp & 7) * 8, (grp >> 3) & 1); };

    uint32_t g = 0;
    const uint32_t stg = sb + SM_REGION + w * PAGE + v * 2048;
    const uint32_t chunk0 = (lane >> 2) * 128 + (((lane & 3) ^ (lane >> 2)) << 4);
    uint32_t ndone = 0;
    auto mark_done = [&]() {
        __syncwarp();
        if (lane == 0) mbar_arrive(sb + BAR_DONE + (ndone & 1) * 8);
        ndone++;
    };
    auto ctx_dst = [&](int rnd, int seg) {
        const int rb = query_rowblock(pair, c, w, seg);
        return ptr_off(g_ctx, ((rb >> 1) * 64 + (rnd * 16 + (pair >> 2)) * 2) * PAGE + (rb & 1) * 8192 + v * 2048);
    };

    uint32_t ctl_tab;
    {
        const int t = lane, firstB = 2 * attn_rowblock(pair, 0) + 2 - w;
        auto is_half = [&](int u) { return (u == firstB - 1 || u == 16) && c == (u >= firstB); };
        auto block = [&](int u) { return u + (w == 1 && u >= firstB); };
        auto place = [](int j) { return ((j & 15) << 3) | ((j - (j * 43 >> 8) * 6) << 11); };
        const int jv = min(2 * block(t - 1) + 2, 35), jk = t == 17 ? jv : max(2 * block(t) - 1, 0);
        const bool diag = t == firstB - 1 || t == 16;
        ctl_tab = ((t == 0 || t == firstB) ? CTL_FIRST : 0) | (t == firstB ? CTL_SWITCH : 0) | (t == 17 ? CTL_LAST : 0) |
                  (diag ? (is_half(t) ? CTL_HALF : CTL_MASKHI) : 0) | (t == firstB + 1 ? CTL_WOUT : 0) |
                  (is_half(t - 1) ? CTL_PVHALF : 0) | ((t == 1 || t == firstB + 1) ? 0 : CTL_PVACC) |
                  place(jk) | ((place(jv) | (t ? 3 : 0)) << 16);
    }

    uint32_t pk[64];
#pragma unroll
    for (int i = 0; i < 64; i++) pk[i] = 0;
    uint8_t* pend = nullptr;
    uint32_t prow = 0x400;
    auto write_part = [&](int p, uint64_t pol = POL_NORMAL) { store_part(pend, prow, p, pk, pol); };
    if (w == 1) bar_arrive(2, 256);

    for (int item = 0; item < 6; item++) {
        if ((0x1B >> item) & 1) {
            constexpr int nk = DC / 64;
            float acc[128];
            auto issue_kblock = [&](int first_acc) {
                wait_full(g);
                const uint32_t pg = sb + (g & 3) * (3 * PAGE);
                const uint64_t da = make_desc(pg + w * 8192, 16), db = make_desc(pg + PAGE, 16);
                wg_fence();
                wgmma_n256_ss(acc, da, db, first_acc);
                wgmma_n256_ss(acc, da + 128, db + 2, 1);
                wgmma_n256_ss(acc, da + 256, db + 4, 1);
                wgmma_n256_ss(acc, da + 384, db + 6, 1);
                wg_commit();
                g++;
            };
            if (item == 0) PROF(17, w);
            issue_kblock(0);
            if (item == 0) PROF(1, w);
            if (item == 0 && w == 0) PROF_GT(1);
            const int nparts = item == 0 ? 0 : (item == 3 ? 4 : 8);
            const int ln_row = (pair * 2 + c) * 16 + warp * 2;
            if (item == 0) {
                const uint8_t* src = ptr_off(x, ln_row * (DM * 2) + lane * 16);
#pragma unroll
                for (int i = 0; i < 8; i++) {
                    const uint4 t = __ldcg(reinterpret_cast<const uint4*>(src + i * 512));
                    pk[4 * i] = t.x; pk[4 * i + 1] = t.y; pk[4 * i + 2] = t.z; pk[4 * i + 3] = t.w;
                }
            }
#pragma unroll 1
            for (int kb = 1; kb < nk; kb++) {
                if (kb == nk - 1 && w == 1) bar_sync(4, 256);
                issue_kblock(1);
                if (kb == nk - 1 && w == 0) bar_arrive(4, 256);
                wg_wait<1>();
                release(g - 2);
                if (kb <= nparts) {
                    if (item == 4 && kb == 1) mbar_wait(sb + BAR_DEP + 16, 0);
                    write_part(kb - 1, item == 3 ? POL_FIRST : POL_NORMAL);
                    if (kb == nk - 1) write_part(nk - 1);
                    if (kb == nparts || kb == nk - 1) mark_done();
                }
                if (g <= 8) {
                    float s[2], q[2];
                    if (g == 4) {
                        ln_sums<0>(pk, s[0], q[0]);
                        pk[32] = __float_as_uint(s[0]); pk[33] = __float_as_uint(q[0]);
                    }
                    if (g == 5) {
                        ln_sums<16>(pk, s[1], q[1]);
                        pk[34] = __float_as_uint(s[1]); pk[35] = __float_as_uint(q[1]);
                    }
                    if (g == 6) {
#pragma unroll
                        for (int r = 0; r < 2; r++) { s[r] = __uint_as_float(pk[32 + 2 * r]); q[r] = __uint_as_float(pk[33 + 2 * r]); }
                        const bool hi = lane & 16, od = lane & 8;
                        float a = hi ? s[1] : s[0], b = hi ? q[1] : q[0];
                        a += __shfl_xor_sync(~0u, hi ? s[0] : s[1], 16);
                        b += __shfl_xor_sync(~0u, hi ? q[0] : q[1], 16);
                        float t = od ? b : a;
                        t += __shfl_xor_sync(~0u, od ? a : b, 8);
#pragma unroll
                        for (int o = 4; o; o >>= 1) t += __shfl_xor_sync(~0u, t, o);
#pragma unroll
                        for (int r = 0; r < 2; r++) {
                            s[r] = __shfl_sync(~0u, t, 16 * r);
                            q[r] = __shfl_sync(~0u, t, 16 * r + 8);
                        }
                        ln_finish(s[0], q[0], pk[36], pk[37], pk[38]);
                        ln_finish(s[1], q[1], pk[39], pk[40], pk[41]);
                    }
                    if (g == 7) ln_apply<0>(pk, pk[36], pk[37], pk[38], ptr_off(g_xn, image_offset(ln_row, lane)));
                    if (g == 8) {
                        ln_apply<16>(pk, pk[39], pk[40], pk[41], ptr_off(g_xn, image_offset(ln_row + 1, lane)));
                        mark_done();
                    }
                }
            }
            wg_wait<0>();
            reg_fence(acc);
            release(g - 1);
            PROF(2 + 2 * item, w);
            if (w == 0) PROF_GT(2 + 2 * item);
#pragma unroll
            for (int i = 0; i < 64; i++) pk[i] = pack_bf16(acc[chunk_src(i)], acc[chunk_src(i) + 1]);
            const uint32_t vrow = (v >> 1) * 32 + (lane >> 3) * 8 + (v & 1) * 4 + ((lane >> 2) & 1);
            pend = ptr_off(g_kv, ((kv_head(pair) + (item == 1 || item == 4 ? 8 : 0)) * 16 + kv_tokens(pair) * 2) * 65536 + w * 8192 +
                                     (c ? 32768 + vrow * 128 + (((lane & 3) ^ (vrow & 7)) << 4) : v * 2048 + chunk0));
            prow = c ? 0x120 : 0x400;
            PROF(3 + 2 * item, w);
            continue;
        }

        float O[64], S[64];
        auto issue_q = [&](int first_acc) {
            wait_full(g);
            const uint32_t pg = sb + (g & 3) * (3 * PAGE);
            const uint64_t da = make_desc(pg + w * 8192, 16), db = make_desc(pg + 2 * PAGE, 8192);
            const uint64_t dab = make_desc(pg + PAGE + (1 - w) * 8192, 16);
            wg_fence();
#pragma unroll
            for (int q = 0; q < 4; q++) wgmma_n128_ss(S, da + 2 * q, db + 128 * q, q ? 1 : first_acc);
            wg_commit();
#pragma unroll
            for (int q = 0; q < 4; q++) wgmma_n128_ss(O, dab + 2 * q, db + 128 * q, q ? 1 : first_acc);
            wg_commit();
            g++;
        };
        issue_q(0);
#pragma unroll 1
        for (int kb = 1; kb < DM / 64; kb++) {
            if (kb == DM / 64 - 2 && w == 1) bar_sync(4, 256);
            issue_q(1);
            if (kb == DM / 64 - 1 && w == 0) bar_arrive(4, 256);
            wg_wait<2>();
            release(g - 2);
            if (kb <= 8) {
                write_part(kb - 1);
                if (kb == 8) mark_done();
            }
        }
        uint32_t Q[32], Pm[32];
#pragma unroll
        for (int i = 0; i < 32; i++) Pm[i] = pk[i];
        float lim = (float)(v * 16 + (lane >> 2) - 8 * (lane & 3));
        float mc[2] = {0.f, 0.f}, l[2] = {0.f, 0.f}, scale[2] = {0.f, 0.f}, sum[2];
        uint32_t ctl = __shfl_sync(~0u, ctl_tab, 0), nxt = __shfl_sync(~0u, ctl_tab, 1);
        int t = 1;
        asm volatile("" : "+f"(lim), "+f"(mc[0]), "+f"(mc[1]), "+f"(l[0]), "+f"(l[1]), "+r"(ctl), "+r"(nxt), "+r"(t));
        wg_wait<1>();
        reg_fence(S);
#pragma unroll
        for (int i = 0; i < 32; i++) Q[i] = pack_bf16(S[2 * i] * SM_SCALE, S[2 * i + 1] * SM_SCALE);
        reg_fence(Q);
        wait_full(g);
        wg_wait<0>();
        reg_fence(O);
        release(g - 1);
        PROF(2 + 2 * item, w);
        if (w == 0) PROF_GT(2 + 2 * item);

        const uint32_t qaddr = stg + lane * 16;
        auto put_queries = [&](const float (&A)[64]) {
#pragma unroll
            for (int i = 0; i < 8; i++)
                sts128(qaddr + (i >> 2) * 8192 + (i & 3) * 512, pack_bf16(A[8 * i] * SM_SCALE, A[8 * i + 1] * SM_SCALE), pack_bf16(A[8 * i + 2] * SM_SCALE, A[8 * i + 3] * SM_SCALE),
                       pack_bf16(A[8 * i + 4] * SM_SCALE, A[8 * i + 5] * SM_SCALE), pack_bf16(A[8 * i + 6] * SM_SCALE, A[8 * i + 7] * SM_SCALE));
        };
        auto get_queries = [&]() {
#pragma unroll
            for (int i = 0; i < 8; i++) lds128(qaddr + (i >> 2) * 8192 + (i & 3) * 512, Q[4 * i], Q[4 * i + 1], Q[4 * i + 2], Q[4 * i + 3]);
        };
        const uint32_t kdesc0 = (uint32_t)make_desc(sb, PAGE), vdesc0 = (uint32_t)make_desc(sb, 16);
        auto wait_block = [&](uint32_t word) { mbar_wait(sb + BAR_FULL + (word & 56), (word >> 6) & 1); };
        auto write_out = [&](auto early) {
            uint8_t* dst = ctx_dst(item == 5, 0);
            uint8_t* d[2] = {ptr_off(dst, chunk0), ptr_off(dst, chunk0 ^ 64)};
#pragma unroll
            for (int i = early.value ? 0 : WN; i < (early.value ? WN : 8); i++) {
                const float sc = scale[i & 1];
                uint32_t q[4];
#pragma unroll
                for (int k = 0; k < 4; k++) q[k] = pack_bf16(O[chunk_src(4 * i + k)] * sc, O[chunk_src(4 * i + k) + 1] * sc);
                if (early.value && i > 0) {
#pragma unroll
                    for (int k = 0; k < 4; k++) O[4 * (i - 1) + k] = __uint_as_float(q[k]);
                }
                stg_hint(d[(i >> 1) & 1] + (i >> 2) * PAGE + (i & 1) * 1024, q[0], q[1], q[2], q[3], item == 2 ? POL_FIRST : POL_NORMAL);
            }
            if (!early.value) mark_done();
        };
        put_queries(O);
        bar_sync(2 + w, 256);
        if (!(ctl & CTL_HALF)) {
            wg_fence();
            issue_qk(S, Q, kdesc0);
            wg_commit();
            wg_fence();
            wg_commit();
            wg_commit();
            bar_arrive(3 - w, 256);
            wg_wait<2>();
            reg_fence(S);
        } else {
            float T[32];
            wg_fence();
            issue_qk_half(T, Q, kdesc0);
            wg_commit();
            wg_fence();
            wg_commit();
            wg_commit();
            bar_arrive(3 - w, 256);
            wg_wait<2>();
            reg_fence(T);
#pragma unroll
            for (int i = 0; i < 32; i++) S[i] = T[i];
        }
        for (;;) {
            const bool kready = mbar_try(sb + BAR_FULL + (nxt & 56), (nxt >> 6) & 1);
            if (ctl & (CTL_HALF | CTL_MASKHI | CTL_SHIFT)) {
                if (ctl & CTL_HALF) mask_half<0>(S, lim, v);
                if (ctl & CTL_MASKHI) mask_half<8>(S, lim, v);
                if (ctl & CTL_SHIFT) shift_rows(S, mc[0], mc[1]);
            }
            float early[4 * EARLY];
#pragma unroll
            for (int j = 0; j < EARLY; j++) {
#pragma unroll
                for (int i = 4 * j; i < 4 * j + 4; i++) early[i] = ex2(S[i]);
                sum[0] = (j ? sum[0] + early[4 * j] : early[4 * j]) + early[4 * j + 1];
                sum[1] = (j ? sum[1] + early[4 * j + 2] : early[4 * j + 2]) + early[4 * j + 3];
            }
            const uint32_t tie = __float_as_uint(sum[0]) & __float_as_uint(sum[1]) & (ctl & 0x80000000u);
            if (lane < 3) mbar_arrive_cluster(empty_rel + tie + (ctl & 56));
            wg_wait<1>();
#pragma unroll
            for (int j = 0; j < EARLY; j++) {
                asm volatile("" : "+r"(Pm[2 * j]), "+r"(Pm[2 * j + 1])::"memory");
                Pm[2 * j] = pack_bf16(early[4 * j], early[4 * j + 1]);
                Pm[2 * j + 1] = pack_bf16(early[4 * j + 2], early[4 * j + 3]);
            }
            exp_groups<EARLY, 8>(S, Pm, sum);
            const bool half = ctl & CTL_HALF;
            if (!half) {
                wg_wait<0>();
                reg_fence(O);
                if (lane < ((ctl >> 16) & 3)) mbar_arrive_cluster(empty_rel + ((ctl >> 16) & 56));
                exp_groups<8, 16>(S, Pm, sum);
            } else {
                asm volatile("wgmma.wait_group.sync.aligned 0;\n" ::: "memory");
                reg_fence(O);
                if (lane < ((ctl >> 16) & 3)) asm volatile("mbarrier.arrive.shared::cluster.b64 _, [%0];\n" ::"r"(empty_rel + ((ctl >> 16) & 56)) : "memory");
            }
            const bool over = !(sum[0] + sum[1] <= SUM_HI);
            if (__any_sync(~0u, over || !kready) || (((ctl & CTL_FIRST) | (nxt & (CTL_SWITCH | CTL_LAST | CTL_HALF))) != 0)) {
                bool bad = __any_sync(~0u, over);
                if (!kready) wait_block(nxt);
                const bool first = ctl & CTL_FIRST;
                if (first) {
                    uint32_t b0 = __ballot_sync(~0u, sum[0] >= SUM_LO), b1 = __ballot_sync(~0u, sum[1] >= SUM_LO);
                    b0 |= b0 >> 1; b1 |= b1 >> 1;
                    b0 |= b0 >> 2; b1 |= b1 >> 2;
                    bad |= (b0 & b1 & 0x11111111u) != 0x11111111u;
                }
                if (bad) {
                    float d0 = fmaxf(S[0], S[1]), d1 = fmaxf(S[2], S[3]);
#pragma unroll
                    for (int j = 1; j < 8; j++) {
                        d0 = fmaxf(d0, fmaxf(S[4 * j], S[4 * j + 1]));
                        d1 = fmaxf(d1, fmaxf(S[4 * j + 2], S[4 * j + 3]));
                    }
                    if (!half) {
#pragma unroll
                        for (int j = 8; j < 16; j++) {
                            d0 = fmaxf(d0, fmaxf(S[4 * j], S[4 * j + 1]));
                            d1 = fmaxf(d1, fmaxf(S[4 * j + 2], S[4 * j + 3]));
                        }
                    }
                    d0 = fmaxf(d0, __shfl_xor_sync(~0u, d0, 1));
                    d1 = fmaxf(d1, __shfl_xor_sync(~0u, d1, 1));
                    d0 = fmaxf(d0, __shfl_xor_sync(~0u, d0, 2));
                    d1 = fmaxf(d1, __shfl_xor_sync(~0u, d1, 2));
                    if (!first) {
                        d0 = fmaxf(d0, 0.f);
                        d1 = fmaxf(d1, 0.f);
                        const float a0 = ex2(-d0), a1 = ex2(-d1);
#pragma unroll
                        for (int j = 0; j < 16; j++) {
                            O[4 * j] *= a0; O[4 * j + 1] *= a0; O[4 * j + 2] *= a1; O[4 * j + 3] *= a1;
                        }
                        l[0] *= a0; l[1] *= a1;
                    }
                    mc[0] += d0; mc[1] += d1;
                    ctl_tab |= CTL_SHIFT;
                    nxt |= CTL_SHIFT;
                    shift_rows(S, d0, d1);
                    exp_groups<0, 8>(S, Pm, sum);
                    if (!half) exp_groups<8, 16>(S, Pm, sum);
                }
                if (ctl & CTL_SWITCH) write_out(std::true_type());
                if (nxt & CTL_LAST) break;
                if (nxt & CTL_SWITCH) {
                    get_queries();
                    nxt &= ~CTL_SHIFT;
                    ctl_tab &= ~CTL_SHIFT;
                }
                if (nxt & CTL_HALF) {
                    ctl = nxt;
                    float T[32];
                    bar_sync(2 + w, 256);
                    wg_fence();
                    issue_qk_half(T, Q, kdesc0 + (ctl & 0x3800));
                    wg_commit();
                    l[0] += sum[0]; l[1] += sum[1];
                    nxt = __shfl_sync(~0u, ctl_tab, ++t);
                    wait_block(ctl >> 16);
                    const uint32_t vdesc = vdesc0 + ((ctl >> 16) & 0x3800);
                    wg_fence();
                    issue_pv<0>(O, Pm, vdesc, ctl & CTL_PVACC);
                    wg_commit();
                    issue_pv<1>(O, Pm, vdesc, 1);
                    wg_commit();
                    bar_arrive(3 - w, 256);
                    wg_wait<2>();
                    reg_fence(T);
#pragma unroll
                    for (int i = 0; i < 32; i++) S[i] = T[i];
                    continue;
                }
            }
            ctl = nxt;
            bar_sync(2 + w, 256);
            wg_fence();
            issue_qk(S, Q, kdesc0 + (ctl & 0x3800));
            wg_commit();
            l[0] += sum[0]; l[1] += sum[1];
            nxt = __shfl_sync(~0u, ctl_tab, ++t);
            if (ctl & (CTL_SWITCH | CTL_WOUT)) {
                if (ctl & CTL_SWITCH) {
                    scale[0] = rcp_approx(quad_sum(l[0]));
                    scale[1] = rcp_approx(quad_sum(l[1]));
                    l[0] = l[1] = mc[0] = mc[1] = 0.f;
                    if (w == 1) { release((ctl >> 3) - 2); release((ctl >> 3) + 1); }
                } else {
                    write_out(std::false_type());
                }
            }
            wait_block(ctl >> 16);
            const uint32_t vdesc = vdesc0 + ((ctl >> 16) & 0x3800);
            if (!(ctl & CTL_PVHALF)) {
                wg_fence();
                issue_pv<0>(O, Pm, vdesc, ctl & CTL_PVACC);
                wg_commit();
                issue_pv<1>(O, Pm, vdesc, 1);
                wg_commit();
            } else {
                wg_fence();
                issue_pv<0>(O, Pm, vdesc, ctl & CTL_PVACC);
                wg_commit();
                wg_commit();
            }
            bar_arrive(3 - w, 256);
            wg_wait<2>();
            reg_fence(S);
        }
        g += 36;
        if (w == 0) release(g - 3);
        const uint32_t vdesc = vdesc0 + (nxt & 0x3800);
        if (nxt & CTL_PVHALF) {
            wg_fence();
            issue_pv<0>(O, Pm, vdesc, nxt & CTL_PVACC);
            wg_commit();
        } else {
            wg_fence();
            issue_pv<0>(O, Pm, vdesc, nxt & CTL_PVACC);
            issue_pv<1>(O, Pm, vdesc, 1);
            wg_commit();
        }
        l[0] += sum[0]; l[1] += sum[1];
        ctl_tab = (ctl_tab & ~(0x00780078u | CTL_SHIFT)) | ((ctl_tab + 0x00200020u) & 0x00780078u);
        const float i0 = rcp_approx(quad_sum(l[0])), i1 = rcp_approx(quad_sum(l[1]));
        wg_wait<0>();
        reg_fence(O);
        if (w == 0) release(g - 2);
        release(g - 1);
#pragma unroll
        for (int i = 0; i < 32; i++) {
            const float sc = (i & 4) ? i1 : i0;
            pk[i] = pack_bf16(O[chunk_src(i)] * sc, O[chunk_src(i) + 1] * sc);
        }
        pend = ptr_off(ctx_dst(item == 5, 1), chunk0);
        prow = 0x400;
#pragma unroll
        for (int i = 32; i < 64; i++) pk[i] = 0;
        PROF(3 + 2 * item, w);
        if (w == 0) PROF_GT(3 + 2 * item);
    }

    float acc[64];
    uint32_t slot = 0;
    auto issue_out = [&](int first_acc) {
        wait_full(g);
        const uint64_t da = make_desc(sb + slot + w * 8192, 16), db = make_desc(sb + slot + PAGE, 8192);
        wg_fence();
#pragma unroll
        for (int q = 0; q < 4; q++) wgmma_n128_ss(acc, da + 2 * q, db + 128 * q, q ? 1 : first_acc);
        wg_commit();
        g++;
        slot = slot == SM_REGION - 2 * PAGE ? 0 : slot + 2 * PAGE;
    };
    issue_out(0);
#pragma unroll 1
    for (int kb = 1; kb < 64 - PEEL; kb++) {
        issue_out(1);
        wg_wait<1>();
        release(g - 2);
        if (kb <= 8 && !(kb & 1)) {
            store_part4(pend, (kb >> 1) - 1, pk);
            if (kb == 8) mark_done();
        }
        if (kb >= 32 - PEEL && ((kb + PEEL) & 3) == 2 * w) {
            uint32_t u0, u1, u2, u3;
            const uint32_t a = stg + ((kb + PEEL) & 16) * 512 + ((kb + PEEL) & 12) * 128 + lane * 16;
            mbar_wait(sb + BAR_G + w * 8, 0);
            lds128(a, u0, u1, u2, u3);
            sts128(a, pack_bf16(silu_f(bf_lo(u0)), silu_f(bf_hi(u0))), pack_bf16(silu_f(bf_lo(u1)), silu_f(bf_hi(u1))),
                   pack_bf16(silu_f(bf_lo(u2)), silu_f(bf_hi(u2))), pack_bf16(silu_f(bf_lo(u3)), silu_f(bf_hi(u3))));
        }
    }
    const uint32_t goff = (out_rows(pair) * 256 + c * 128 + w * 64 + v * 16 + (lane >> 3)) * (DM * 2) +
                          out_cols(pair) * 128 + (((lane & 7) ^ (lane >> 3)) << 4);
    uint32_t xr[32], gr[32];
    {
        const uint8_t* src[2] = {ptr_off(x, goff), ptr_off(x, goff ^ 64)};
#pragma unroll
        for (int i = 0; i < 8; i++) {
            const uint4 t = ldg_hint(src[i & 1] + (i & 3) * (4 * DM * 2) + (i >> 2) * 128, POL_FIRST);
            xr[4 * i] = t.x; xr[4 * i + 1] = t.y; xr[4 * i + 2] = t.z; xr[4 * i + 3] = t.w;
        }
    }
#pragma unroll 1
    for (int i = 0; i < PEEL; i++) {
        if (i == PEEL - STAG && w == 1) bar_sync(4, 256);
        issue_out(1);
        if (i == PEEL - 1 && w == 0) bar_arrive(4, 256);
        wg_wait<1>();
    }
    asm volatile("barrier.cluster.arrive.relaxed.aligned;" ::: "memory");
#pragma unroll
    for (int i = 0; i < 8; i++) lds128(stg + (i >> 2) * 8192 + (i & 3) * 512 + lane * 16, gr[4 * i], gr[4 * i + 1], gr[4 * i + 2], gr[4 * i + 3]);
    uint8_t* dst[2] = {ptr_off(out, goff), ptr_off(out, goff ^ 64)};
    __syncwarp();
    wg_wait<0>();
    reg_fence(acc);
    PROF(14, w);
    if (w == 0) PROF_GT(14);
#pragma unroll
    for (int s = 0; s < 8; s++)
        stmatrix_x4(slab_addr(stg, lane, s), pack_bf16(acc[8 * s], acc[8 * s + 1]), pack_bf16(acc[8 * s + 2], acc[8 * s + 3]),
                    pack_bf16(acc[8 * s + 4], acc[8 * s + 5]), pack_bf16(acc[8 * s + 6], acc[8 * s + 7]));
    __syncwarp();
    uint32_t o[32];
#pragma unroll
    for (int i = 0; i < 8; i++) lds128(stg + (i >> 2) * 8192 + (i & 3) * 512 + lane * 16, o[4 * i], o[4 * i + 1], o[4 * i + 2], o[4 * i + 3]);
#pragma unroll
    for (int i = 0; i < 8; i++) {
#pragma unroll
        for (int k = 0; k < 4; k++) xr[4 * i + k] = bf2_add(xr[4 * i + k], bf2_mul(o[4 * i + k], gr[4 * i + k]));
        __stcg(reinterpret_cast<uint4*>(dst[i & 1] + (i & 3) * (4 * DM * 2) + (i >> 2) * 128), make_uint4(xr[4 * i], xr[4 * i + 1], xr[4 * i + 2], xr[4 * i + 3]));
    }
    PROF(28, w);
}

__global__ void __cluster_dims__(2, 1, 1) __launch_bounds__(384, 1)
fused_kernel(const __grid_constant__ CUtensorMap m_ckv, const __grid_constant__ CUtensorMap m_wuk,
             const __grid_constant__ CUtensorMap m_wuv, const __grid_constant__ CUtensorMap m_wq,
             const __grid_constant__ CUtensorMap m_wo, const __grid_constant__ CUtensorMap m_gate,
             const __grid_constant__ CUtensorMap m_up, const __grid_constant__ CUtensorMap m_down, const Params P) {
    extern __shared__ __align__(1024) uint8_t smem[];
    const uint32_t sb = __shfl_sync(~0u, smem_u32(smem), 0);
    const int tid = threadIdx.x;
    const int cl = blockIdx.x >> 1, c = blockIdx.x & 1;
    const int pair = cl >= 64 ? cl : cl < 4 ? cl * 16 + 15 : cl < 36 ? ((cl - 4) >> 3) * 16 + ((cl - 4) & 7)
                                                                    : ((cl - 36) / 7) * 16 + 8 + (cl - 36) % 7;
    const bool starter = tid == 256 && pair < NMAIN / 2;
    const CUtensorMap* m_wu = c ? &m_wuv : &m_wuk;
    if (tid == 256) {
        mbar_init(sb + BAR_FULL, 1);
        if (starter) {
            asm volatile("fence.mbarrier_init.release.cluster;" ::: "memory");
            mbar_expect_tx(sb + BAR_FULL, 3 * PAGE);
            tma_3d(sb, m_wu, 0, 0, kv_head(pair) * 2, sb + BAR_FULL);
            tma_3d(sb + PAGE, &m_ckv, 0, kv_tokens(pair) * 256, 0, sb + BAR_FULL);
            tma_3d(sb + 2 * PAGE, &m_ckv, 0, kv_tokens(pair) * 256 + 128, 0, sb + BAR_FULL);
        }
#pragma unroll
        for (int i = 1; i < NBAR; i++) mbar_init(sb + SM_BAR + i * 8, (i >> 3) == 1 ? 16 : i >= 25 ? 8 : 1);
        asm volatile("fence.mbarrier_init.release.cluster;" ::: "memory");
    }
    if (starter) {
#pragma unroll 1
        for (int kb = 1; kb < 4; kb++) mbar_expect_tx(sb + BAR_FULL + kb * 8, 3 * PAGE);
        tma_3d(sb + 3 * PAGE, m_wu, 0, 64, kv_head(pair) * 2, sb + BAR_FULL + 8);
    }
    PROF(18, (tid >> 7) & 1);
    __syncthreads();
    cluster_sync();
    PROF(22, (tid >> 7) & 1);
    PROF(19, (tid >> 7) & 1);
    const int warp = __shfl_sync(~0u, tid >> 5, 0), lane = tid & 31;
    auto dump_prof = [&]() {
    };
    if (pair >= NMAIN / 2) {
        if (warp < 8) ffn_cta(smem, sb, blockIdx.x - NMAIN, __ldcg(&g_sync.done) / NCTA, P.w_r);
        else if (tid == 256) ffn_producer(sb, blockIdx.x - NMAIN, &m_gate, &m_up, &m_down);
        __syncwarp();
        PROF(29, tid >> 7);
        cluster_sync();
        if (tid == 0) atomicAdd(&g_sync.done, 1u);
        if (warp < 8) dump_prof();
    } else if (warp < 8) {
        asm volatile("setmaxnreg.inc.sync.aligned.u32 232;");
        consumer(sb, pair, c, P.out, (const uint8_t*)P.x);
        PROF(29, tid >> 7);
        asm volatile("barrier.cluster.wait.aligned;" ::: "memory");
        dump_prof();
    } else {
        asm volatile("setmaxnreg.dec.sync.aligned.u32 40;");
        if (starter) {
#pragma unroll 1
            for (int kb = 1; kb < 4; kb++) {
                if (kb > 1) tma_3d(sb + kb * (3 * PAGE), m_wu, 0, kb * 64, kv_head(pair) * 2, sb + BAR_FULL + kb * 8);
                tma_3d_mc(sb + kb * (3 * PAGE) + (1 + c) * PAGE, &m_ckv, 0, kv_tokens(pair) * 256 + c * 128, kb, sb + BAR_FULL + kb * 8);
            }
        }
        if (warp == 10) {
            sync_helper(sb, lane, pair, c);
        } else if (warp & 1) {
            fetch_helper((warp & 2) ? P.w_uv : P.w_uk, (const uint8_t*)P.x, sb, (warp >> 1) & 1, lane, pair, c);
        } else {
            producer(P, sb, pair, c, &m_ckv, m_wu, &m_wq, &m_wo);
        }
        bar_sync(6, 128);
        if (tid == 256) atomicAdd(&g_sync.done, 1u);
        cluster_sync();
    }
}

typedef CUresult (*EncodeFn)(CUtensorMap*, CUtensorMapDataType, cuuint32_t, void*, const cuuint64_t*, const cuuint64_t*,
                             const cuuint32_t*, const cuuint32_t*, CUtensorMapInterleave, CUtensorMapSwizzle,
                             CUtensorMapL2promotion, CUtensorMapFloatOOBfill);

void make_map_w(EncodeFn fn, CUtensorMap* m, const void* ptr, int rows, int cols, int blocks, int box_rows = 32) {
    cuuint64_t dims[3] = {64, (cuuint64_t)rows, (cuuint64_t)cols / 64};
    cuuint64_t strides[2] = {(cuuint64_t)cols * 2, 128};
    cuuint32_t box[3] = {64, (cuuint32_t)box_rows, (cuuint32_t)blocks};
    cuuint32_t es[3] = {1, 1, 1};
    fn(m, CU_TENSOR_MAP_DATA_TYPE_BFLOAT16, 3, const_cast<void*>(ptr), dims, strides, box, es, CU_TENSOR_MAP_INTERLEAVE_NONE,
       CU_TENSOR_MAP_SWIZZLE_128B, CU_TENSOR_MAP_L2_PROMOTION_L2_256B, CU_TENSOR_MAP_FLOAT_OOB_FILL_NONE);
}

}

extern "C" void kernel_launch(void* const* d_in, const int* in_sizes, int n_in, void* d_out, int out_size) {
    static EncodeFn fn = nullptr;
    if (!fn) {
        void* f = nullptr;
        cudaDriverEntryPointQueryResult qr;
        cudaGetDriverEntryPoint("cuTensorMapEncodeTiled", &f, cudaEnableDefault, &qr);
        fn = (EncodeFn)f;
        cudaFuncSetAttribute(fused_kernel, cudaFuncAttributeMaxDynamicSharedMemorySize, SMEM_BYTES);
    }
    CUtensorMap m_ckv, m_wuk, m_wuv, m_wq, m_wo, m_gate, m_up, m_down;
    make_map_w(fn, &m_gate, d_in[8], DM, FF, FS / 64, 16);
    make_map_w(fn, &m_up, d_in[9], DM, FF, FS / 64, 16);
    make_map_w(fn, &m_down, d_in[10], FF, DM, DM / 64, 16);
    make_map_w(fn, &m_ckv, d_in[1], SEQ, DC, 1, 128);
    make_map_w(fn, &m_wq, d_in[2], DM, NH * 128, 1, 64);
    make_map_w(fn, &m_wuk, d_in[3], DC, NH * 128, 2, 64);
    make_map_w(fn, &m_wuv, d_in[4], DC, NH * 128, 2, 64);
    make_map_w(fn, &m_wo, d_in[5], NH * 128, DM, 1, 64);
    Params P;
    P.x = (const __nv_bfloat16*)d_in[0];
    P.w_r = (const __nv_bfloat16*)d_in[7];
    P.c_kv = (const uint8_t*)d_in[1];
    P.w_uk = (const uint8_t*)d_in[3];
    P.w_uv = (const uint8_t*)d_in[4];
    P.out = (uint8_t*)d_out;
    fused_kernel<<<NCTA, 384, SMEM_BYTES>>>(m_ckv, m_wuk, m_wuv, m_wq, m_wo, m_gate, m_up, m_down, P);
}
```

```cpp
#include <cuda_runtime.h>
#include <cuda_bf16.h>
#include <cuda.h>
#include <stdint.h>
#include <type_traits>

namespace {

constexpr int SEQ = 2048, DM = 1024, NH = 32, DC = 512, FF = 3584;
constexpr int PAGE = 16384;
constexpr int NRING = 12;
constexpr int NCTA = 132, NMAIN = 128;
constexpr uint32_t SM_REGION = NRING * PAGE;
constexpr uint32_t SM_BAR = (NRING + 2) * PAGE;
constexpr uint32_t BAR_FULL = SM_BAR, BAR_EMPTY = SM_BAR + 64;
constexpr uint32_t BAR_DEP = SM_BAR + 128;
constexpr uint32_t BAR_G = SM_BAR + 184;
constexpr uint32_t BAR_DONE = SM_BAR + 200;
constexpr uint32_t BAR_EMPTYL = SM_BAR + 216;
constexpr int NBAR = 35;
constexpr uint32_t SM_PROF = SM_BAR + 320;
constexpr int SMEM_BYTES = SM_PROF + 512;
constexpr uint32_t SPIN_LIMIT = 1u << 16;
constexpr uint32_t POLL_MASK = 7;
constexpr int EARLY = 2;
constexpr int WN = 5;
constexpr int PEEL = 5, STAG = 3;

struct SyncBlock {
    unsigned done;       unsigned pad0[31];
    unsigned ln;         unsigned pad1[31];
    unsigned router;     unsigned pad4[31];
    unsigned ffn_ticket; unsigned pad2[31];
    unsigned ffn_done;   unsigned pad3[31];
    unsigned kv[NH * 8];
    unsigned kvfree[16 * 8];
    unsigned ctx[32 * NH];
};

__device__ __align__(1024) uint8_t g_xn[8 * 16 * 4 * 8192];
__device__ __align__(4096) uint8_t g_kv[16 * 16 * 65536];
__device__ __align__(4096) uint8_t g_ctx[16 * 64 * 16384];
__device__ __align__(16) uint4 g_routed[2 * 128];
__device__ int g_sel[2];
__device__ __align__(16) float g_r[SEQ];
__device__ __align__(16) float g_ypart[4 * 2 * DM];
__device__ SyncBlock g_sync;

__device__ __forceinline__ uint32_t smem_u32(const void* p) { return (uint32_t)__cvta_generic_to_shared(p); }

__device__ __forceinline__ void mbar_init(uint32_t bar, uint32_t count) {
    asm volatile("mbarrier.init.shared::cta.b64 [%0], %1;" ::"r"(bar), "r"(count) : "memory");
}
#define MBAR_WAIT_ASM(HINT, LIMIT)                                                                  \
    asm volatile("{\n.reg .pred p;\n.reg .u32 n;\nmov.u32 n, 0;\n"                                  \
                 "WAIT_LOOP:\n"                                                                     \
                 "mbarrier.try_wait.parity.shared::cta.b64 p, [%0], %1" HINT ";\n"                  \
                 "@p bra WAIT_DONE;\n"                                                              \
                 "add.u32 n, n, 1;\n"                                                               \
                 "setp.lt.u32 p, n, " LIMIT ";\n"                                                   \
                 "@p bra WAIT_LOOP;\n"                                                              \
                 "WAIT_DONE:\n}\n" ::"r"(bar), "r"(parity) : "memory")
__device__ __forceinline__ void mbar_wait(uint32_t bar, uint32_t parity) { MBAR_WAIT_ASM("", "131072"); }
__device__ __forceinline__ void mbar_sleep(uint32_t bar, uint32_t parity) { MBAR_WAIT_ASM(", 2000", "8192"); }
__device__ __forceinline__ bool mbar_try(uint32_t bar, uint32_t parity) {
    uint32_t ok;
    asm volatile("{\n.reg .pred p;\nmbarrier.try_wait.parity.shared::cta.b64 p, [%1], %2;\nselp.u32 %0, 1, 0, p;\n}\n"
                 : "=r"(ok) : "r"(bar), "r"(parity) : "memory");
    return ok;
}
__device__ __forceinline__ bool mbar_test(uint32_t bar, uint32_t parity) {
    uint32_t ok;
    asm volatile("{\n.reg .pred p;\nmbarrier.test_wait.parity.shared::cta.b64 p, [%1], %2;\nselp.u32 %0, 1, 0, p;\n}\n"
                 : "=r"(ok) : "r"(bar), "r"(parity) : "memory");
    return ok;
}
__device__ __forceinline__ bool elect_one() {
    uint32_t ok;
    asm volatile("{\n.reg .pred p;\nelect.sync _|p, 0xffffffff;\nselp.u32 %0, 1, 0, p;\n}\n" : "=r"(ok));
    return ok;
}
__device__ __forceinline__ void mbar_arrive(uint32_t bar) {
    asm volatile("mbarrier.arrive.shared::cta.b64 _, [%0];" ::"r"(bar) : "memory");
}
__device__ __forceinline__ void mbar_expect_tx(uint32_t bar, uint32_t bytes) {
    asm volatile("mbarrier.arrive.expect_tx.shared::cta.b64 _, [%0], %1;" ::"r"(bar), "r"(bytes) : "memory");
}
__device__ __forceinline__ void mbar_arrive_cluster(uint32_t cluster_addr) {
    asm volatile("mbarrier.arrive.shared::cluster.b64 _, [%0];" ::"r"(cluster_addr) : "memory");
}
__device__ __forceinline__ uint32_t mapa(uint32_t addr, uint32_t rank) {
    uint32_t r;
    asm("mapa.shared::cluster.u32 %0, %1, %2;" : "=r"(r) : "r"(addr), "r"(rank));
    return r;
}
__device__ __forceinline__ void tma_3d(uint32_t dst, const CUtensorMap* m, int c0, int c1, int c2, uint32_t bar) {
    asm volatile("cp.async.bulk.tensor.3d.shared::cluster.global.mbarrier::complete_tx::bytes [%0], [%1, {%3, %4, %5}], [%2];"
                 ::"r"(dst), "l"(m), "r"(bar), "r"(c0), "r"(c1), "r"(c2) : "memory");
}
__device__ __forceinline__ void tma_3d_hint(uint32_t dst, const CUtensorMap* m, int c0, int c1, int c2, uint32_t bar, uint64_t pol) {
    asm volatile("cp.async.bulk.tensor.3d.shared::cluster.global.mbarrier::complete_tx::bytes.L2::cache_hint [%0], [%1, {%3, %4, %5}], [%2], %6;"
                 ::"r"(dst), "l"(m), "r"(bar), "r"(c0), "r"(c1), "r"(c2), "l"(pol) : "memory");
}
__device__ __forceinline__ void tma_3d_mc(uint32_t dst, const CUtensorMap* m, int c0, int c1, int c2, uint32_t bar) {
    asm volatile("cp.async.bulk.tensor.3d.shared::cluster.global.mbarrier::complete_tx::bytes.multicast::cluster [%0], [%1, {%3, %4, %5}], [%2], %6;"
                 ::"r"(dst), "l"(m), "r"(bar), "r"(c0), "r"(c1), "r"(c2), "h"((uint16_t)3) : "memory");
}
__device__ __forceinline__ void bulk_load(uint32_t dst, const void* src, uint32_t bytes, uint32_t bar) {
    asm volatile("cp.async.bulk.shared::cluster.global.mbarrier::complete_tx::bytes [%0], [%1], %2, [%3];"
                 ::"r"(dst), "l"(src), "r"(bytes), "r"(bar) : "memory");
}
__device__ __forceinline__ void cp_async16(uint32_t dst, const void* src) {
    asm volatile("cp.async.cg.shared.global [%0], [%1], 16;" ::"r"(dst), "l"(src) : "memory");
}
__device__ __forceinline__ void bulk_load_mc(uint32_t dst, const void* src, uint32_t bytes, uint32_t bar) {
    asm volatile("cp.async.bulk.shared::cluster.global.mbarrier::complete_tx::bytes.multicast::cluster [%0], [%1], %2, [%3], %4;"
                 ::"r"(dst), "l"(src), "r"(bytes), "r"(bar), "h"((uint16_t)3) : "memory");
}
__device__ __forceinline__ void fence_async_smem() { asm volatile("fence.proxy.async.shared::cta;" ::: "memory"); }
__device__ __forceinline__ void prefetch_map(const CUtensorMap* m) {
    asm volatile("prefetch.tensormap [%0];" ::"l"(m) : "memory");
}
__device__ __forceinline__ void red_release(unsigned* p) {
    asm volatile("red.release.gpu.global.add.u32 [%0], 1;" ::"l"(p) : "memory");
}
__device__ __forceinline__ unsigned ld_relaxed(const unsigned* p) {
    unsigned v;
    asm volatile("ld.relaxed.gpu.global.u32 %0, [%1];" : "=r"(v) : "l"(p) : "memory");
    return v;
}
__device__ __forceinline__ void wait_counter(const unsigned* p, unsigned target) {
    for (uint32_t n = 0; (int)(ld_relaxed(p) - target) < 0 && n < SPIN_LIMIT; n++) __nanosleep(100);
    asm volatile("fence.acquire.gpu;" ::: "memory");
    asm volatile("fence.proxy.async.global;" ::: "memory");
}
__device__ __forceinline__ void bar_sync(int id, int n) { asm volatile("bar.sync %0, %1;" ::"r"(id), "r"(n) : "memory"); }
__device__ __forceinline__ void bar_arrive(int id, int n) { asm volatile("bar.arrive %0, %1;" ::"r"(id), "r"(n) : "memory"); }
__device__ __forceinline__ void cluster_sync() {
    asm volatile("barrier.cluster.arrive.relaxed.aligned;\nbarrier.cluster.wait.aligned;" ::: "memory");
}
__device__ __forceinline__ void wg_fence() { asm volatile("wgmma.fence.sync.aligned;" ::: "memory"); }
__device__ __forceinline__ void wg_commit() { asm volatile("wgmma.commit_group.sync.aligned;" ::: "memory"); }
template <int N> __device__ __forceinline__ void wg_wait() { asm volatile("wgmma.wait_group.sync.aligned %0;" ::"n"(N) : "memory"); }
template <int N> __device__ __forceinline__ void reg_fence(float (&a)[N]) {
#pragma unroll
    for (int i = 0; i < N; i++) asm volatile("" : "+f"(a[i])::"memory");
}
template <int N> __device__ __forceinline__ void reg_fence(uint32_t (&a)[N]) {
#pragma unroll
    for (int i = 0; i < N; i++) asm volatile("" : "+r"(a[i])::"memory");
}
__device__ __forceinline__ uint32_t pack_bf16(float lo, float hi) {
    uint32_t r;
    asm("cvt.rn.bf16x2.f32 %0, %1, %2;" : "=r"(r) : "f"(hi), "f"(lo));
    return r;
}
__device__ __forceinline__ float bf_lo(uint32_t v) { return __uint_as_float(v << 16); }
__device__ __forceinline__ float bf_hi(uint32_t v) { return __uint_as_float(v & 0xffff0000u); }
__device__ __forceinline__ float bf_round(float v) { return __bfloat162float(__float2bfloat16_rn(v)); }
__device__ __forceinline__ float ex2(float v) {
    float r;
    asm("ex2.approx.ftz.f32 %0, %1;" : "=f"(r) : "f"(v));
    return r;
}
__device__ __forceinline__ float sqrt_approx(float v) {
    float r;
    asm("sqrt.approx.ftz.f32 %0, %1;" : "=f"(r) : "f"(v));
    return r;
}
__device__ __forceinline__ float rcp_approx(float v) {
    float r;
    asm("rcp.approx.ftz.f32 %0, %1;" : "=f"(r) : "f"(v));
    return r;
}
__device__ __forceinline__ float silu_f(float v) { return v * rcp_approx(1.0f + ex2(v * -1.4426950408889634f)); }
__device__ __forceinline__ void stmatrix_x4(uint32_t addr, uint32_t r0, uint32_t r1, uint32_t r2, uint32_t r3) {
    asm volatile("stmatrix.sync.aligned.m8n8.x4.shared.b16 [%0], {%1, %2, %3, %4};"
                 ::"r"(addr), "r"(r0), "r"(r1), "r"(r2), "r"(r3) : "memory");
}
__device__ __forceinline__ void sts128(uint32_t addr, uint32_t r0, uint32_t r1, uint32_t r2, uint32_t r3) {
    asm volatile("st.shared.v4.b32 [%0], {%1, %2, %3, %4};" ::"r"(addr), "r"(r0), "r"(r1), "r"(r2), "r"(r3) : "memory");
}
__device__ __forceinline__ void lds128(uint32_t addr, uint32_t& r0, uint32_t& r1, uint32_t& r2, uint32_t& r3) {
    asm volatile("ld.shared.v4.b32 {%0, %1, %2, %3}, [%4];" : "=r"(r0), "=r"(r1), "=r"(r2), "=r"(r3) : "r"(addr) : "memory");
}
__device__ __forceinline__ uint32_t bf2_mul(uint32_t a, uint32_t b) {
    uint32_t r;
    asm("mul.rn.bf16x2 %0, %1, %2;" : "=r"(r) : "r"(a), "r"(b));
    return r;
}
__device__ __forceinline__ uint32_t bf2_add(uint32_t a, uint32_t b) {
    uint32_t r;
    asm("add.rn.bf16x2 %0, %1, %2;" : "=r"(r) : "r"(a), "r"(b));
    return r;
}
constexpr uint64_t POL_FIRST = 0x12F0000000000000ull, POL_NORMAL = 0x1000000000000000ull;
__device__ __forceinline__ uint4 ldg_hint(const void* p, uint64_t pol) {
    uint4 v;
    asm volatile("ld.global.cg.L2::cache_hint.v4.u32 {%0, %1, %2, %3}, [%4], %5;" : "=r"(v.x), "=r"(v.y), "=r"(v.z), "=r"(v.w) : "l"(p), "l"(pol));
    return v;
}
__device__ __forceinline__ void stg_hint(void* p, uint32_t r0, uint32_t r1, uint32_t r2, uint32_t r3, uint64_t pol) {
    asm volatile("st.global.cg.L2::cache_hint.v4.u32 [%0], {%1, %2, %3, %4}, %5;" ::"l"(p), "r"(r0), "r"(r1), "r"(r2), "r"(r3), "l"(pol) : "memory");
}

__device__ __forceinline__ uint64_t make_desc(uint32_t addr, uint32_t lbo_bytes) {
    return (uint64_t)((addr & 0x3FFFF) >> 4) | ((uint64_t)(lbo_bytes >> 4) << 16) | ((uint64_t)(1024 >> 4) << 32) | (1ull << 62);
}

__device__ __forceinline__ void wgmma_n256_ss(float (&d)[128], uint64_t da, uint64_t db, int acc) {
    asm volatile(
        "{\n.reg .pred p;\nsetp.ne.b32 p, %130, 0;\n"
        "wgmma.mma_async.sync.aligned.m64n256k16.f32.bf16.bf16 {"
        "%0, %1, %2, %3, %4, %5, %6, %7, %8, %9, %10, %11, %12, %13, %14, %15, "
        "%16, %17, %18, %19, %20, %21, %22, %23, %24, %25, %26, %27, %28, %29, %30, %31, "
        "%32, %33, %34, %35, %36, %37, %38, %39, %40, %41, %42, %43, %44, %45, %46, %47, "
        "%48, %49, %50, %51, %52, %53, %54, %55, %56, %57, %58, %59, %60, %61, %62, %63, "
        "%64, %65, %66, %67, %68, %69, %70, %71, %72, %73, %74, %75, %76, %77, %78, %79, "
        "%80, %81, %82, %83, %84, %85, %86, %87, %88, %89, %90, %91, %92, %93, %94, %95, "
        "%96, %97, %98, %99, %100, %101, %102, %103, %104, %105, %106, %107, %108, %109, %110, %111, "
        "%112, %113, %114, %115, %116, %117, %118, %119, %120, %121, %122, %123, %124, %125, %126, %127"
        "}, %128, %129, p, 1, 1, 1, 0;\n}\n"
        :
        "+f"(d[0]), "+f"(d[1]), "+f"(d[2]), "+f"(d[3]), "+f"(d[4]), "+f"(d[5]), "+f"(d[6]), "+f"(d[7]),
        "+f"(d[8]), "+f"(d[9]), "+f"(d[10]), "+f"(d[11]), "+f"(d[12]), "+f"(d[13]), "+f"(d[14]), "+f"(d[15]),
        "+f"(d[16]), "+f"(d[17]), "+f"(d[18]), "+f"(d[19]), "+f"(d[20]), "+f"(d[21]), "+f"(d[22]), "+f"(d[23]),
        "+f"(d[24]), "+f"(d[25]), "+f"(d[26]), "+f"(d[27]), "+f"(d[28]), "+f"(d[29]), "+f"(d[30]), "+f"(d[31]),
        "+f"(d[32]), "+f"(d[33]), "+f"(d[34]), "+f"(d[35]), "+f"(d[36]), "+f"(d[37]), "+f"(d[38]), "+f"(d[39]),
        "+f"(d[40]), "+f"(d[41]), "+f"(d[42]), "+f"(d[43]), "+f"(d[44]), "+f"(d[45]), "+f"(d[46]), "+f"(d[47]),
        "+f"(d[48]), "+f"(d[49]), "+f"(d[50]), "+f"(d[51]), "+f"(d[52]), "+f"(d[53]), "+f"(d[54]), "+f"(d[55]),
        "+f"(d[56]), "+f"(d[57]), "+f"(d[58]), "+f"(d[59]), "+f"(d[60]), "+f"(d[61]), "+f"(d[62]), "+f"(d[63]),
        "+f"(d[64]), "+f"(d[65]), "+f"(d[66]), "+f"(d[67]), "+f"(d[68]), "+f"(d[69]), "+f"(d[70]), "+f"(d[71]),
        "+f"(d[72]), "+f"(d[73]), "+f"(d[74]), "+f"(d[75]), "+f"(d[76]), "+f"(d[77]), "+f"(d[78]), "+f"(d[79]),
        "+f"(d[80]), "+f"(d[81]), "+f"(d[82]), "+f"(d[83]), "+f"(d[84]), "+f"(d[85]), "+f"(d[86]), "+f"(d[87]),
        "+f"(d[88]), "+f"(d[89]), "+f"(d[90]), "+f"(d[91]), "+f"(d[92]), "+f"(d[93]), "+f"(d[94]), "+f"(d[95]),
        "+f"(d[96]), "+f"(d[97]), "+f"(d[98]), "+f"(d[99]), "+f"(d[100]), "+f"(d[101]), "+f"(d[102]), "+f"(d[103]),
        "+f"(d[104]), "+f"(d[105]), "+f"(d[106]), "+f"(d[107]), "+f"(d[108]), "+f"(d[109]), "+f"(d[110]), "+f"(d[111]),
        "+f"(d[112]), "+f"(d[113]), "+f"(d[114]), "+f"(d[115]), "+f"(d[116]), "+f"(d[117]), "+f"(d[118]), "+f"(d[119]),
        "+f"(d[120]), "+f"(d[121]), "+f"(d[122]), "+f"(d[123]), "+f"(d[124]), "+f"(d[125]), "+f"(d[126]), "+f"(d[127])
        : "l"(da), "l"(db), "r"(acc));
}

__device__ __forceinline__ void wgmma_n64_rs_tb(float* d, uint32_t a0, uint32_t a1, uint32_t a2, uint32_t a3, uint32_t db, int acc) {
    asm volatile(
        "{\n.reg .pred p;\n.reg .b64 db;\nsetp.ne.b32 p, %37, 0;\nmov.b64 db, {%36, 0x40000040};\n"
        "wgmma.mma_async.sync.aligned.m64n64k16.f32.bf16.bf16 {"
        "%0, %1, %2, %3, %4, %5, %6, %7, %8, %9, %10, %11, %12, %13, %14, %15, "
        "%16, %17, %18, %19, %20, %21, %22, %23, %24, %25, %26, %27, %28, %29, %30, %31"
        "}, {%32, %33, %34, %35}, db, p, 1, 1, 1;\n}\n"
        :
        "+f"(d[0]), "+f"(d[1]), "+f"(d[2]), "+f"(d[3]), "+f"(d[4]), "+f"(d[5]), "+f"(d[6]), "+f"(d[7]),
        "+f"(d[8]), "+f"(d[9]), "+f"(d[10]), "+f"(d[11]), "+f"(d[12]), "+f"(d[13]), "+f"(d[14]), "+f"(d[15]),
        "+f"(d[16]), "+f"(d[17]), "+f"(d[18]), "+f"(d[19]), "+f"(d[20]), "+f"(d[21]), "+f"(d[22]), "+f"(d[23]),
        "+f"(d[24]), "+f"(d[25]), "+f"(d[26]), "+f"(d[27]), "+f"(d[28]), "+f"(d[29]), "+f"(d[30]), "+f"(d[31])
        : "r"(a0), "r"(a1), "r"(a2), "r"(a3), "r"(db), "r"(acc));
}

template <int TB>
__device__ __forceinline__ void wgmma_n128_rs(float (&d)[64], uint32_t a0, uint32_t a1, uint32_t a2, uint32_t a3, uint32_t db, int acc) {
    asm volatile(
        "{\n.reg .pred p;\n.reg .b64 db;\nsetp.ne.b32 p, %69, 0;\nmov.b64 db, {%68, 0x40000040};\n"
        "wgmma.mma_async.sync.aligned.m64n128k16.f32.bf16.bf16 {"
        "%0, %1, %2, %3, %4, %5, %6, %7, %8, %9, %10, %11, %12, %13, %14, %15, "
        "%16, %17, %18, %19, %20, %21, %22, %23, %24, %25, %26, %27, %28, %29, %30, %31, "
        "%32, %33, %34, %35, %36, %37, %38, %39, %40, %41, %42, %43, %44, %45, %46, %47, "
        "%48, %49, %50, %51, %52, %53, %54, %55, %56, %57, %58, %59, %60, %61, %62, %63"
        "}, {%64, %65, %66, %67}, db, p, 1, 1, %70;\n}\n"
        :
        "+f"(d[0]), "+f"(d[1]), "+f"(d[2]), "+f"(d[3]), "+f"(d[4]), "+f"(d[5]), "+f"(d[6]), "+f"(d[7]),
        "+f"(d[8]), "+f"(d[9]), "+f"(d[10]), "+f"(d[11]), "+f"(d[12]), "+f"(d[13]), "+f"(d[14]), "+f"(d[15]),
        "+f"(d[16]), "+f"(d[17]), "+f"(d[18]), "+f"(d[19]), "+f"(d[20]), "+f"(d[21]), "+f"(d[22]), "+f"(d[23]),
        "+f"(d[24]), "+f"(d[25]), "+f"(d[26]), "+f"(d[27]), "+f"(d[28]), "+f"(d[29]), "+f"(d[30]), "+f"(d[31]),
        "+f"(d[32]), "+f"(d[33]), "+f"(d[34]), "+f"(d[35]), "+f"(d[36]), "+f"(d[37]), "+f"(d[38]), "+f"(d[39]),
        "+f"(d[40]), "+f"(d[41]), "+f"(d[42]), "+f"(d[43]), "+f"(d[44]), "+f"(d[45]), "+f"(d[46]), "+f"(d[47]),
        "+f"(d[48]), "+f"(d[49]), "+f"(d[50]), "+f"(d[51]), "+f"(d[52]), "+f"(d[53]), "+f"(d[54]), "+f"(d[55]),
        "+f"(d[56]), "+f"(d[57]), "+f"(d[58]), "+f"(d[59]), "+f"(d[60]), "+f"(d[61]), "+f"(d[62]), "+f"(d[63])
        : "r"(a0), "r"(a1), "r"(a2), "r"(a3), "r"(db), "r"(acc), "n"(TB));
}

__device__ __forceinline__ void wgmma_n128_ss(float* d, uint64_t da, uint64_t db, int acc) {
    asm volatile(
        "{\n.reg .pred p;\nsetp.ne.b32 p, %66, 0;\n"
        "wgmma.mma_async.sync.aligned.m64n128k16.f32.bf16.bf16 {"
        "%0, %1, %2, %3, %4, %5, %6, %7, %8, %9, %10, %11, %12, %13, %14, %15, "
        "%16, %17, %18, %19, %20, %21, %22, %23, %24, %25, %26, %27, %28, %29, %30, %31, "
        "%32, %33, %34, %35, %36, %37, %38, %39, %40, %41, %42, %43, %44, %45, %46, %47, "
        "%48, %49, %50, %51, %52, %53, %54, %55, %56, %57, %58, %59, %60, %61, %62, %63"
        "}, %64, %65, p, 1, 1, 0, 1;\n}\n"
        :
        "+f"(d[0]), "+f"(d[1]), "+f"(d[2]), "+f"(d[3]), "+f"(d[4]), "+f"(d[5]), "+f"(d[6]), "+f"(d[7]),
        "+f"(d[8]), "+f"(d[9]), "+f"(d[10]), "+f"(d[11]), "+f"(d[12]), "+f"(d[13]), "+f"(d[14]), "+f"(d[15]),
        "+f"(d[16]), "+f"(d[17]), "+f"(d[18]), "+f"(d[19]), "+f"(d[20]), "+f"(d[21]), "+f"(d[22]), "+f"(d[23]),
        "+f"(d[24]), "+f"(d[25]), "+f"(d[26]), "+f"(d[27]), "+f"(d[28]), "+f"(d[29]), "+f"(d[30]), "+f"(d[31]),
        "+f"(d[32]), "+f"(d[33]), "+f"(d[34]), "+f"(d[35]), "+f"(d[36]), "+f"(d[37]), "+f"(d[38]), "+f"(d[39]),
        "+f"(d[40]), "+f"(d[41]), "+f"(d[42]), "+f"(d[43]), "+f"(d[44]), "+f"(d[45]), "+f"(d[46]), "+f"(d[47]),
        "+f"(d[48]), "+f"(d[49]), "+f"(d[50]), "+f"(d[51]), "+f"(d[52]), "+f"(d[53]), "+f"(d[54]), "+f"(d[55]),
        "+f"(d[56]), "+f"(d[57]), "+f"(d[58]), "+f"(d[59]), "+f"(d[60]), "+f"(d[61]), "+f"(d[62]), "+f"(d[63])
        : "l"(da), "l"(db), "r"(acc));
}

__device__ __forceinline__ void wgmma_n8_ta(float* d, uint64_t da, uint64_t db) {
    asm volatile("wgmma.mma_async.sync.aligned.m64n8k16.f32.bf16.bf16 {%0, %1, %2, %3}, %4, %5, 1, 1, 1, 1, 0;\n"
                 : "+f"(d[0]), "+f"(d[1]), "+f"(d[2]), "+f"(d[3]) : "l"(da), "l"(db));
}

#define PROF(slot, role)
#undef PROF_GT
#define PROF_GT(slot)

struct Params {
    const __nv_bfloat16* x;
    const __nv_bfloat16* w_r;
    const uint8_t *c_kv, *w_uk, *w_uv;
    uint8_t* out;
};
__device__ __forceinline__ void lsu_prefetch(const void* p) { asm volatile("prefetch.global.L2 [%0];" ::"l"(p) : "memory"); }

template <typename T>
__device__ __forceinline__ T* ptr_off(T* base, uint32_t off) {
    uint32_t lo, hi;
    asm("mov.b64 {%0, %1}, %2;" : "=r"(lo), "=r"(hi) : "l"(base));
    asm("add.cc.u32 %0, %0, %2;\naddc.u32 %1, %1, 0;" : "+r"(lo), "+r"(hi) : "r"(off));
    T* r;
    asm("mov.b64 %0, {%1, %2};" : "=l"(r) : "r"(lo), "r"(hi));
    return r;
}
__device__ __forceinline__ int kv_head(int pair) { return pair & 7; }
__device__ __forceinline__ int kv_tokens(int pair) { return ((pair >> 3) & 1) * 4 + (pair >> 4); }
__device__ __forceinline__ int out_rows(int pair) { return pair & 7; }
__device__ __forceinline__ int out_cols(int pair) { return (pair >> 4) * 4 + ((pair >> 3) & 1) * 2; }
__device__ __forceinline__ int attn_rowblock(int pair, int seg) {
    int j = pair & 3, hl = pair >> 2;
    return (((hl & 1) | (j == 0)) ^ seg) ? j : 7 - j;
}
__device__ __forceinline__ int outproj_head(int i, int ib) {
    if (i < 16) return i;
    return 16 + 2 * (i & 7) + ((ib < 4) ^ ((i >> 3) & 1));
}

__device__ __forceinline__ void pin_value(uint32_t& v) { asm volatile("" : "+r"(v)); }
__device__ __forceinline__ void pin_value(int& v) { asm volatile("" : "+r"(v)); }
__device__ __forceinline__ void pin_value(const uint8_t*& v) { asm volatile("" : "+l"(v)); }

__device__ __forceinline__ void producer(const Params& P, uint32_t sb, int pair, int c,
                                         const CUtensorMap* m_ckv, const CUtensorMap* m_wu,
                                         const CUtensorMap* m_wq, const CUtensorMap* m_wo) {
    const int hl = pair >> 2;
    const int ibA = attn_rowblock(pair, 0), nA = 2 * ibA + 2;
    const int ib = out_rows(pair), mi = 2 * ib + c, nb = out_cols(pair);
    const bool leader = elect_one();
    uint32_t g = 4, tail = 0;
    if (leader) prefetch_map(m_wq);
    auto wait_released = [&](uint32_t need) {
#pragma unroll 1
        for (; tail <= need; tail++) mbar_wait(sb + BAR_EMPTY + (tail & 7) * 8, (tail >> 3) & 1);
    };
    auto wait_released_here = [&](uint32_t need) {
#pragma unroll 1
        for (; tail < need; tail++) mbar_wait(sb + BAR_EMPTY + (tail & 7) * 8, (tail >> 3) & 1);
        if (tail == need) mbar_wait(sb + BAR_EMPTYL + (need & 7) * 8, (need >> 3) & 1);
    };
    auto wait_released_peer = [&](uint32_t need) {
        if (tail == need) {
            uint32_t eb = sb + BAR_EMPTY + (need & 7) * 8, ep = (need >> 3) & 1;
            tail++;
            mbar_wait(eb, ep);
        }
    };
    auto full_bar = [&]() { return sb + BAR_FULL + (g & 7) * 8; };
    auto pin = [](auto&... v) { (pin_value(v), ...); };
#pragma unroll 1
    for (int rnd = 0; rnd < 2; rnd++) {
#pragma unroll 1
        for (int i = rnd ? 0 : 4; i < 16; i++) {
            int kb = i & 7, h2 = (kv_head(pair) + (i & 8) + rnd * 16) * 2, krow = kb * 64;
            uint32_t pg = sb + (i & 3) * (3 * PAGE), pb = pg + (1 + c) * PAGE, bar = full_bar();
            pin(kb, h2, krow, pg, pb, bar);
            const uint32_t need = g - 4 - (i < 2);
            wait_released_here(need);
            if (leader) {
                mbar_expect_tx(bar, 3 * PAGE);
                tma_3d(pg, m_wu, 0, krow, h2, bar);
            }
            wait_released_peer(need);
            if (leader) {
                tma_3d_mc(pb, m_ckv, 0, kv_tokens(pair) * 256 + c * 128, kb, bar);
                if (rnd == 1 && i == 3) asm volatile("red.relaxed.gpu.global.add.u32 [%0], 1;" ::"l"(ptr_off(g_sync.kvfree, hl * 32)) : "memory");
            }
            g++;
        }
        mbar_sleep(sb + BAR_DEP, 0);
        const uint8_t* xa = ptr_off(g_xn, ibA * (16 * 32768) + c * PAGE);
        const uint8_t* xb = ptr_off(g_xn, (7 - ibA) * (16 * 32768) + (1 - c) * PAGE);
#pragma unroll 1
        for (int kb = 0; kb < DM / 64; kb++) {
            uint32_t pg = sb + (kb & 3) * (3 * PAGE), pw = pg + 2 * PAGE + c * 8192, bar = full_bar(), p2 = pg + PAGE;
            int krow = kb * 64;
            pin(pg, pw, p2, bar, krow);
            wait_released_here(g - 4);
            if (leader) {
                mbar_expect_tx(bar, 3 * PAGE);
                bulk_load(pg, xa, PAGE, bar);
            }
            wait_released_peer(g - 4);
            if (leader) {
                tma_3d_mc(pw, m_wq, 0, krow, (rnd * 16 + hl) * 2 + c, bar);
                bulk_load(p2, xb, PAGE, bar);
            }
            g++;
            xa += 32768;
            xb += 32768;
        }
        mbar_sleep(sb + BAR_DEP + 8 + rnd * 16, 0);
        if (rnd == 1 && leader) prefetch_map(m_wo);
        uint32_t pg = sb + c * PAGE;
#pragma unroll 1
        for (int j = 0; j < 36; j++) {
            const bool isk = j == 0 || ((j & 1) && j != 35);
            const int t = isk ? (j + 1) >> 1 : (j - 1) >> 1;
            const uint8_t* src = ptr_off(g_kv, (hl * 16 + (t >= nA ? t - nA : t)) * 65536 + (isk ? 0 : 32768) + c * PAGE);
            uint32_t bar = full_bar(), need = g - 6 + (j < 2) + (j < 5);
            pin(src, bar, need);
            wait_released(need);
            if (leader) {
                mbar_expect_tx(bar, 2 * PAGE);
                bulk_load_mc(pg, src, PAGE, bar);
            }
            g++;
            if (rnd == 0 && j >= 22 && j < 34) {
                const int cta = pair * 2 + c, i = j - 22;
                const uint32_t l = (threadIdx.x & 31) * 128;
                if (i < 8) lsu_prefetch(ptr_off(i & 1 ? P.w_uv : P.w_uk, cta * 32768 + (i >> 1) * 8192 + 4096 + l));
                else lsu_prefetch(ptr_off(P.c_kv, cta * 16384 + (i - 8) * 4096 + l));
            }
            pg = pg >= sb + SM_REGION - 2 * PAGE ? pg - (SM_REGION - 2 * PAGE) : pg + 2 * PAGE;
        }
    }
    uint32_t pg = sb;
#pragma unroll 1
    for (int i = 0; i < 64; i++) {
        if ((i & 15) == 0 && i != 16) mbar_sleep(sb + BAR_DEP + 32 + (i >> 1) - (i ? 8 : 0), 0);
        const int kb = outproj_head(i >> 1, ib) * 2 + (i & 1);
        const uint8_t* src = ptr_off(g_ctx, (mi * 64 + kb) * PAGE);
        uint32_t bar = full_bar(), pw = pg + PAGE + c * 8192;
        int krow = kb * 64;
        pin(src, bar, pw, krow);
        wait_released_here(g - 6);
        if (leader) {
            mbar_expect_tx(bar, 2 * PAGE);
            bulk_load(pg, src, PAGE, bar);
        }
        wait_released_peer(g - 6);
        if (leader) tma_3d_mc(pw, m_wo, 0, krow, nb + c, bar);
        g++;
        pg = pg == sb + SM_REGION - 2 * PAGE ? sb : pg + 2 * PAGE;
    }
}

__device__ __forceinline__ uint32_t xn_block(int row64, int kb) {
    return (((row64 >> 2) * 16 + kb) * 4 + ((row64 & 1) * 2 + (((row64 >> 1) & 1) ^ 1))) * 8192;
}
__device__ __forceinline__ uint32_t image_offset(int row, int ch) {
    return xn_block(row >> 6, ch >> 3) + (row & 63) * 128 + (((ch & 7) ^ (row & 7)) << 4);
}
__device__ __forceinline__ uint32_t bf2_sub(uint32_t a, uint32_t b) {
    uint32_t r;
    asm("sub.rn.bf16x2 %0, %1, %2;" : "=r"(r) : "r"(a), "r"(b));
    return r;
}
__device__ __forceinline__ uint32_t bf2_fma(uint32_t a, uint32_t b, uint32_t c) {
    uint32_t r;
    asm("fma.rn.bf16x2 %0, %1, %2, %3;" : "=r"(r) : "r"(a), "r"(b), "r"(c));
    return r;
}
template <int N0, int N>
__device__ __forceinline__ void ln_sums(const uint32_t (&u)[N], float& sum, float& sq) {
    float s0 = 0.f, s1 = 0.f, q0 = 0.f, q1 = 0.f;
#pragma unroll
    for (int k = N0; k < N0 + 16; k++) {
        const float a = bf_lo(u[k]), b = bf_hi(u[k]);
        s0 += a; s1 += b;
        q0 = fmaf(a, a, q0); q1 = fmaf(b, b, q1);
    }
    sum = s0 + s1;
    sq = q0 + q1;
}
__device__ __forceinline__ void ln_finish(float sum, float sq, uint32_t& mean2, uint32_t& rhi2, uint32_t& rlo2) {
    const float ms = sum * (1.0f / DM);
    const float var = fmaxf(fmaf(-ms, ms, sq * (1.0f / DM)), 0.f);
    const float rden = rcp_approx(bf_round(sqrt_approx(bf_round(bf_round(var) + 1e-5f))));
    const float rhi = bf_round(rden);
    mean2 = pack_bf16(ms, ms);
    rhi2 = pack_bf16(rhi, rhi);
    rlo2 = pack_bf16(rden - rhi, rden - rhi);
}
template <int N0, int N>
__device__ __forceinline__ void ln_apply(uint32_t (&u)[N], uint32_t mean2, uint32_t rhi2, uint32_t rlo2, uint8_t* dst) {
#pragma unroll
    for (int i = 0; i < 4; i++) {
        uint32_t o[4];
#pragma unroll
        for (int k = 0; k < 4; k++) {
            const uint32_t d = bf2_sub(u[N0 + 4 * i + k], mean2);
            o[k] = bf2_fma(d, rhi2, bf2_mul(d, rlo2));
        }
#pragma unroll
        for (int k = 0; k < 4; k++) u[N0 + 4 * i + k] = o[k];
        __stcg(reinterpret_cast<uint4*>(dst + i * 131072), make_uint4(o[0], o[1], o[2], o[3]));
    }
}
__device__ __forceinline__ int query_rowblock(int pair, int c, int w, int seg) {
    const int qA = (w ? 0 : 2) + c;
    return 4 * attn_rowblock(pair, seg) + (seg ? 3 - qA : qA);
}

__device__ __noinline__ void fetch_helper(const uint8_t* w_u, const uint8_t* x, uint32_t sb, int w, int lane, int pair, int c) {
    const uint32_t page = sb + SM_REGION + w * PAGE + lane * 16;
    mbar_sleep(sb + BAR_FULL + 5 * 8, 0);
#pragma unroll 1
    for (int i = 0; i < 2; i++) {
        lsu_prefetch(ptr_off(w_u, ((pair * 2 + c) * 4 + i * 2 + (lane >> 4)) * 8192 + 2048 + (lane & 15) * 128));
        __nanosleep(300);
    }
    const unsigned e1 = __ldcg(&g_sync.done) / NCTA + 1;
#pragma unroll 1
    for (int e = 1; e <= 7; e += 2) mbar_sleep(sb + BAR_DONE + 8, (e >> 1) & 1);
    const int rb = out_rows(pair) * 4 + c * 2 + w, kb0 = out_cols(pair);
    const uint8_t* src = ptr_off(g_xn, xn_block(rb, kb0) + lane * 16);
#pragma unroll 1
    for (int i = 0; i < 32; i += 4) {
#pragma unroll
        for (int k = 0; k < 4; k++) cp_async16(page + (i + k) * 512, src + (i + k) * 512 + (i >> 4) * (32768 - 8192));
        __nanosleep(200);
    }
#pragma unroll 1
    for (int i = 0; i < 4; i++) lsu_prefetch(ptr_off(x, (rb * 64 + i * 16 + (lane >> 1)) * (DM * 2) + kb0 * 128 + (lane & 1) * 128));
    wait_counter(&g_sync.ffn_done, e1);
    const int r = __ldcg(ptr_off(g_sel, (lane >> 4) * 4)) - rb * 64, ch = lane & 15;
    const uint4 t = __ldcg(ptr_off(g_routed, ((lane >> 4) * 128 + kb0 * 8 + ch) * 16));
    asm volatile("cp.async.wait_all;" ::: "memory");
    __syncwarp();
    if (r >= 0 && r < 64)
        sts128(sb + SM_REGION + w * PAGE + (ch >> 3) * 8192 + r * 128 + (((ch & 7) ^ (r & 7)) << 4), t.x, t.y, t.z, t.w);
    __syncwarp();
    if (lane == 0) mbar_arrive(sb + BAR_G + w * 8);
    PROF(20, 2);
}

__device__ __noinline__ void sync_helper(uint32_t sb, int lane, int pair, int c) {
    const unsigned e1 = __ldcg(&g_sync.done) / NCTA + 1;
    const int ib = out_rows(pair);
    int e = 0, b = 0;
#pragma unroll 1
    for (uint32_t n = 0; (e < 9 || b < 7) && n < SPIN_LIMIT; n++) {
        if (e < 9 && __all_sync(~0u, mbar_test(sb + BAR_DONE + (e & 1) * 8, (e >> 1) & 1))) {
            const int rnd = e > 4, ev = (e - 1) & 3;
            unsigned* flag = e == 0 ? &g_sync.ln
                           : ev < 2 ? ptr_off(g_sync.kv, (rnd * 16 + kv_head(pair) + 8 * ev) * 32)
                                    : ptr_off(g_sync.ctx, (query_rowblock(pair, c, lane & 1, ev & 1) * NH + rnd * 16 + (pair >> 2)) * 4);
            asm volatile("fence.proxy.async.global;\nfence.release.gpu;" ::: "memory");
            if (lane < ((e == 0 || ev < 2) ? 1 : 2)) asm volatile("red.relaxed.gpu.global.add.u32 [%0], 1;" ::"l"(flag) : "memory");
            PROF(10 + e, 2);
            e++;
        }
        if (b < 7 && e > 0 && (b < 4 || (n & POLL_MASK) == 0)) {
            const int i = b == 4 ? lane >> 1 : 8 * b - 24 + ((lane >> 1) & 7);
            const unsigned* cnt = b == 0 ? &g_sync.ln
                                : b == 2 ? ptr_off(g_sync.kvfree, (kv_head(pair) + 8 * (lane & 1)) * 32)
                                : b < 4 ? ptr_off(g_sync.kv, ((b >> 1) * 16 + (pair >> 2)) * 32)
                                        : ptr_off(g_sync.ctx, ((4 * ib + 2 * c + (lane & 1)) * NH + outproj_head(i & 31, ib)) * 4);
            if (__all_sync(~0u, (int)(ld_relaxed(cnt) - e1 * (b == 0 ? NMAIN : b == 2 ? 8 : b < 4 ? 16 : 1)) >= 0)) {
                asm volatile("fence.acquire.gpu;\nfence.proxy.async.global;" ::: "memory");
                __syncwarp();
                if (lane == 0) mbar_arrive(sb + BAR_DEP + b * 8);
                PROF(1 + b, 2);
                b++;
            }
        }
        __nanosleep(150);
    }
}

__device__ __forceinline__ unsigned long long block_max_key(unsigned long long k, unsigned long long* red, int tid) {
#pragma unroll
    for (int o = 16; o; o >>= 1) {
        unsigned long long t = __shfl_xor_sync(~0u, k, o);
        k = t > k ? t : k;
    }
    bar_sync(1, 256);
    if ((tid & 31) == 0) red[tid >> 5] = k;
    bar_sync(1, 256);
    k = red[0];
#pragma unroll
    for (int i = 1; i < 8; i++) k = red[i] > k ? red[i] : k;
    return k;
}

constexpr int FS = FF / 4;
constexpr int FSTAGE = 32768, FNST = 6;
constexpr int FN1 = 2 * (DM / 16), FN2 = FS / 16;

__device__ __forceinline__ void ffn_producer(uint32_t sb, int s, const CUtensorMap* m_gate, const CUtensorMap* m_up,
                                             const CUtensorMap* m_down) {
    wait_counter(&g_sync.ln, (__ldcg(&g_sync.done) / NCTA + 1) * NMAIN);
    int slot = 0, ph = 1;
#pragma unroll 1
    for (int st = 0; st < FN1 + FN2; st++) {
        mbar_sleep(sb + BAR_EMPTY + slot * 8, ph);
        const uint32_t bar = sb + BAR_FULL + slot * 8;
        const bool up = st < FN1;
        mbar_expect_tx(bar, up ? FS * 32 : DM * 32);
        tma_3d_hint(sb + slot * FSTAGE, up ? ((st & 1) ? m_up : m_gate) : m_down, 0,
                    up ? (st >> 1) * 16 : s * FS + (st - FN1) * 16, up ? s * (FS / 64) : 0, bar, POL_FIRST);
        if (++slot == FNST) { slot = 0; ph ^= 1; }
    }
}

__device__ __forceinline__ void ffn_cta(uint8_t* smem, uint32_t sb, int s, unsigned epoch, const __nv_bfloat16* w_r) {
    const int tid = threadIdx.x, lane = tid & 31;
    const int warp = __shfl_sync(~0u, tid >> 5, 0), w = warp >> 2;
    constexpr uint32_t XB = FNST * FSTAGE, HB = XB + 16384, AUX = HB + 14336;
    unsigned long long* red = reinterpret_cast<unsigned long long*>(smem + AUX);
    unsigned* flag = reinterpret_cast<unsigned*>(smem + AUX + 128);
    const unsigned e1 = epoch + 1;
    for (int i = tid; i < (16384 + 14336) / 16; i += 256) reinterpret_cast<uint4*>(smem + XB)[i] = make_uint4(0, 0, 0, 0);
    {
        float wf[32];
#pragma unroll
        for (int i = 0; i < 4; i++) {
            const uint4 t = __ldg(reinterpret_cast<const uint4*>(w_r) + lane + 32 * i);
            const uint32_t tu[4] = {t.x, t.y, t.z, t.w};
#pragma unroll
            for (int k = 0; k < 4; k++) { wf[8 * i + 2 * k] = bf_lo(tu[k]); wf[8 * i + 2 * k + 1] = bf_hi(tu[k]); }
        }
        if (tid == 0) wait_counter(&g_sync.ln, e1 * NMAIN);
        bar_sync(1, 256);
#pragma unroll 1
        for (int r0 = s * (SEQ / 4) + warp * (SEQ / 32); r0 < s * (SEQ / 4) + (warp + 1) * (SEQ / 32); r0 += 4) {
            uint4 t[4][4];
#pragma unroll
            for (int r = 0; r < 4; r++)
#pragma unroll
                for (int i = 0; i < 4; i++) t[r][i] = __ldcg(reinterpret_cast<const uint4*>(g_xn + image_offset(r0 + r, lane) + i * 131072));
            float acc[4];
#pragma unroll
            for (int r = 0; r < 4; r++) {
                float a = 0.f, b = 0.f;
#pragma unroll
                for (int i = 0; i < 4; i++) {
                    const uint32_t tu[4] = {t[r][i].x, t[r][i].y, t[r][i].z, t[r][i].w};
#pragma unroll
                    for (int k = 0; k < 4; k++) {
                        a = fmaf(bf_lo(tu[k]), wf[8 * i + 2 * k], a);
                        b = fmaf(bf_hi(tu[k]), wf[8 * i + 2 * k + 1], b);
                    }
                }
                acc[r] = a + b;
            }
#pragma unroll
            for (int o = 16; o; o >>= 1)
#pragma unroll
                for (int r = 0; r < 4; r++) acc[r] += __shfl_xor_sync(~0u, acc[r], o);
            if (lane < 4) __stcg(&g_r[r0 + lane], bf_round(lane == 0 ? acc[0] : lane == 1 ? acc[1] : lane == 2 ? acc[2] : acc[3]));
        }
        __threadfence();
        bar_sync(1, 256);
        if (tid == 0) {
            red_release(&g_sync.router);
            wait_counter(&g_sync.router, e1 * 4);
        }
        bar_sync(1, 256);
    }
    unsigned long long keys[8];
    unsigned long long best = 0;
#pragma unroll
    for (int i = 0; i < 8; i++) {
        int idx = tid + 256 * i;
        uint32_t b = __float_as_uint(__ldcg(&g_r[idx]) + 0.0f);
        b = (b & 0x80000000u) ? ~b : (b | 0x80000000u);
        keys[i] = ((unsigned long long)b << 32) | (unsigned)(SEQ - 1 - idx);
        best = keys[i] > best ? keys[i] : best;
    }
    const unsigned long long k0 = block_max_key(best, red, tid);
    best = 0;
#pragma unroll
    for (int i = 0; i < 8; i++) best = (keys[i] != k0 && keys[i] > best) ? keys[i] : best;
    const unsigned long long k1 = block_max_key(best, red, tid);
    const int row = SEQ - 1 - (int)((w ? k1 : k0) & 0xffffffffu);
    const int ch = tid & 127;
    const uint4 xrow = __ldcg(reinterpret_cast<const uint4*>(g_xn + image_offset(row, ch)));
    *reinterpret_cast<uint4*>(smem + XB + (ch >> 3) * 1024 + w * 128 + (((ch & 7) ^ w) << 4)) = xrow;
    fence_async_smem();
    bar_sync(1, 256);
    PROF(20, tid >> 7);
    int slot = 0, ph = 0, prev = 0;
    auto next_stage = [&](bool has_prev) {
        wg_commit();
        wg_wait<1>();
        if (has_prev && lane < 2) mbar_arrive(sb + BAR_EMPTY + prev * 8);
        prev = slot;
        if (++slot == FNST) { slot = 0; ph ^= 1; }
    };
    {
        float ag[28], au[28];
#pragma unroll
        for (int i = 0; i < 28; i++) ag[i] = au[i] = 0.f;
#pragma unroll 1
        for (int ks = 0; ks < DM / 16; ks++) {
            const uint64_t db = make_desc(sb + XB + (ks >> 2) * 1024 + (ks & 3) * 32, 16);
            mbar_wait(sb + BAR_FULL + slot * 8, ph);
            uint64_t da = make_desc(sb + slot * FSTAGE + w * (7 * 2048), 16);
            wg_fence();
#pragma unroll
            for (int b = 0; b < 7; b++) wgmma_n8_ta(ag + 4 * b, da + b * 128, db);
            next_stage(ks > 0);
            mbar_wait(sb + BAR_FULL + slot * 8, ph);
            da = make_desc(sb + slot * FSTAGE + w * (7 * 2048), 16);
            wg_fence();
#pragma unroll
            for (int b = 0; b < 7; b++) wgmma_n8_ta(au + 4 * b, da + b * 128, db);
            next_stage(true);
        }
        wg_wait<0>();
        reg_fence(ag);
        reg_fence(au);
        if ((lane & 3) == 0) {
#pragma unroll
            for (int i = 0; i < 28; i++) {
                const int f = (warp & 3) * 16 + (lane >> 2) + (i & 2) * 4, tok = i & 1;
                const float h = bf_round(silu_f(bf_round(ag[i]))) * bf_round(au[i]);
                *reinterpret_cast<__nv_bfloat16*>(smem + HB + (w * 7 + (i >> 2)) * 1024 + tok * 128 + (((f >> 3) ^ tok) << 4) + (f & 7) * 2) =
                    __float2bfloat16_rn(h);
            }
        }
    }
    fence_async_smem();
    bar_sync(1, 256);
    PROF(21, tid >> 7);
    {
        float ay[32];
#pragma unroll
        for (int i = 0; i < 32; i++) ay[i] = 0.f;
#pragma unroll 1
        for (int ks = 0; ks < FN2; ks++) {
            const uint64_t db = make_desc(sb + HB + (ks >> 2) * 1024 + (ks & 3) * 32, 16);
            mbar_wait(sb + BAR_FULL + slot * 8, ph);
            const uint64_t da = make_desc(sb + slot * FSTAGE + w * (8 * 2048), 16);
            wg_fence();
#pragma unroll
            for (int b = 0; b < 8; b++) wgmma_n8_ta(ay + 4 * b, da + b * 128, db);
            next_stage(true);
        }
        wg_wait<0>();
        reg_fence(ay);
        if ((lane & 3) == 0) {
#pragma unroll
            for (int i = 0; i < 32; i++)
                g_ypart[(s * 2 + (i & 1)) * DM + (w * 8 + (i >> 2)) * 64 + (warp & 3) * 16 + (lane >> 2) + (i & 2) * 4] = ay[i];
        }
    }
    PROF(23, tid >> 7);
    __threadfence();
    bar_sync(1, 256);
    if (tid == 0) {
        *flag = atomicAdd(&g_sync.ffn_ticket, 1u) == epoch * 4 + 3;
        __threadfence();
    }
    bar_sync(1, 256);
    if (*flag) {
        const float sg = bf_round(__fdividef(1.0f, 1.0f + __expf(-__ldcg(&g_r[row]))));
        const uint32_t xu[4] = {xrow.x, xrow.y, xrow.z, xrow.w};
        uint32_t o[4];
#pragma unroll
        for (int k = 0; k < 4; k++) {
            float y0 = 0.f, y1 = 0.f;
#pragma unroll
            for (int q = 0; q < 4; q++) {
                const float2 y = __ldcg(reinterpret_cast<const float2*>(&g_ypart[(q * 2 + w) * DM + ch * 8 + 2 * k]));
                y0 += y.x; y1 += y.y;
            }
            o[k] = pack_bf16(bf_lo(xu[k]) + bf_round(bf_round(y0) * sg), bf_hi(xu[k]) + bf_round(bf_round(y1) * sg));
        }
        g_routed[w * 128 + ch] = make_uint4(o[0], o[1], o[2], o[3]);
        if (ch == 0) g_sel[w] = row;
        bar_sync(1, 256);
        if (tid == 0) red_release(&g_sync.ffn_done);
    }
}

__device__ __forceinline__ uint32_t slab_addr(uint32_t stg, int lane, int s) {
    const int row = ((lane >> 3) & 1) * 8 + (lane & 7);
    const int chunk = 2 * (s & 3) + (lane >> 4);
    return stg + row * 128 + (s >> 2) * 8192 + ((chunk ^ (lane & 7)) << 4);
}

constexpr float SM_SCALE = 0.08838834764831845f * 1.4426950408889634f;
constexpr float SUM_HI = 1048576.f, SUM_LO = 1.0f / 1048576.f;

template <int I0, int I1, int J0>
__device__ __forceinline__ void mask_range(float (&S)[64], float limf) {
#pragma unroll
    for (int i = I0; i < I1; i++) {
        const int j = i >> 2;
        float t;
        asm("add.sat.f32 %0, %1, %2;" : "=f"(t) : "f"((float)(32 * (j >> 2) + 2 * (j & 3) + (i & 1) - (i & 2) * 4)), "f"(-limf));
        S[4 * J0 + i] = fmaf(t, -1e30f, S[4 * J0 + i]);
    }
}
template <int J0>
__device__ __forceinline__ void mask_half(float (&S)[64], float limf, int v) {
    asm volatile("" : "+f"(limf));
    if (v < 2) {
        mask_range<0, 16, J0>(S, limf);
#pragma unroll
        for (int i = 16; i < 32; i++) S[4 * J0 + i] = -1e30f;
    } else {
        mask_range<16, 32, J0>(S, limf);
    }
}
__device__ __forceinline__ void issue_qk(float (&S)[64], const uint32_t (&Q)[32], uint32_t d0) {
#pragma unroll
    for (int s = 0; s < 8; s++)
        wgmma_n128_rs<1>(S, Q[4 * s], Q[4 * s + 1], Q[4 * s + 2], Q[4 * s + 3], d0 + s * 128, s > 0);
}
__device__ __forceinline__ void issue_qk_half(float (&T)[32], const uint32_t (&Q)[32], uint32_t d0) {
#pragma unroll
    for (int s = 0; s < 8; s++) wgmma_n64_rs_tb(T, Q[4 * s], Q[4 * s + 1], Q[4 * s + 2], Q[4 * s + 3], d0 + s * 128, s > 0);
}
template <int H>
__device__ __forceinline__ void issue_pv(float (&O)[64], const uint32_t (&Pm)[32], uint32_t d0, int acc) {
#pragma unroll
    for (int s = 4 * H; s < 4 * H + 4; s++)
        wgmma_n128_rs<0>(O, Pm[4 * s], Pm[4 * s + 1], Pm[4 * s + 2], Pm[4 * s + 3], d0 + H * (PAGE >> 4) + (s & 3) * 2, s > 0 ? 1 : acc);
}
template <int J0, int J1>
__device__ __forceinline__ void exp_groups(const float (&S)[64], uint32_t (&Pm)[32], float (&sum)[2]) {
#pragma unroll
    for (int i = 2 * J0; i < 2 * J1; i++) asm volatile("" : "+r"(Pm[i])::"memory");
#pragma unroll
    for (int j = J0; j < J1; j++) {
        const float e0 = ex2(S[4 * j]), e1 = ex2(S[4 * j + 1]), e2 = ex2(S[4 * j + 2]), e3 = ex2(S[4 * j + 3]);
        sum[0] = (j ? sum[0] + e0 : e0) + e1;
        sum[1] = (j ? sum[1] + e2 : e2) + e3;
        Pm[2 * j] = pack_bf16(e0, e1);
        Pm[2 * j + 1] = pack_bf16(e2, e3);
    }
}
__device__ __forceinline__ void shift_rows(float (&S)[64], float d0, float d1) {
#pragma unroll
    for (int j = 0; j < 16; j++) {
        S[4 * j] -= d0; S[4 * j + 1] -= d0; S[4 * j + 2] -= d1; S[4 * j + 3] -= d1;
    }
}
__device__ constexpr int chunk_src(int i) { return 4 * (4 * (i >> 3) + (i & 3)) + 2 * ((i >> 2) & 1); }
enum : uint32_t { CTL_FIRST = 1, CTL_SWITCH = 2, CTL_LAST = 4, CTL_HALF = 128, CTL_MASKHI = 256, CTL_WOUT = 512, CTL_PVHALF = 1024, CTL_PVACC = 16384,
                  CTL_SHIFT = 32768 };
__device__ __forceinline__ float quad_sum(float v) {
    v += __shfl_xor_sync(~0u, v, 1);
    return v + __shfl_xor_sync(~0u, v, 2);
}

__device__ __forceinline__ void store_part(uint8_t* base, uint32_t row_bits, int p, const uint32_t (&pk)[64], uint64_t pol) {
    asm volatile("{\n.reg .b64 d0, d1;\nxor.b64 d0, %0, %1;\nxor.b64 d1, d0, 64;\n"
                 "TS: .branchtargets P0, P1, P2, P3, P4, P5, P6, P7;\n"
                 "brx.idx.uni %2, TS;\n"
                 "P0:\n st.global.cg.L2::cache_hint.v4.u32 [d0 + 0], {%3, %4, %5, %6}, %67;\n st.global.cg.L2::cache_hint.v4.u32 [d1 + 0], {%11, %12, %13, %14}, %67;\n bra.uni DONE;\n"
                 "P1:\n st.global.cg.L2::cache_hint.v4.u32 [d0 + 0], {%7, %8, %9, %10}, %67;\n st.global.cg.L2::cache_hint.v4.u32 [d1 + 0], {%15, %16, %17, %18}, %67;\n bra.uni DONE;\n"
                 "P2:\n st.global.cg.L2::cache_hint.v4.u32 [d0 + 16384], {%19, %20, %21, %22}, %67;\n st.global.cg.L2::cache_hint.v4.u32 [d1 + 16384], {%27, %28, %29, %30}, %67;\n bra.uni DONE;\n"
                 "P3:\n st.global.cg.L2::cache_hint.v4.u32 [d0 + 16384], {%23, %24, %25, %26}, %67;\n st.global.cg.L2::cache_hint.v4.u32 [d1 + 16384], {%31, %32, %33, %34}, %67;\n bra.uni DONE;\n"
                 "P4:\n st.global.cg.L2::cache_hint.v4.u32 [d0 + 65536], {%35, %36, %37, %38}, %67;\n st.global.cg.L2::cache_hint.v4.u32 [d1 + 65536], {%43, %44, %45, %46}, %67;\n bra.uni DONE;\n"
                 "P5:\n st.global.cg.L2::cache_hint.v4.u32 [d0 + 65536], {%39, %40, %41, %42}, %67;\n st.global.cg.L2::cache_hint.v4.u32 [d1 + 65536], {%47, %48, %49, %50}, %67;\n bra.uni DONE;\n"
                 "P6:\n st.global.cg.L2::cache_hint.v4.u32 [d0 + 81920], {%51, %52, %53, %54}, %67;\n st.global.cg.L2::cache_hint.v4.u32 [d1 + 81920], {%59, %60, %61, %62}, %67;\n bra.uni DONE;\n"
                 "P7:\n st.global.cg.L2::cache_hint.v4.u32 [d0 + 81920], {%55, %56, %57, %58}, %67;\n st.global.cg.L2::cache_hint.v4.u32 [d1 + 81920], {%63, %64, %65, %66}, %67;\n bra.uni DONE;\n"
                 "DONE:\n}\n"
                 ::"l"(base), "l"((uint64_t)((p & 1) ? row_bits : 0)), "r"(p), "r"(pk[0]), "r"(pk[1]), "r"(pk[2]), "r"(pk[3]), "r"(pk[4]), "r"(pk[5]), "r"(pk[6]), "r"(pk[7]), "r"(pk[8]), "r"(pk[9]), "r"(pk[10]), "r"(pk[11]), "r"(pk[12]), "r"(pk[13]), "r"(pk[14]), "r"(pk[15]), "r"(pk[16]), "r"(pk[17]), "r"(pk[18]), "r"(pk[19]), "r"(pk[20]), "r"(pk[21]), "r"(pk[22]), "r"(pk[23]), "r"(pk[24]), "r"(pk[25]), "r"(pk[26]), "r"(pk[27]), "r"(pk[28]), "r"(pk[29]), "r"(pk[30]), "r"(pk[31]), "r"(pk[32]), "r"(pk[33]), "r"(pk[34]), "r"(pk[35]), "r"(pk[36]), "r"(pk[37]), "r"(pk[38]), "r"(pk[39]), "r"(pk[40]), "r"(pk[41]), "r"(pk[42]), "r"(pk[43]), "r"(pk[44]), "r"(pk[45]), "r"(pk[46]), "r"(pk[47]), "r"(pk[48]), "r"(pk[49]), "r"(pk[50]), "r"(pk[51]), "r"(pk[52]), "r"(pk[53]), "r"(pk[54]), "r"(pk[55]), "r"(pk[56]), "r"(pk[57]), "r"(pk[58]), "r"(pk[59]), "r"(pk[60]), "r"(pk[61]), "r"(pk[62]), "r"(pk[63]), "l"(pol)
                 : "memory");
}

__device__ __forceinline__ void store_part4(uint8_t* d0, int p, const uint32_t (&pk)[64]) {
    asm volatile("{\n.reg .b64 d1;\nxor.b64 d1, %0, 64;\n"
                 "TS: .branchtargets P0, P1, P2, P3;\n"
                 "brx.idx.uni %1, TS;\n"
                 "P0:\n st.global.cg.v4.u32 [%0 + 0], {%2, %3, %4, %5};\n st.global.cg.v4.u32 [d1 + 0], {%10, %11, %12, %13};\n bra.uni DONE;\n"
                 "P1:\n st.global.cg.v4.u32 [%0 + 1024], {%6, %7, %8, %9};\n st.global.cg.v4.u32 [d1 + 1024], {%14, %15, %16, %17};\n bra.uni DONE;\n"
                 "P2:\n st.global.cg.v4.u32 [%0 + 16384], {%18, %19, %20, %21};\n st.global.cg.v4.u32 [d1 + 16384], {%26, %27, %28, %29};\n bra.uni DONE;\n"
                 "P3:\n st.global.cg.v4.u32 [%0 + 17408], {%22, %23, %24, %25};\n st.global.cg.v4.u32 [d1 + 17408], {%30, %31, %32, %33};\n bra.uni DONE;\n"
                 "DONE:\n}\n"
                 ::"l"(d0), "r"(p), "r"(pk[0]), "r"(pk[1]), "r"(pk[2]), "r"(pk[3]), "r"(pk[4]), "r"(pk[5]), "r"(pk[6]), "r"(pk[7]), "r"(pk[8]), "r"(pk[9]), "r"(pk[10]), "r"(pk[11]), "r"(pk[12]), "r"(pk[13]), "r"(pk[14]), "r"(pk[15]), "r"(pk[16]), "r"(pk[17]), "r"(pk[18]), "r"(pk[19]), "r"(pk[20]), "r"(pk[21]), "r"(pk[22]), "r"(pk[23]), "r"(pk[24]), "r"(pk[25]), "r"(pk[26]), "r"(pk[27]), "r"(pk[28]), "r"(pk[29]), "r"(pk[30]), "r"(pk[31])
                 : "memory");
}

__device__ __forceinline__ void consumer(uint32_t sb, int pair, int c, uint8_t* out, const uint8_t* x) {
    const int tid = threadIdx.x;
    const int warp = __shfl_sync(~0u, tid >> 5, 0);
    const int w = warp >> 2, v = warp & 3;
    const int lane = __shfl_sync(~0u, tid & 31, tid & 31);

    const uint32_t empty_rel = lane == 2 ? mapa(sb + BAR_EMPTYL, c) : mapa(sb + BAR_EMPTY, lane & 1);
    auto release = [&](uint32_t grp) {
        if (lane < 3) mbar_arrive_cluster(empty_rel + (grp & 7) * 8);
    };
    auto wait_full = [&](uint32_t grp) { mbar_wait(sb + BAR_FULL + (grp & 7) * 8, (grp >> 3) & 1); };

    uint32_t g = 0;
    const uint32_t stg = sb + SM_REGION + w * PAGE + v * 2048;
    const uint32_t chunk0 = (lane >> 2) * 128 + (((lane & 3) ^ (lane >> 2)) << 4);
    uint32_t ndone = 0;
    auto mark_done = [&]() {
        __syncwarp();
        if (lane == 0) mbar_arrive(sb + BAR_DONE + (ndone & 1) * 8);
        ndone++;
    };
    auto ctx_dst = [&](int rnd, int seg) {
        const int rb = query_rowblock(pair, c, w, seg);
        return ptr_off(g_ctx, ((rb >> 1) * 64 + (rnd * 16 + (pair >> 2)) * 2) * PAGE + (rb & 1) * 8192 + v * 2048);
    };

    uint32_t ctl_tab;
    {
        const int t = lane, firstB = 2 * attn_rowblock(pair, 0) + 2 - w;
        auto is_half = [&](int u) { return (u == firstB - 1 || u == 16) && c == (u >= firstB); };
        auto block = [&](int u) { return u + (w == 1 && u >= firstB); };
        auto place = [](int j) { return ((j & 15) << 3) | ((j - (j * 43 >> 8) * 6) << 11); };
        const int jv = min(2 * block(t - 1) + 2, 35), jk = t == 17 ? jv : max(2 * block(t) - 1, 0);
        const bool diag = t == firstB - 1 || t == 16;
        ctl_tab = ((t == 0 || t == firstB) ? CTL_FIRST : 0) | (t == firstB ? CTL_SWITCH : 0) | (t == 17 ? CTL_LAST : 0) |
                  (diag ? (is_half(t) ? CTL_HALF : CTL_MASKHI) : 0) | (t == firstB + 1 ? CTL_WOUT : 0) |
                  (is_half(t - 1) ? CTL_PVHALF : 0) | ((t == 1 || t == firstB + 1) ? 0 : CTL_PVACC) |
                  place(jk) | ((place(jv) | (t ? 3 : 0)) << 16);
    }

    uint32_t pk[64];
#pragma unroll
    for (int i = 0; i < 64; i++) pk[i] = 0;
    uint8_t* pend = nullptr;
    uint32_t prow = 0x400;
    auto write_part = [&](int p, uint64_t pol = POL_NORMAL) { store_part(pend, prow, p, pk, pol); };
    if (w == 1) bar_arrive(2, 256);

    for (int item = 0; item < 6; item++) {
        if ((0x1B >> item) & 1) {
            constexpr int nk = DC / 64;
            float acc[128];
            auto issue_kblock = [&](int first_acc) {
                wait_full(g);
                const uint32_t pg = sb + (g & 3) * (3 * PAGE);
                const uint64_t da = make_desc(pg + w * 8192, 16), db = make_desc(pg + PAGE, 16);
                wg_fence();
                wgmma_n256_ss(acc, da, db, first_acc);
                wgmma_n256_ss(acc, da + 128, db + 2, 1);
                wgmma_n256_ss(acc, da + 256, db + 4, 1);
                wgmma_n256_ss(acc, da + 384, db + 6, 1);
                wg_commit();
                g++;
            };
            if (item == 0) PROF(17, w);
            issue_kblock(0);
            if (item == 0) PROF(1, w);
            if (item == 0 && w == 0) PROF_GT(1);
            const int nparts = item == 0 ? 0 : (item == 3 ? 4 : 8);
            const int ln_row = (pair * 2 + c) * 16 + warp * 2;
            if (item == 0) {
                const uint8_t* src = ptr_off(x, ln_row * (DM * 2) + lane * 16);
#pragma unroll
                for (int i = 0; i < 8; i++) {
                    const uint4 t = __ldcg(reinterpret_cast<const uint4*>(src + i * 512));
                    pk[4 * i] = t.x; pk[4 * i + 1] = t.y; pk[4 * i + 2] = t.z; pk[4 * i + 3] = t.w;
                }
            }
#pragma unroll 1
            for (int kb = 1; kb < nk; kb++) {
                if (kb == nk - 1 && w == 1) bar_sync(4, 256);
                issue_kblock(1);
                if (kb == nk - 1 && w == 0) bar_arrive(4, 256);
                wg_wait<1>();
                release(g - 2);
                if (kb <= nparts) {
                    if (item == 4 && kb == 1) mbar_wait(sb + BAR_DEP + 16, 0);
                    write_part(kb - 1, item == 3 ? POL_FIRST : POL_NORMAL);
                    if (kb == nk - 1) write_part(nk - 1);
                    if (kb == nparts || kb == nk - 1) mark_done();
                }
                if (g <= 8) {
                    float s[2], q[2];
                    if (g == 4) {
                        ln_sums<0>(pk, s[0], q[0]);
                        pk[32] = __float_as_uint(s[0]); pk[33] = __float_as_uint(q[0]);
                    }
                    if (g == 5) {
                        ln_sums<16>(pk, s[1], q[1]);
                        pk[34] = __float_as_uint(s[1]); pk[35] = __float_as_uint(q[1]);
                    }
                    if (g == 6) {
#pragma unroll
                        for (int r = 0; r < 2; r++) { s[r] = __uint_as_float(pk[32 + 2 * r]); q[r] = __uint_as_float(pk[33 + 2 * r]); }
                        const bool hi = lane & 16, od = lane & 8;
                        float a = hi ? s[1] : s[0], b = hi ? q[1] : q[0];
                        a += __shfl_xor_sync(~0u, hi ? s[0] : s[1], 16);
                        b += __shfl_xor_sync(~0u, hi ? q[0] : q[1], 16);
                        float t = od ? b : a;
                        t += __shfl_xor_sync(~0u, od ? a : b, 8);
#pragma unroll
                        for (int o = 4; o; o >>= 1) t += __shfl_xor_sync(~0u, t, o);
#pragma unroll
                        for (int r = 0; r < 2; r++) {
                            s[r] = __shfl_sync(~0u, t, 16 * r);
                            q[r] = __shfl_sync(~0u, t, 16 * r + 8);
                        }
                        ln_finish(s[0], q[0], pk[36], pk[37], pk[38]);
                        ln_finish(s[1], q[1], pk[39], pk[40], pk[41]);
                    }
                    if (g == 7) ln_apply<0>(pk, pk[36], pk[37], pk[38], ptr_off(g_xn, image_offset(ln_row, lane)));
                    if (g == 8) {
                        ln_apply<16>(pk, pk[39], pk[40], pk[41], ptr_off(g_xn, image_offset(ln_row + 1, lane)));
                        mark_done();
                    }
                }
            }
            wg_wait<0>();
            reg_fence(acc);
            release(g - 1);
            PROF(2 + 2 * item, w);
            if (w == 0) PROF_GT(2 + 2 * item);
#pragma unroll
            for (int i = 0; i < 64; i++) pk[i] = pack_bf16(acc[chunk_src(i)], acc[chunk_src(i) + 1]);
            const uint32_t vrow = (v >> 1) * 32 + (lane >> 3) * 8 + (v & 1) * 4 + ((lane >> 2) & 1);
            pend = ptr_off(g_kv, ((kv_head(pair) + (item == 1 || item == 4 ? 8 : 0)) * 16 + kv_tokens(pair) * 2) * 65536 + w * 8192 +
                                     (c ? 32768 + vrow * 128 + (((lane & 3) ^ (vrow & 7)) << 4) : v * 2048 + chunk0));
            prow = c ? 0x120 : 0x400;
            PROF(3 + 2 * item, w);
            continue;
        }

        float O[64], S[64];
        auto issue_q = [&](int first_acc) {
            wait_full(g);
            const uint32_t pg = sb + (g & 3) * (3 * PAGE);
            const uint64_t da = make_desc(pg + w * 8192, 16), db = make_desc(pg + 2 * PAGE, 8192);
            const uint64_t dab = make_desc(pg + PAGE + (1 - w) * 8192, 16);
            wg_fence();
#pragma unroll
            for (int q = 0; q < 4; q++) wgmma_n128_ss(S, da + 2 * q, db + 128 * q, q ? 1 : first_acc);
            wg_commit();
#pragma unroll
            for (int q = 0; q < 4; q++) wgmma_n128_ss(O, dab + 2 * q, db + 128 * q, q ? 1 : first_acc);
            wg_commit();
            g++;
        };
        issue_q(0);
#pragma unroll 1
        for (int kb = 1; kb < DM / 64; kb++) {
            if (kb == DM / 64 - 2 && w == 1) bar_sync(4, 256);
            issue_q(1);
            if (kb == DM / 64 - 1 && w == 0) bar_arrive(4, 256);
            wg_wait<2>();
            release(g - 2);
            if (kb <= 8) {
                write_part(kb - 1);
                if (kb == 8) mark_done();
            }
        }
        uint32_t Q[32], Pm[32];
#pragma unroll
        for (int i = 0; i < 32; i++) Pm[i] = pk[i];
        float lim = (float)(v * 16 + (lane >> 2) - 8 * (lane & 3));
        float mc[2] = {0.f, 0.f}, l[2] = {0.f, 0.f}, scale[2] = {0.f, 0.f}, sum[2];
        uint32_t ctl = __shfl_sync(~0u, ctl_tab, 0), nxt = __shfl_sync(~0u, ctl_tab, 1);
        int t = 1;
        asm volatile("" : "+f"(lim), "+f"(mc[0]), "+f"(mc[1]), "+f"(l[0]), "+f"(l[1]), "+r"(ctl), "+r"(nxt), "+r"(t));
        wg_wait<1>();
        reg_fence(S);
#pragma unroll
        for (int i = 0; i < 32; i++) Q[i] = pack_bf16(S[2 * i] * SM_SCALE, S[2 * i + 1] * SM_SCALE);
        reg_fence(Q);
        wait_full(g);
        wg_wait<0>();
        reg_fence(O);
        release(g - 1);
        PROF(2 + 2 * item, w);
        if (w == 0) PROF_GT(2 + 2 * item);

        const uint32_t qaddr = stg + lane * 16;
        auto put_queries = [&](const float (&A)[64]) {
#pragma unroll
            for (int i = 0; i < 8; i++)
                sts128(qaddr + (i >> 2) * 8192 + (i & 3) * 512, pack_bf16(A[8 * i] * SM_SCALE, A[8 * i + 1] * SM_SCALE), pack_bf16(A[8 * i + 2] * SM_SCALE, A[8 * i + 3] * SM_SCALE),
                       pack_bf16(A[8 * i + 4] * SM_SCALE, A[8 * i + 5] * SM_SCALE), pack_bf16(A[8 * i + 6] * SM_SCALE, A[8 * i + 7] * SM_SCALE));
        };
        auto get_queries = [&]() {
#pragma unroll
            for (int i = 0; i < 8; i++) lds128(qaddr + (i >> 2) * 8192 + (i & 3) * 512, Q[4 * i], Q[4 * i + 1], Q[4 * i + 2], Q[4 * i + 3]);
        };
        const uint32_t kdesc0 = (uint32_t)make_desc(sb, PAGE), vdesc0 = (uint32_t)make_desc(sb, 16);
        auto wait_block = [&](uint32_t word) { mbar_wait(sb + BAR_FULL + (word & 56), (word >> 6) & 1); };
        auto write_out = [&](auto early) {
            uint8_t* dst = ctx_dst(item == 5, 0);
            uint8_t* d[2] = {ptr_off(dst, chunk0), ptr_off(dst, chunk0 ^ 64)};
#pragma unroll
            for (int i = early.value ? 0 : WN; i < (early.value ? WN : 8); i++) {
                const float sc = scale[i & 1];
                uint32_t q[4];
#pragma unroll
                for (int k = 0; k < 4; k++) q[k] = pack_bf16(O[chunk_src(4 * i + k)] * sc, O[chunk_src(4 * i + k) + 1] * sc);
                if (early.value && i > 0) {
#pragma unroll
                    for (int k = 0; k < 4; k++) O[4 * (i - 1) + k] = __uint_as_float(q[k]);
                }
                stg_hint(d[(i >> 1) & 1] + (i >> 2) * PAGE + (i & 1) * 1024, q[0], q[1], q[2], q[3], item == 2 ? POL_FIRST : POL_NORMAL);
            }
            if (!early.value) mark_done();
        };
        put_queries(O);
        bar_sync(2 + w, 256);
        if (!(ctl & CTL_HALF)) {
            wg_fence();
            issue_qk(S, Q, kdesc0);
            wg_commit();
            wg_fence();
            wg_commit();
            wg_commit();
            bar_arrive(3 - w, 256);
            wg_wait<2>();
            reg_fence(S);
        } else {
            float T[32];
            wg_fence();
            issue_qk_half(T, Q, kdesc0);
            wg_commit();
            wg_fence();
            wg_commit();
            wg_commit();
            bar_arrive(3 - w, 256);
            wg_wait<2>();
            reg_fence(T);
#pragma unroll
            for (int i = 0; i < 32; i++) S[i] = T[i];
        }
        for (;;) {
            const bool kready = mbar_try(sb + BAR_FULL + (nxt & 56), (nxt >> 6) & 1);
            if (ctl & (CTL_HALF | CTL_MASKHI | CTL_SHIFT)) {
                if (ctl & CTL_HALF) mask_half<0>(S, lim, v);
                if (ctl & CTL_MASKHI) mask_half<8>(S, lim, v);
                if (ctl & CTL_SHIFT) shift_rows(S, mc[0], mc[1]);
            }
            float early[4 * EARLY];
#pragma unroll
            for (int j = 0; j < EARLY; j++) {
#pragma unroll
                for (int i = 4 * j; i < 4 * j + 4; i++) early[i] = ex2(S[i]);
                sum[0] = (j ? sum[0] + early[4 * j] : early[4 * j]) + early[4 * j + 1];
                sum[1] = (j ? sum[1] + early[4 * j + 2] : early[4 * j + 2]) + early[4 * j + 3];
            }
            const uint32_t tie = __float_as_uint(sum[0]) & __float_as_uint(sum[1]) & (ctl & 0x80000000u);
            if (lane < 3) mbar_arrive_cluster(empty_rel + tie + (ctl & 56));
            wg_wait<1>();
#pragma unroll
            for (int j = 0; j < EARLY; j++) {
                asm volatile("" : "+r"(Pm[2 * j]), "+r"(Pm[2 * j + 1])::"memory");
                Pm[2 * j] = pack_bf16(early[4 * j], early[4 * j + 1]);
                Pm[2 * j + 1] = pack_bf16(early[4 * j + 2], early[4 * j + 3]);
            }
            exp_groups<EARLY, 8>(S, Pm, sum);
            const bool half = ctl & CTL_HALF;
            if (!half) {
                wg_wait<0>();
                reg_fence(O);
                if (lane < ((ctl >> 16) & 3)) mbar_arrive_cluster(empty_rel + ((ctl >> 16) & 56));
                exp_groups<8, 16>(S, Pm, sum);
            } else {
                asm volatile("wgmma.wait_group.sync.aligned 0;\n" ::: "memory");
                reg_fence(O);
                if (lane < ((ctl >> 16) & 3)) asm volatile("mbarrier.arrive.shared::cluster.b64 _, [%0];\n" ::"r"(empty_rel + ((ctl >> 16) & 56)) : "memory");
            }
            const bool over = !(sum[0] + sum[1] <= SUM_HI);
            if (__any_sync(~0u, over || !kready) || (((ctl & CTL_FIRST) | (nxt & (CTL_SWITCH | CTL_LAST | CTL_HALF))) != 0)) {
                bool bad = __any_sync(~0u, over);
                if (!kready) wait_block(nxt);
                const bool first = ctl & CTL_FIRST;
                if (first) {
                    uint32_t b0 = __ballot_sync(~0u, sum[0] >= SUM_LO), b1 = __ballot_sync(~0u, sum[1] >= SUM_LO);
                    b0 |= b0 >> 1; b1 |= b1 >> 1;
                    b0 |= b0 >> 2; b1 |= b1 >> 2;
                    bad |= (b0 & b1 & 0x11111111u) != 0x11111111u;
                }
                if (bad) {
                    float d0 = fmaxf(S[0], S[1]), d1 = fmaxf(S[2], S[3]);
#pragma unroll
                    for (int j = 1; j < 8; j++) {
                        d0 = fmaxf(d0, fmaxf(S[4 * j], S[4 * j + 1]));
                        d1 = fmaxf(d1, fmaxf(S[4 * j + 2], S[4 * j + 3]));
                    }
                    if (!half) {
#pragma unroll
                        for (int j = 8; j < 16; j++) {
                            d0 = fmaxf(d0, fmaxf(S[4 * j], S[4 * j + 1]));
                            d1 = fmaxf(d1, fmaxf(S[4 * j + 2], S[4 * j + 3]));
                        }
                    }
                    d0 = fmaxf(d0, __shfl_xor_sync(~0u, d0, 1));
                    d1 = fmaxf(d1, __shfl_xor_sync(~0u, d1, 1));
                    d0 = fmaxf(d0, __shfl_xor_sync(~0u, d0, 2));
                    d1 = fmaxf(d1, __shfl_xor_sync(~0u, d1, 2));
                    if (!first) {
                        d0 = fmaxf(d0, 0.f);
                        d1 = fmaxf(d1, 0.f);
                        const float a0 = ex2(-d0), a1 = ex2(-d1);
#pragma unroll
                        for (int j = 0; j < 16; j++) {
                            O[4 * j] *= a0; O[4 * j + 1] *= a0; O[4 * j + 2] *= a1; O[4 * j + 3] *= a1;
                        }
                        l[0] *= a0; l[1] *= a1;
                    }
                    mc[0] += d0; mc[1] += d1;
                    ctl_tab |= CTL_SHIFT;
                    nxt |= CTL_SHIFT;
                    shift_rows(S, d0, d1);
                    exp_groups<0, 8>(S, Pm, sum);
                    if (!half) exp_groups<8, 16>(S, Pm, sum);
                }
                if (ctl & CTL_SWITCH) write_out(std::true_type());
                if (nxt & CTL_LAST) break;
                if (nxt & CTL_SWITCH) {
                    get_queries();
                    nxt &= ~CTL_SHIFT;
                    ctl_tab &= ~CTL_SHIFT;
                }
                if (nxt & CTL_HALF) {
                    ctl = nxt;
                    float T[32];
                    bar_sync(2 + w, 256);
                    wg_fence();
                    issue_qk_half(T, Q, kdesc0 + (ctl & 0x3800));
                    wg_commit();
                    l[0] += sum[0]; l[1] += sum[1];
                    nxt = __shfl_sync(~0u, ctl_tab, ++t);
                    wait_block(ctl >> 16);
                    const uint32_t vdesc = vdesc0 + ((ctl >> 16) & 0x3800);
                    wg_fence();
                    issue_pv<0>(O, Pm, vdesc, ctl & CTL_PVACC);
                    wg_commit();
                    issue_pv<1>(O, Pm, vdesc, 1);
                    wg_commit();
                    bar_arrive(3 - w, 256);
                    wg_wait<2>();
                    reg_fence(T);
#pragma unroll
                    for (int i = 0; i < 32; i++) S[i] = T[i];
                    continue;
                }
            }
            ctl = nxt;
            bar_sync(2 + w, 256);
            wg_fence();
            issue_qk(S, Q, kdesc0 + (ctl & 0x3800));
            wg_commit();
            l[0] += sum[0]; l[1] += sum[1];
            nxt = __shfl_sync(~0u, ctl_tab, ++t);
            if (ctl & (CTL_SWITCH | CTL_WOUT)) {
                if (ctl & CTL_SWITCH) {
                    scale[0] = rcp_approx(quad_sum(l[0]));
                    scale[1] = rcp_approx(quad_sum(l[1]));
                    l[0] = l[1] = mc[0] = mc[1] = 0.f;
                    if (w == 1) { release((ctl >> 3) - 2); release((ctl >> 3) + 1); }
                } else {
                    write_out(std::false_type());
                }
            }
            wait_block(ctl >> 16);
            const uint32_t vdesc = vdesc0 + ((ctl >> 16) & 0x3800);
            if (!(ctl & CTL_PVHALF)) {
                wg_fence();
                issue_pv<0>(O, Pm, vdesc, ctl & CTL_PVACC);
                wg_commit();
                issue_pv<1>(O, Pm, vdesc, 1);
                wg_commit();
            } else {
                wg_fence();
                issue_pv<0>(O, Pm, vdesc, ctl & CTL_PVACC);
                wg_commit();
                wg_commit();
            }
            bar_arrive(3 - w, 256);
            wg_wait<2>();
            reg_fence(S);
        }
        g += 36;
        if (w == 0) release(g - 3);
        const uint32_t vdesc = vdesc0 + (nxt & 0x3800);
        if (nxt & CTL_PVHALF) {
            wg_fence();
            issue_pv<0>(O, Pm, vdesc, nxt & CTL_PVACC);
            wg_commit();
        } else {
            wg_fence();
            issue_pv<0>(O, Pm, vdesc, nxt & CTL_PVACC);
            issue_pv<1>(O, Pm, vdesc, 1);
            wg_commit();
        }
        l[0] += sum[0]; l[1] += sum[1];
        ctl_tab = (ctl_tab & ~(0x00780078u | CTL_SHIFT)) | ((ctl_tab + 0x00200020u) & 0x00780078u);
        const float i0 = rcp_approx(quad_sum(l[0])), i1 = rcp_approx(quad_sum(l[1]));
        wg_wait<0>();
        reg_fence(O);
        if (w == 0) release(g - 2);
        release(g - 1);
#pragma unroll
        for (int i = 0; i < 32; i++) {
            const float sc = (i & 4) ? i1 : i0;
            pk[i] = pack_bf16(O[chunk_src(i)] * sc, O[chunk_src(i) + 1] * sc);
        }
        pend = ptr_off(ctx_dst(item == 5, 1), chunk0);
        prow = 0x400;
#pragma unroll
        for (int i = 32; i < 64; i++) pk[i] = 0;
        PROF(3 + 2 * item, w);
        if (w == 0) PROF_GT(3 + 2 * item);
    }

    float acc[64];
    uint32_t slot = 0;
    auto issue_out = [&](int first_acc) {
        wait_full(g);
        const uint64_t da = make_desc(sb + slot + w * 8192, 16), db = make_desc(sb + slot + PAGE, 8192);
        wg_fence();
#pragma unroll
        for (int q = 0; q < 4; q++) wgmma_n128_ss(acc, da + 2 * q, db + 128 * q, q ? 1 : first_acc);
        wg_commit();
        g++;
        slot = slot == SM_REGION - 2 * PAGE ? 0 : slot + 2 * PAGE;
    };
    issue_out(0);
#pragma unroll 1
    for (int kb = 1; kb < 64 - PEEL; kb++) {
        issue_out(1);
        wg_wait<1>();
        release(g - 2);
        if (kb <= 8 && !(kb & 1)) {
            store_part4(pend, (kb >> 1) - 1, pk);
            if (kb == 8) mark_done();
        }
        if (kb >= 32 - PEEL && ((kb + PEEL) & 3) == 2 * w) {
            uint32_t u0, u1, u2, u3;
            const uint32_t a = stg + ((kb + PEEL) & 16) * 512 + ((kb + PEEL) & 12) * 128 + lane * 16;
            mbar_wait(sb + BAR_G + w * 8, 0);
            lds128(a, u0, u1, u2, u3);
            sts128(a, pack_bf16(silu_f(bf_lo(u0)), silu_f(bf_hi(u0))), pack_bf16(silu_f(bf_lo(u1)), silu_f(bf_hi(u1))),
                   pack_bf16(silu_f(bf_lo(u2)), silu_f(bf_hi(u2))), pack_bf16(silu_f(bf_lo(u3)), silu_f(bf_hi(u3))));
        }
    }
    const uint32_t goff = (out_rows(pair) * 256 + c * 128 + w * 64 + v * 16 + (lane >> 3)) * (DM * 2) +
                          out_cols(pair) * 128 + (((lane & 7) ^ (lane >> 3)) << 4);
    uint32_t xr[32], gr[32];
    {
        const uint8_t* src[2] = {ptr_off(x, goff), ptr_off(x, goff ^ 64)};
#pragma unroll
        for (int i = 0; i < 8; i++) {
            const uint4 t = ldg_hint(src[i & 1] + (i & 3) * (4 * DM * 2) + (i >> 2) * 128, POL_FIRST);
            xr[4 * i] = t.x; xr[4 * i + 1] = t.y; xr[4 * i + 2] = t.z; xr[4 * i + 3] = t.w;
        }
    }
#pragma unroll 1
    for (int i = 0; i < PEEL; i++) {
        if (i == PEEL - STAG && w == 1) bar_sync(4, 256);
        issue_out(1);
        if (i == PEEL - 1 && w == 0) bar_arrive(4, 256);
        wg_wait<1>();
    }
    asm volatile("barrier.cluster.arrive.relaxed.aligned;" ::: "memory");
#pragma unroll
    for (int i = 0; i < 8; i++) lds128(stg + (i >> 2) * 8192 + (i & 3) * 512 + lane * 16, gr[4 * i], gr[4 * i + 1], gr[4 * i + 2], gr[4 * i + 3]);
    uint8_t* dst[2] = {ptr_off(out, goff), ptr_off(out, goff ^ 64)};
    __syncwarp();
    wg_wait<0>();
    reg_fence(acc);
    PROF(14, w);
    if (w == 0) PROF_GT(14);
#pragma unroll
    for (int s = 0; s < 8; s++)
        stmatrix_x4(slab_addr(stg, lane, s), pack_bf16(acc[8 * s], acc[8 * s + 1]), pack_bf16(acc[8 * s + 2], acc[8 * s + 3]),
                    pack_bf16(acc[8 * s + 4], acc[8 * s + 5]), pack_bf16(acc[8 * s + 6], acc[8 * s + 7]));
    __syncwarp();
    uint32_t o[32];
#pragma unroll
    for (int i = 0; i < 8; i++) lds128(stg + (i >> 2) * 8192 + (i & 3) * 512 + lane * 16, o[4 * i], o[4 * i + 1], o[4 * i + 2], o[4 * i + 3]);
#pragma unroll
    for (int i = 0; i < 8; i++) {
#pragma unroll
        for (int k = 0; k < 4; k++) xr[4 * i + k] = bf2_add(xr[4 * i + k], bf2_mul(o[4 * i + k], gr[4 * i + k]));
        __stcg(reinterpret_cast<uint4*>(dst[i & 1] + (i & 3) * (4 * DM * 2) + (i >> 2) * 128), make_uint4(xr[4 * i], xr[4 * i + 1], xr[4 * i + 2], xr[4 * i + 3]));
    }
    PROF(28, w);
}

__global__ void __cluster_dims__(2, 1, 1) __launch_bounds__(384, 1)
fused_kernel(const __grid_constant__ CUtensorMap m_ckv, const __grid_constant__ CUtensorMap m_wuk,
             const __grid_constant__ CUtensorMap m_wuv, const __grid_constant__ CUtensorMap m_wq,
             const __grid_constant__ CUtensorMap m_wo, const __grid_constant__ CUtensorMap m_gate,
             const __grid_constant__ CUtensorMap m_up, const __grid_constant__ CUtensorMap m_down, const Params P) {
    extern __shared__ __align__(1024) uint8_t smem[];
    const uint32_t sb = __shfl_sync(~0u, smem_u32(smem), 0);
    const int tid = threadIdx.x;
    const int cl = blockIdx.x >> 1, c = blockIdx.x & 1;
    const int pair = cl >= 64 ? cl : cl < 4 ? cl * 16 + 15 : cl < 36 ? ((cl - 4) >> 3) * 16 + ((cl - 4) & 7)
                                                                    : ((cl - 36) / 7) * 16 + 8 + (cl - 36) % 7;
    const bool starter = tid == 256 && pair < NMAIN / 2;
    const CUtensorMap* m_wu = c ? &m_wuv : &m_wuk;
    if (tid == 256) {
        mbar_init(sb + BAR_FULL, 1);
        if (starter) {
            asm volatile("fence.mbarrier_init.release.cluster;" ::: "memory");
            mbar_expect_tx(sb + BAR_FULL, 3 * PAGE);
            tma_3d(sb, m_wu, 0, 0, kv_head(pair) * 2, sb + BAR_FULL);
            tma_3d(sb + PAGE, &m_ckv, 0, kv_tokens(pair) * 256, 0, sb + BAR_FULL);
            tma_3d(sb + 2 * PAGE, &m_ckv, 0, kv_tokens(pair) * 256 + 128, 0, sb + BAR_FULL);
        }
#pragma unroll
        for (int i = 1; i < NBAR; i++) mbar_init(sb + SM_BAR + i * 8, (i >> 3) == 1 ? 16 : i >= 25 ? 8 : 1);
        asm volatile("fence.mbarrier_init.release.cluster;" ::: "memory");
    }
    if (starter) {
#pragma unroll 1
        for (int kb = 1; kb < 4; kb++) mbar_expect_tx(sb + BAR_FULL + kb * 8, 3 * PAGE);
        tma_3d(sb + 3 * PAGE, m_wu, 0, 64, kv_head(pair) * 2, sb + BAR_FULL + 8);
    }
    PROF(18, (tid >> 7) & 1);
    __syncthreads();
    cluster_sync();
    PROF(22, (tid >> 7) & 1);
    PROF(19, (tid >> 7) & 1);
    const int warp = __shfl_sync(~0u, tid >> 5, 0), lane = tid & 31;
    auto dump_prof = [&]() {
    };
    if (pair >= NMAIN / 2) {
        if (warp < 8) ffn_cta(smem, sb, blockIdx.x - NMAIN, __ldcg(&g_sync.done) / NCTA, P.w_r);
        else if (tid == 256) ffn_producer(sb, blockIdx.x - NMAIN, &m_gate, &m_up, &m_down);
        __syncwarp();
        PROF(29, tid >> 7);
        cluster_sync();
        if (tid == 0) atomicAdd(&g_sync.done, 1u);
        if (warp < 8) dump_prof();
    } else if (warp < 8) {
        asm volatile("setmaxnreg.inc.sync.aligned.u32 232;");
        consumer(sb, pair, c, P.out, (const uint8_t*)P.x);
        PROF(29, tid >> 7);
        asm volatile("barrier.cluster.wait.aligned;" ::: "memory");
        dump_prof();
    } else {
        asm volatile("setmaxnreg.dec.sync.aligned.u32 40;");
        if (starter) {
#pragma unroll 1
            for (int kb = 1; kb < 4; kb++) {
                if (kb > 1) tma_3d(sb + kb * (3 * PAGE), m_wu, 0, kb * 64, kv_head(pair) * 2, sb + BAR_FULL + kb * 8);
                tma_3d_mc(sb + kb * (3 * PAGE) + (1 + c) * PAGE, &m_ckv, 0, kv_tokens(pair) * 256 + c * 128, kb, sb + BAR_FULL + kb * 8);
            }
        }
        if (warp == 10) {
            sync_helper(sb, lane, pair, c);
        } else if (warp & 1) {
            fetch_helper((warp & 2) ? P.w_uv : P.w_uk, (const uint8_t*)P.x, sb, (warp >> 1) & 1, lane, pair, c);
        } else {
            producer(P, sb, pair, c, &m_ckv, m_wu, &m_wq, &m_wo);
        }
        bar_sync(6, 128);
        if (tid == 256) atomicAdd(&g_sync.done, 1u);
        cluster_sync();
    }
}

typedef CUresult (*EncodeFn)(CUtensorMap*, CUtensorMapDataType, cuuint32_t, void*, const cuuint64_t*, const cuuint64_t*,
                             const cuuint32_t*, const cuuint32_t*, CUtensorMapInterleave, CUtensorMapSwizzle,
                             CUtensorMapL2promotion, CUtensorMapFloatOOBfill);

void make_map_w(EncodeFn fn, CUtensorMap* m, const void* ptr, int rows, int cols, int blocks, int box_rows = 32) {
    cuuint64_t dims[3] = {64, (cuuint64_t)rows, (cuuint64_t)cols / 64};
    cuuint64_t strides[2] = {(cuuint64_t)cols * 2, 128};
    cuuint32_t box[3] = {64, (cuuint32_t)box_rows, (cuuint32_t)blocks};
    cuuint32_t es[3] = {1, 1, 1};
    fn(m, CU_TENSOR_MAP_DATA_TYPE_BFLOAT16, 3, const_cast<void*>(ptr), dims, strides, box, es, CU_TENSOR_MAP_INTERLEAVE_NONE,
       CU_TENSOR_MAP_SWIZZLE_128B, CU_TENSOR_MAP_L2_PROMOTION_L2_256B, CU_TENSOR_MAP_FLOAT_OOB_FILL_NONE);
}

}

extern "C" void kernel_launch(void* const* d_in, const int* in_sizes, int n_in, void* d_out, int out_size) {
    static EncodeFn fn = nullptr;
    if (!fn) {
        void* f = nullptr;
        cudaDriverEntryPointQueryResult qr;
        cudaGetDriverEntryPoint("cuTensorMapEncodeTiled", &f, cudaEnableDefault, &qr);
        fn = (EncodeFn)f;
        cudaFuncSetAttribute(fused_kernel, cudaFuncAttributeMaxDynamicSharedMemorySize, SMEM_BYTES);
    }
    CUtensorMap m_ckv, m_wuk, m_wuv, m_wq, m_wo, m_gate, m_up, m_down;
    make_map_w(fn, &m_gate, d_in[8], DM, FF, FS / 64, 16);
    make_map_w(fn, &m_up, d_in[9], DM, FF, FS / 64, 16);
    make_map_w(fn, &m_down, d_in[10], FF, DM, DM / 64, 16);
    make_map_w(fn, &m_ckv, d_in[1], SEQ, DC, 1, 128);
    make_map_w(fn, &m_wq, d_in[2], DM, NH * 128, 1, 64);
    make_map_w(fn, &m_wuk, d_in[3], DC, NH * 128, 2, 64);
    make_map_w(fn, &m_wuv, d_in[4], DC, NH * 128, 2, 64);
    make_map_w(fn, &m_wo, d_in[5], NH * 128, DM, 1, 64);
    Params P;
    P.x = (const __nv_bfloat16*)d_in[0];
    P.w_r = (const __nv_bfloat16*)d_in[7];
    P.c_kv = (const uint8_t*)d_in[1];
    P.w_uk = (const uint8_t*)d_in[3];
    P.w_uv = (const uint8_t*)d_in[4];
    P.out = (uint8_t*)d_out;
    fused_kernel<<<NCTA, 384, SMEM_BYTES>>>(m_ckv, m_wuk, m_wuv, m_wq, m_wo, m_gate, m_up, m_down, P);
}
```

```cpp
#include <cuda_runtime.h>
#include <cuda_bf16.h>
#include <cuda.h>
#include <stdint.h>
#include <type_traits>

namespace {

constexpr int SEQ = 2048, DM = 1024, NH = 32, DC = 512, FF = 3584;
constexpr int PAGE = 16384;
constexpr int NRING = 12;
constexpr int NCTA = 132, NMAIN = 128;
constexpr uint32_t SM_REGION = NRING * PAGE;
constexpr uint32_t SM_BAR = (NRING + 2) * PAGE;
constexpr uint32_t BAR_FULL = SM_BAR, BAR_EMPTY = SM_BAR + 64;
constexpr uint32_t BAR_DEP = SM_BAR + 128;
constexpr uint32_t BAR_G = SM_BAR + 184;
constexpr uint32_t BAR_DONE = SM_BAR + 200;
constexpr uint32_t BAR_EMPTYL = SM_BAR + 216;
constexpr int NBAR = 35;
constexpr uint32_t SM_PROF = SM_BAR + 320;
constexpr int SMEM_BYTES = SM_PROF + 512;
constexpr uint32_t SPIN_LIMIT = 1u << 16;
constexpr uint32_t POLL_MASK = 7;
constexpr int EARLY = 2;
constexpr int WN = 5;
constexpr int PEEL = 5, STAG = 3;

struct SyncBlock {
    unsigned done;       unsigned pad0[31];
    unsigned ln;         unsigned pad1[31];
    unsigned router;     unsigned pad4[31];
    unsigned ffn_ticket; unsigned pad2[31];
    unsigned ffn_done;   unsigned pad3[31];
    unsigned kv[NH * 8];
    unsigned kvfree[16 * 8];
    unsigned ctx[32 * NH];
};

__device__ __align__(1024) uint8_t g_xn[8 * 16 * 4 * 8192];
__device__ __align__(4096) uint8_t g_kv[16 * 16 * 65536];
__device__ __align__(4096) uint8_t g_ctx[16 * 64 * 16384];
__device__ __align__(16) uint4 g_routed[2 * 128];
__device__ int g_sel[2];
__device__ __align__(16) float g_r[SEQ];
__device__ __align__(16) float g_ypart[4 * 2 * DM];
__device__ SyncBlock g_sync;

__device__ __forceinline__ uint32_t smem_u32(const void* p) { return (uint32_t)__cvta_generic_to_shared(p); }

__device__ __forceinline__ void mbar_init(uint32_t bar, uint32_t count) {
    asm volatile("mbarrier.init.shared::cta.b64 [%0], %1;" ::"r"(bar), "r"(count) : "memory");
}
#define MBAR_WAIT_ASM(HINT, LIMIT)                                                                  \
    asm volatile("{\n.reg .pred p;\n.reg .u32 n;\nmov.u32 n, 0;\n"                                  \
                 "WAIT_LOOP:\n"                                                                     \
                 "mbarrier.try_wait.parity.shared::cta.b64 p, [%0], %1" HINT ";\n"                  \
                 "@p bra WAIT_DONE;\n"                                                              \
                 "add.u32 n, n, 1;\n"                                                               \
                 "setp.lt.u32 p, n, " LIMIT ";\n"                                                   \
                 "@p bra WAIT_LOOP;\n"                                                              \
                 "WAIT_DONE:\n}\n" ::"r"(bar), "r"(parity) : "memory")
__device__ __forceinline__ void mbar_wait(uint32_t bar, uint32_t parity) { MBAR_WAIT_ASM("", "131072"); }
__device__ __forceinline__ void mbar_sleep(uint32_t bar, uint32_t parity) { MBAR_WAIT_ASM(", 2000", "8192"); }
__device__ __forceinline__ bool mbar_try(uint32_t bar, uint32_t parity) {
    uint32_t ok;
    asm volatile("{\n.reg .pred p;\nmbarrier.try_wait.parity.shared::cta.b64 p, [%1], %2;\nselp.u32 %0, 1, 0, p;\n}\n"
                 : "=r"(ok) : "r"(bar), "r"(parity) : "memory");
    return ok;
}
__device__ __forceinline__ bool mbar_test(uint32_t bar, uint32_t parity) {
    uint32_t ok;
    asm volatile("{\n.reg .pred p;\nmbarrier.test_wait.parity.shared::cta.b64 p, [%1], %2;\nselp.u32 %0, 1, 0, p;\n}\n"
                 : "=r"(ok) : "r"(bar), "r"(parity) : "memory");
    return ok;
}
__device__ __forceinline__ bool elect_one() {
    uint32_t ok;
    asm volatile("{\n.reg .pred p;\nelect.sync _|p, 0xffffffff;\nselp.u32 %0, 1, 0, p;\n}\n" : "=r"(ok));
    return ok;
}
__device__ __forceinline__ void mbar_arrive(uint32_t bar) {
    asm volatile("mbarrier.arrive.shared::cta.b64 _, [%0];" ::"r"(bar) : "memory");
}
__device__ __forceinline__ void mbar_expect_tx(uint32_t bar, uint32_t bytes) {
    asm volatile("mbarrier.arrive.expect_tx.shared::cta.b64 _, [%0], %1;" ::"r"(bar), "r"(bytes) : "memory");
}
__device__ __forceinline__ void mbar_arrive_cluster(uint32_t cluster_addr) {
    asm volatile("mbarrier.arrive.shared::cluster.b64 _, [%0];" ::"r"(cluster_addr) : "memory");
}
__device__ __forceinline__ uint32_t mapa(uint32_t addr, uint32_t rank) {
    uint32_t r;
    asm("mapa.shared::cluster.u32 %0, %1, %2;" : "=r"(r) : "r"(addr), "r"(rank));
    return r;
}
__device__ __forceinline__ void tma_3d(uint32_t dst, const CUtensorMap* m, int c0, int c1, int c2, uint32_t bar) {
    asm volatile("cp.async.bulk.tensor.3d.shared::cluster.global.mbarrier::complete_tx::bytes [%0], [%1, {%3, %4, %5}], [%2];"
                 ::"r"(dst), "l"(m), "r"(bar), "r"(c0), "r"(c1), "r"(c2) : "memory");
}
__device__ __forceinline__ void tma_3d_hint(uint32_t dst, const CUtensorMap* m, int c0, int c1, int c2, uint32_t bar, uint64_t pol) {
    asm volatile("cp.async.bulk.tensor.3d.shared::cluster.global.mbarrier::complete_tx::bytes.L2::cache_hint [%0], [%1, {%3, %4, %5}], [%2], %6;"
                 ::"r"(dst), "l"(m), "r"(bar), "r"(c0), "r"(c1), "r"(c2), "l"(pol) : "memory");
}
__device__ __forceinline__ void tma_3d_mc(uint32_t dst, const CUtensorMap* m, int c0, int c1, int c2, uint32_t bar) {
    asm volatile("cp.async.bulk.tensor.3d.shared::cluster.global.mbarrier::complete_tx::bytes.multicast::cluster [%0], [%1, {%3, %4, %5}], [%2], %6;"
                 ::"r"(dst), "l"(m), "r"(bar), "r"(c0), "r"(c1), "r"(c2), "h"((uint16_t)3) : "memory");
}
__device__ __forceinline__ void bulk_load(uint32_t dst, const void* src, uint32_t bytes, uint32_t bar) {
    asm volatile("cp.async.bulk.shared::cluster.global.mbarrier::complete_tx::bytes [%0], [%1], %2, [%3];"
                 ::"r"(dst), "l"(src), "r"(bytes), "r"(bar) : "memory");
}
__device__ __forceinline__ void cp_async16(uint32_t dst, const void* src) {
    asm volatile("cp.async.cg.shared.global [%0], [%1], 16;" ::"r"(dst), "l"(src) : "memory");
}
__device__ __forceinline__ void bulk_load_mc(uint32_t dst, const void* src, uint32_t bytes, uint32_t bar) {
    asm volatile("cp.async.bulk.shared::cluster.global.mbarrier::complete_tx::bytes.multicast::cluster [%0], [%1], %2, [%3], %4;"
                 ::"r"(dst), "l"(src), "r"(bytes), "r"(bar), "h"((uint16_t)3) : "memory");
}
__device__ __forceinline__ void fence_async_smem() { asm volatile("fence.proxy.async.shared::cta;" ::: "memory"); }
__device__ __forceinline__ void prefetch_map(const CUtensorMap* m) {
    asm volatile("prefetch.tensormap [%0];" ::"l"(m) : "memory");
}
__device__ __forceinline__ void red_release(unsigned* p) {
    asm volatile("red.release.gpu.global.add.u32 [%0], 1;" ::"l"(p) : "memory");
}
__device__ __forceinline__ unsigned ld_relaxed(const unsigned* p) {
    unsigned v;
    asm volatile("ld.relaxed.gpu.global.u32 %0, [%1];" : "=r"(v) : "l"(p) : "memory");
    return v;
}
__device__ __forceinline__ void wait_counter(const unsigned* p, unsigned target) {
    for (uint32_t n = 0; (int)(ld_relaxed(p) - target) < 0 && n < SPIN_LIMIT; n++) __nanosleep(100);
    asm volatile("fence.acquire.gpu;" ::: "memory");
    asm volatile("fence.proxy.async.global;" ::: "memory");
}
__device__ __forceinline__ void bar_sync(int id, int n) { asm volatile("bar.sync %0, %1;" ::"r"(id), "r"(n) : "memory"); }
__device__ __forceinline__ void bar_arrive(int id, int n) { asm volatile("bar.arrive %0, %1;" ::"r"(id), "r"(n) : "memory"); }
__device__ __forceinline__ void cluster_sync() {
    asm volatile("barrier.cluster.arrive.relaxed.aligned;\nbarrier.cluster.wait.aligned;" ::: "memory");
}
__device__ __forceinline__ void wg_fence() { asm volatile("wgmma.fence.sync.aligned;" ::: "memory"); }
__device__ __forceinline__ void wg_commit() { asm volatile("wgmma.commit_group.sync.aligned;" ::: "memory"); }
template <int N> __device__ __forceinline__ void wg_wait() { asm volatile("wgmma.wait_group.sync.aligned %0;" ::"n"(N) : "memory"); }
template <int N> __device__ __forceinline__ void reg_fence(float (&a)[N]) {
#pragma unroll
    for (int i = 0; i < N; i++) asm volatile("" : "+f"(a[i])::"memory");
}
template <int N> __device__ __forceinline__ void reg_fence(uint32_t (&a)[N]) {
#pragma unroll
    for (int i = 0; i < N; i++) asm volatile("" : "+r"(a[i])::"memory");
}
__device__ __forceinline__ uint32_t pack_bf16(float lo, float hi) {
    uint32_t r;
    asm("cvt.rn.bf16x2.f32 %0, %1, %2;" : "=r"(r) : "f"(hi), "f"(lo));
    return r;
}
__device__ __forceinline__ float bf_lo(uint32_t v) { return __uint_as_float(v << 16); }
__device__ __forceinline__ float bf_hi(uint32_t v) { return __uint_as_float(v & 0xffff0000u); }
__device__ __forceinline__ float bf_round(float v) { return __bfloat162float(__float2bfloat16_rn(v)); }
__device__ __forceinline__ float ex2(float v) {
    float r;
    asm("ex2.approx.ftz.f32 %0, %1;" : "=f"(r) : "f"(v));
    return r;
}
__device__ __forceinline__ float sqrt_approx(float v) {
    float r;
    asm("sqrt.approx.ftz.f32 %0, %1;" : "=f"(r) : "f"(v));
    return r;
}
__device__ __forceinline__ float rcp_approx(float v) {
    float r;
    asm("rcp.approx.ftz.f32 %0, %1;" : "=f"(r) : "f"(v));
    return r;
}
__device__ __forceinline__ float silu_f(float v) { return v * rcp_approx(1.0f + ex2(v * -1.4426950408889634f)); }
__device__ __forceinline__ void stmatrix_x4(uint32_t addr, uint32_t r0, uint32_t r1, uint32_t r2, uint32_t r3) {
    asm volatile("stmatrix.sync.aligned.m8n8.x4.shared.b16 [%0], {%1, %2, %3, %4};"
                 ::"r"(addr), "r"(r0), "r"(r1), "r"(r2), "r"(r3) : "memory");
}
__device__ __forceinline__ void sts128(uint32_t addr, uint32_t r0, uint32_t r1, uint32_t r2, uint32_t r3) {
    asm volatile("st.shared.v4.b32 [%0], {%1, %2, %3, %4};" ::"r"(addr), "r"(r0), "r"(r1), "r"(r2), "r"(r3) : "memory");
}
__device__ __forceinline__ void lds128(uint32_t addr, uint32_t& r0, uint32_t& r1, uint32_t& r2, uint32_t& r3) {
    asm volatile("ld.shared.v4.b32 {%0, %1, %2, %3}, [%4];" : "=r"(r0), "=r"(r1), "=r"(r2), "=r"(r3) : "r"(addr) : "memory");
}
__device__ __forceinline__ uint32_t bf2_mul(uint32_t a, uint32_t b) {
    uint32_t r;
    asm("mul.rn.bf16x2 %0, %1, %2;" : "=r"(r) : "r"(a), "r"(b));
    return r;
}
__device__ __forceinline__ uint32_t bf2_add(uint32_t a, uint32_t b) {
    uint32_t r;
    asm("add.rn.bf16x2 %0, %1, %2;" : "=r"(r) : "r"(a), "r"(b));
    return r;
}
constexpr uint64_t POL_FIRST = 0x12F0000000000000ull, POL_NORMAL = 0x1000000000000000ull;
__device__ __forceinline__ uint4 ldg_hint(const void* p, uint64_t pol) {
    uint4 v;
    asm volatile("ld.global.cg.L2::cache_hint.v4.u32 {%0, %1, %2, %3}, [%4], %5;" : "=r"(v.x), "=r"(v.y), "=r"(v.z), "=r"(v.w) : "l"(p), "l"(pol));
    return v;
}
__device__ __forceinline__ void stg_hint(void* p, uint32_t r0, uint32_t r1, uint32_t r2, uint32_t r3, uint64_t pol) {
    asm volatile("st.global.cg.L2::cache_hint.v4.u32 [%0], {%1, %2, %3, %4}, %5;" ::"l"(p), "r"(r0), "r"(r1), "r"(r2), "r"(r3), "l"(pol) : "memory");
}

__device__ __forceinline__ uint64_t make_desc(uint32_t addr, uint32_t lbo_bytes) {
    return (uint64_t)((addr & 0x3FFFF) >> 4) | ((uint64_t)(lbo_bytes >> 4) << 16) | ((uint64_t)(1024 >> 4) << 32) | (1ull << 62);
}

__device__ __forceinline__ void wgmma_n256_ss(float (&d)[128], uint64_t da, uint64_t db, int acc) {
    asm volatile(
        "{\n.reg .pred p;\nsetp.ne.b32 p, %130, 0;\n"
        "wgmma.mma_async.sync.aligned.m64n256k16.f32.bf16.bf16 {"
        "%0, %1, %2, %3, %4, %5, %6, %7, %8, %9, %10, %11, %12, %13, %14, %15, "
        "%16, %17, %18, %19, %20, %21, %22, %23, %24, %25, %26, %27, %28, %29, %30, %31, "
        "%32, %33, %34, %35, %36, %37, %38, %39, %40, %41, %42, %43, %44, %45, %46, %47, "
        "%48, %49, %50, %51, %52, %53, %54, %55, %56, %57, %58, %59, %60, %61, %62, %63, "
        "%64, %65, %66, %67, %68, %69, %70, %71, %72, %73, %74, %75, %76, %77, %78, %79, "
        "%80, %81, %82, %83, %84, %85, %86, %87, %88, %89, %90, %91, %92, %93, %94, %95, "
        "%96, %97, %98, %99, %100, %101, %102, %103, %104, %105, %106, %107, %108, %109, %110, %111, "
        "%112, %113, %114, %115, %116, %117, %118, %119, %120, %121, %122, %123, %124, %125, %126, %127"
        "}, %128, %129, p, 1, 1, 1, 0;\n}\n"
        :
        "+f"(d[0]), "+f"(d[1]), "+f"(d[2]), "+f"(d[3]), "+f"(d[4]), "+f"(d[5]), "+f"(d[6]), "+f"(d[7]),
        "+f"(d[8]), "+f"(d[9]), "+f"(d[10]), "+f"(d[11]), "+f"(d[12]), "+f"(d[13]), "+f"(d[14]), "+f"(d[15]),
        "+f"(d[16]), "+f"(d[17]), "+f"(d[18]), "+f"(d[19]), "+f"(d[20]), "+f"(d[21]), "+f"(d[22]), "+f"(d[23]),
        "+f"(d[24]), "+f"(d[25]), "+f"(d[26]), "+f"(d[27]), "+f"(d[28]), "+f"(d[29]), "+f"(d[30]), "+f"(d[31]),
        "+f"(d[32]), "+f"(d[33]), "+f"(d[34]), "+f"(d[35]), "+f"(d[36]), "+f"(d[37]), "+f"(d[38]), "+f"(d[39]),
        "+f"(d[40]), "+f"(d[41]), "+f"(d[42]), "+f"(d[43]), "+f"(d[44]), "+f"(d[45]), "+f"(d[46]), "+f"(d[47]),
        "+f"(d[48]), "+f"(d[49]), "+f"(d[50]), "+f"(d[51]), "+f"(d[52]), "+f"(d[53]), "+f"(d[54]), "+f"(d[55]),
        "+f"(d[56]), "+f"(d[57]), "+f"(d[58]), "+f"(d[59]), "+f"(d[60]), "+f"(d[61]), "+f"(d[62]), "+f"(d[63]),
        "+f"(d[64]), "+f"(d[65]), "+f"(d[66]), "+f"(d[67]), "+f"(d[68]), "+f"(d[69]), "+f"(d[70]), "+f"(d[71]),
        "+f"(d[72]), "+f"(d[73]), "+f"(d[74]), "+f"(d[75]), "+f"(d[76]), "+f"(d[77]), "+f"(d[78]), "+f"(d[79]),
        "+f"(d[80]), "+f"(d[81]), "+f"(d[82]), "+f"(d[83]), "+f"(d[84]), "+f"(d[85]), "+f"(d[86]), "+f"(d[87]),
        "+f"(d[88]), "+f"(d[89]), "+f"(d[90]), "+f"(d[91]), "+f"(d[92]), "+f"(d[93]), "+f"(d[94]), "+f"(d[95]),
        "+f"(d[96]), "+f"(d[97]), "+f"(d[98]), "+f"(d[99]), "+f"(d[100]), "+f"(d[101]), "+f"(d[102]), "+f"(d[103]),
        "+f"(d[104]), "+f"(d[105]), "+f"(d[106]), "+f"(d[107]), "+f"(d[108]), "+f"(d[109]), "+f"(d[110]), "+f"(d[111]),
        "+f"(d[112]), "+f"(d[113]), "+f"(d[114]), "+f"(d[115]), "+f"(d[116]), "+f"(d[117]), "+f"(d[118]), "+f"(d[119]),
        "+f"(d[120]), "+f"(d[121]), "+f"(d[122]), "+f"(d[123]), "+f"(d[124]), "+f"(d[125]), "+f"(d[126]), "+f"(d[127])
        : "l"(da), "l"(db), "r"(acc));
}

__device__ __forceinline__ void wgmma_n64_rs_tb(float* d, uint32_t a0, uint32_t a1, uint32_t a2, uint32_t a3, uint32_t db, int acc) {
    asm volatile(
        "{\n.reg .pred p;\n.reg .b64 db;\nsetp.ne.b32 p, %37, 0;\nmov.b64 db, {%36, 0x40000040};\n"
        "wgmma.mma_async.sync.aligned.m64n64k16.f32.bf16.bf16 {"
        "%0, %1, %2, %3, %4, %5, %6, %7, %8, %9, %10, %11, %12, %13, %14, %15, "
        "%16, %17, %18, %19, %20, %21, %22, %23, %24, %25, %26, %27, %28, %29, %30, %31"
        "}, {%32, %33, %34, %35}, db, p, 1, 1, 1;\n}\n"
        :
        "+f"(d[0]), "+f"(d[1]), "+f"(d[2]), "+f"(d[3]), "+f"(d[4]), "+f"(d[5]), "+f"(d[6]), "+f"(d[7]),
        "+f"(d[8]), "+f"(d[9]), "+f"(d[10]), "+f"(d[11]), "+f"(d[12]), "+f"(d[13]), "+f"(d[14]), "+f"(d[15]),
        "+f"(d[16]), "+f"(d[17]), "+f"(d[18]), "+f"(d[19]), "+f"(d[20]), "+f"(d[21]), "+f"(d[22]), "+f"(d[23]),
        "+f"(d[24]), "+f"(d[25]), "+f"(d[26]), "+f"(d[27]), "+f"(d[28]), "+f"(d[29]), "+f"(d[30]), "+f"(d[31])
        : "r"(a0), "r"(a1), "r"(a2), "r"(a3), "r"(db), "r"(acc));
}

template <int TB>
__device__ __forceinline__ void wgmma_n128_rs(float (&d)[64], uint32_t a0, uint32_t a1, uint32_t a2, uint32_t a3, uint32_t db, int acc) {
    asm volatile(
        "{\n.reg .pred p;\n.reg .b64 db;\nsetp.ne.b32 p, %69, 0;\nmov.b64 db, {%68, 0x40000040};\n"
        "wgmma.mma_async.sync.aligned.m64n128k16.f32.bf16.bf16 {"
        "%0, %1, %2, %3, %4, %5, %6, %7, %8, %9, %10, %11, %12, %13, %14, %15, "
        "%16, %17, %18, %19, %20, %21, %22, %23, %24, %25, %26, %27, %28, %29, %30, %31, "
        "%32, %33, %34, %35, %36, %37, %38, %39, %40, %41, %42, %43, %44, %45, %46, %47, "
        "%48, %49, %50, %51, %52, %53, %54, %55, %56, %57, %58, %59, %60, %61, %62, %63"
        "}, {%64, %65, %66, %67}, db, p, 1, 1, %70;\n}\n"
        :
        "+f"(d[0]), "+f"(d[1]), "+f"(d[2]), "+f"(d[3]), "+f"(d[4]), "+f"(d[5]), "+f"(d[6]), "+f"(d[7]),
        "+f"(d[8]), "+f"(d[9]), "+f"(d[10]), "+f"(d[11]), "+f"(d[12]), "+f"(d[13]), "+f"(d[14]), "+f"(d[15]),
        "+f"(d[16]), "+f"(d[17]), "+f"(d[18]), "+f"(d[19]), "+f"(d[20]), "+f"(d[21]), "+f"(d[22]), "+f"(d[23]),
        "+f"(d[24]), "+f"(d[25]), "+f"(d[26]), "+f"(d[27]), "+f"(d[28]), "+f"(d[29]), "+f"(d[30]), "+f"(d[31]),
        "+f"(d[32]), "+f"(d[33]), "+f"(d[34]), "+f"(d[35]), "+f"(d[36]), "+f"(d[37]), "+f"(d[38]), "+f"(d[39]),
        "+f"(d[40]), "+f"(d[41]), "+f"(d[42]), "+f"(d[43]), "+f"(d[44]), "+f"(d[45]), "+f"(d[46]), "+f"(d[47]),
        "+f"(d[48]), "+f"(d[49]), "+f"(d[50]), "+f"(d[51]), "+f"(d[52]), "+f"(d[53]), "+f"(d[54]), "+f"(d[55]),
        "+f"(d[56]), "+f"(d[57]), "+f"(d[58]), "+f"(d[59]), "+f"(d[60]), "+f"(d[61]), "+f"(d[62]), "+f"(d[63])
        : "r"(a0), "r"(a1), "r"(a2), "r"(a3), "r"(db), "r"(acc), "n"(TB));
}

__device__ __forceinline__ void wgmma_n128_ss(float* d, uint64_t da, uint64_t db, int acc) {
    asm volatile(
        "{\n.reg .pred p;\nsetp.ne.b32 p, %66, 0;\n"
        "wgmma.mma_async.sync.aligned.m64n128k16.f32.bf16.bf16 {"
        "%0, %1, %2, %3, %4, %5, %6, %7, %8, %9, %10, %11, %12, %13, %14, %15, "
        "%16, %17, %18, %19, %20, %21, %22, %23, %24, %25, %26, %27, %28, %29, %30, %31, "
        "%32, %33, %34, %35, %36, %37, %38, %39, %40, %41, %42, %43, %44, %45, %46, %47, "
        "%48, %49, %50, %51, %52, %53, %54, %55, %56, %57, %58, %59, %60, %61, %62, %63"
        "}, %64, %65, p, 1, 1, 0, 1;\n}\n"
        :
        "+f"(d[0]), "+f"(d[1]), "+f"(d[2]), "+f"(d[3]), "+f"(d[4]), "+f"(d[5]), "+f"(d[6]), "+f"(d[7]),
        "+f"(d[8]), "+f"(d[9]), "+f"(d[10]), "+f"(d[11]), "+f"(d[12]), "+f"(d[13]), "+f"(d[14]), "+f"(d[15]),
        "+f"(d[16]), "+f"(d[17]), "+f"(d[18]), "+f"(d[19]), "+f"(d[20]), "+f"(d[21]), "+f"(d[22]), "+f"(d[23]),
        "+f"(d[24]), "+f"(d[25]), "+f"(d[26]), "+f"(d[27]), "+f"(d[28]), "+f"(d[29]), "+f"(d[30]), "+f"(d[31]),
        "+f"(d[32]), "+f"(d[33]), "+f"(d[34]), "+f"(d[35]), "+f"(d[36]), "+f"(d[37]), "+f"(d[38]), "+f"(d[39]),
        "+f"(d[40]), "+f"(d[41]), "+f"(d[42]), "+f"(d[43]), "+f"(d[44]), "+f"(d[45]), "+f"(d[46]), "+f"(d[47]),
        "+f"(d[48]), "+f"(d[49]), "+f"(d[50]), "+f"(d[51]), "+f"(d[52]), "+f"(d[53]), "+f"(d[54]), "+f"(d[55]),
        "+f"(d[56]), "+f"(d[57]), "+f"(d[58]), "+f"(d[59]), "+f"(d[60]), "+f"(d[61]), "+f"(d[62]), "+f"(d[63])
        : "l"(da), "l"(db), "r"(acc));
}

__device__ __forceinline__ void wgmma_n8_ta(float* d, uint64_t da, uint64_t db) {
    asm volatile("wgmma.mma_async.sync.aligned.m64n8k16.f32.bf16.bf16 {%0, %1, %2, %3}, %4, %5, 1, 1, 1, 1, 0;\n"
                 : "+f"(d[0]), "+f"(d[1]), "+f"(d[2]), "+f"(d[3]) : "l"(da), "l"(db));
}

#define PROF(slot, role)
#undef PROF_GT
#define PROF_GT(slot)

struct Params {
    const __nv_bfloat16* x;
    const __nv_bfloat16* w_r;
    const uint8_t *c_kv, *w_uk, *w_uv;
    uint8_t* out;
};
__device__ __forceinline__ void lsu_prefetch(const void* p) { asm volatile("prefetch.global.L2 [%0];" ::"l"(p) : "memory"); }

template <typename T>
__device__ __forceinline__ T* ptr_off(T* base, uint32_t off) {
    uint32_t lo, hi;
    asm("mov.b64 {%0, %1}, %2;" : "=r"(lo), "=r"(hi) : "l"(base));
    asm("add.cc.u32 %0, %0, %2;\naddc.u32 %1, %1, 0;" : "+r"(lo), "+r"(hi) : "r"(off));
    T* r;
    asm("mov.b64 %0, {%1, %2};" : "=l"(r) : "r"(lo), "r"(hi));
    return r;
}
__device__ __forceinline__ int kv_head(int pair) { return pair & 7; }
__device__ __forceinline__ int kv_tokens(int pair) { return ((pair >> 3) & 1) * 4 + (pair >> 4); }
__device__ __forceinline__ int out_rows(int pair) { return pair & 7; }
__device__ __forceinline__ int out_cols(int pair) { return (pair >> 4) * 4 + ((pair >> 3) & 1) * 2; }
__device__ __forceinline__ int attn_rowblock(int pair, int seg) {
    int j = pair & 3, hl = pair >> 2;
    return (((hl & 1) | (j == 0)) ^ seg) ? j : 7 - j;
}
__device__ __forceinline__ int outproj_head(int i, int ib) {
    if (i < 16) return i;
    return 16 + 2 * (i & 7) + ((ib < 4) ^ ((i >> 3) & 1));
}

__device__ __forceinline__ void pin_value(uint32_t& v) { asm volatile("" : "+r"(v)); }
__device__ __forceinline__ void pin_value(int& v) { asm volatile("" : "+r"(v)); }
__device__ __forceinline__ void pin_value(const uint8_t*& v) { asm volatile("" : "+l"(v)); }

__device__ __forceinline__ void producer(const Params& P, uint32_t sb, int pair, int c,
                                         const CUtensorMap* m_ckv, const CUtensorMap* m_wu,
                                         const CUtensorMap* m_wq, const CUtensorMap* m_wo) {
    const int hl = pair >> 2;
    const int ibA = attn_rowblock(pair, 0), nA = 2 * ibA + 2;
    const int ib = out_rows(pair), mi = 2 * ib + c, nb = out_cols(pair);
    const bool leader = elect_one();
    uint32_t g = 4, tail = 0;
    if (leader) prefetch_map(m_wq);
    auto wait_released = [&](uint32_t need) {
#pragma unroll 1
        for (; tail <= need; tail++) mbar_wait(sb + BAR_EMPTY + (tail & 7) * 8, (tail >> 3) & 1);
    };
    auto wait_released_here = [&](uint32_t need) {
#pragma unroll 1
        for (; tail < need; tail++) mbar_wait(sb + BAR_EMPTY + (tail & 7) * 8, (tail >> 3) & 1);
        if (tail == need) mbar_wait(sb + BAR_EMPTYL + (need & 7) * 8, (need >> 3) & 1);
    };
    auto wait_released_peer = [&](uint32_t need) {
        if (tail == need) {
            uint32_t eb = sb + BAR_EMPTY + (need & 7) * 8, ep = (need >> 3) & 1;
            tail++;
            mbar_wait(eb, ep);
        }
    };
    auto full_bar = [&]() { return sb + BAR_FULL + (g & 7) * 8; };
    auto pin = [](auto&... v) { (pin_value(v), ...); };
#pragma unroll 1
    for (int rnd = 0; rnd < 2; rnd++) {
#pragma unroll 1
        for (int i = rnd ? 0 : 4; i < 16; i++) {
            int kb = i & 7, h2 = (kv_head(pair) + (i & 8) + rnd * 16) * 2, krow = kb * 64;
            uint32_t pg = sb + (i & 3) * (3 * PAGE), pb = pg + (1 + c) * PAGE, bar = full_bar();
            pin(kb, h2, krow, pg, pb, bar);
            const uint32_t need = g - 4 - (i < 2);
            wait_released_here(need);
            if (leader) {
                mbar_expect_tx(bar, 3 * PAGE);
                tma_3d(pg, m_wu, 0, krow, h2, bar);
            }
            wait_released_peer(need);
            if (leader) {
                tma_3d_mc(pb, m_ckv, 0, kv_tokens(pair) * 256 + c * 128, kb, bar);
                if (rnd == 1 && i == 3) asm volatile("red.relaxed.gpu.global.add.u32 [%0], 1;" ::"l"(ptr_off(g_sync.kvfree, hl * 32)) : "memory");
            }
            g++;
        }
        mbar_sleep(sb + BAR_DEP, 0);
        const uint8_t* xa = ptr_off(g_xn, ibA * (16 * 32768) + c * PAGE);
        const uint8_t* xb = ptr_off(g_xn, (7 - ibA) * (16 * 32768) + (1 - c) * PAGE);
#pragma unroll 1
        for (int kb = 0; kb < DM / 64; kb++) {
            uint32_t pg = sb + (kb & 3) * (3 * PAGE), pw = pg + 2 * PAGE + c * 8192, bar = full_bar(), p2 = pg + PAGE;
            int krow = kb * 64;
            pin(pg, pw, p2, bar, krow);
            wait_released_here(g - 4);
            if (leader) {
                mbar_expect_tx(bar, 3 * PAGE);
                bulk_load(pg, xa, PAGE, bar);
            }
            wait_released_peer(g - 4);
            if (leader) {
                tma_3d_mc(pw, m_wq, 0, krow, (rnd * 16 + hl) * 2 + c, bar);
                bulk_load(p2, xb, PAGE, bar);
            }
            g++;
            xa += 32768;
            xb += 32768;
        }
        mbar_sleep(sb + BAR_DEP + 8 + rnd * 16, 0);
        if (rnd == 1 && leader) prefetch_map(m_wo);
        uint32_t pg = sb + c * PAGE;
#pragma unroll 1
        for (int j = 0; j < 36; j++) {
            const bool isk = j == 0 || ((j & 1) && j != 35);
            const int t = isk ? (j + 1) >> 1 : (j - 1) >> 1;
            const uint8_t* src = ptr_off(g_kv, (hl * 16 + (t >= nA ? t - nA : t)) * 65536 + (isk ? 0 : 32768) + c * PAGE);
            uint32_t bar = full_bar(), need = g - 6 + (j < 2) + (j < 5);
            pin(src, bar, need);
            wait_released(need);
            if (leader) {
                mbar_expect_tx(bar, 2 * PAGE);
                bulk_load_mc(pg, src, PAGE, bar);
            }
            g++;
            if (rnd == 0 && j >= 22 && j < 34) {
                const int cta = pair * 2 + c, i = j - 22;
                const uint32_t l = (threadIdx.x & 31) * 128;
                if (i < 8) lsu_prefetch(ptr_off(i & 1 ? P.w_uv : P.w_uk, cta * 32768 + (i >> 1) * 8192 + 4096 + l));
                else lsu_prefetch(ptr_off(P.c_kv, cta * 16384 + (i - 8) * 4096 + l));
            }
            pg = pg >= sb + SM_REGION - 2 * PAGE ? pg - (SM_REGION - 2 * PAGE) : pg + 2 * PAGE;
        }
    }
    uint32_t pg = sb;
#pragma unroll 1
    for (int i = 0; i < 64; i++) {
        if ((i & 15) == 0 && i != 16) mbar_sleep(sb + BAR_DEP + 32 + (i >> 1) - (i ? 8 : 0), 0);
        const int kb = outproj_head(i >> 1, ib) * 2 + (i & 1);
        const uint8_t* src = ptr_off(g_ctx, (mi * 64 + kb) * PAGE);
        uint32_t bar = full_bar(), pw = pg + PAGE + c * 8192;
        int krow = kb * 64;
        pin(src, bar, pw, krow);
        wait_released_here(g - 6);
        if (leader) {
            mbar_expect_tx(bar, 2 * PAGE);
            bulk_load(pg, src, PAGE, bar);
        }
        wait_released_peer(g - 6);
        if (leader) tma_3d_mc(pw, m_wo, 0, krow, nb + c, bar);
        g++;
        pg = pg == sb + SM_REGION - 2 * PAGE ? sb : pg + 2 * PAGE;
    }
}

__device__ __forceinline__ uint32_t xn_block(int row64, int kb) {
    return (((row64 >> 2) * 16 + kb) * 4 + ((row64 & 1) * 2 + (((row64 >> 1) & 1) ^ 1))) * 8192;
}
__device__ __forceinline__ uint32_t image_offset(int row, int ch) {
    return xn_block(row >> 6, ch >> 3) + (row & 63) * 128 + (((ch & 7) ^ (row & 7)) << 4);
}
__device__ __forceinline__ uint32_t bf2_sub(uint32_t a, uint32_t b) {
    uint32_t r;
    asm("sub.rn.bf16x2 %0, %1, %2;" : "=r"(r) : "r"(a), "r"(b));
    return r;
}
__device__ __forceinline__ uint32_t bf2_fma(uint32_t a, uint32_t b, uint32_t c) {
    uint32_t r;
    asm("fma.rn.bf16x2 %0, %1, %2, %3;" : "=r"(r) : "r"(a), "r"(b), "r"(c));
    return r;
}
template <int N0, int N>
__device__ __forceinline__ void ln_sums(const uint32_t (&u)[N], float& sum, float& sq) {
    float s0 = 0.f, s1 = 0.f, q0 = 0.f, q1 = 0.f;
#pragma unroll
    for (int k = N0; k < N0 + 16; k++) {
        const float a = bf_lo(u[k]), b = bf_hi(u[k]);
        s0 += a; s1 += b;
        q0 = fmaf(a, a, q0); q1 = fmaf(b, b, q1);
    }
    sum = s0 + s1;
    sq = q0 + q1;
}
__device__ __forceinline__ void ln_finish(float sum, float sq, uint32_t& mean2, uint32_t& rhi2, uint32_t& rlo2) {
    const float ms = sum * (1.0f / DM);
    const float var = fmaxf(fmaf(-ms, ms, sq * (1.0f / DM)), 0.f);
    const float rden = rcp_approx(bf_round(sqrt_approx(bf_round(bf_round(var) + 1e-5f))));
    const float rhi = bf_round(rden);
    mean2 = pack_bf16(ms, ms);
    rhi2 = pack_bf16(rhi, rhi);
    rlo2 = pack_bf16(rden - rhi, rden - rhi);
}
template <int N0, int N>
__device__ __forceinline__ void ln_apply(uint32_t (&u)[N], uint32_t mean2, uint32_t rhi2, uint32_t rlo2, uint8_t* dst) {
#pragma unroll
    for (int i = 0; i < 4; i++) {
        uint32_t o[4];
#pragma unroll
        for (int k = 0; k < 4; k++) {
            const uint32_t d = bf2_sub(u[N0 + 4 * i + k], mean2);
            o[k] = bf2_fma(d, rhi2, bf2_mul(d, rlo2));
        }
#pragma unroll
        for (int k = 0; k < 4; k++) u[N0 + 4 * i + k] = o[k];
        __stcg(reinterpret_cast<uint4*>(dst + i * 131072), make_uint4(o[0], o[1], o[2], o[3]));
    }
}
__device__ __forceinline__ int query_rowblock(int pair, int c, int w, int seg) {
    const int qA = (w ? 0 : 2) + c;
    return 4 * attn_rowblock(pair, seg) + (seg ? 3 - qA : qA);
}

__device__ __noinline__ void fetch_helper(const uint8_t* w_u, uint32_t sb, int w, int lane, int pair, int c) {
    const uint32_t page = sb + SM_REGION + w * PAGE + lane * 16;
    mbar_sleep(sb + BAR_FULL + 5 * 8, 0);
#pragma unroll 1
    for (int i = 0; i < 2; i++) {
        lsu_prefetch(ptr_off(w_u, ((pair * 2 + c) * 4 + i * 2 + (lane >> 4)) * 8192 + 2048 + (lane & 15) * 128));
        __nanosleep(300);
    }
    const unsigned e1 = __ldcg(&g_sync.done) / NCTA + 1;
#pragma unroll 1
    for (int e = 1; e <= 7; e += 2) mbar_sleep(sb + BAR_DONE + 8, (e >> 1) & 1);
    const int rb = out_rows(pair) * 4 + c * 2 + w, kb0 = out_cols(pair);
    const uint8_t* src = ptr_off(g_xn, xn_block(rb, kb0) + lane * 16);
#pragma unroll 1
    for (int i = 0; i < 32; i += 4) {
#pragma unroll
        for (int k = 0; k < 4; k++) cp_async16(page + (i + k) * 512, src + (i + k) * 512 + (i >> 4) * (32768 - 8192));
        __nanosleep(200);
    }
    wait_counter(&g_sync.ffn_done, e1);
    const int r = __ldcg(ptr_off(g_sel, (lane >> 4) * 4)) - rb * 64, ch = lane & 15;
    const uint4 t = __ldcg(ptr_off(g_routed, ((lane >> 4) * 128 + kb0 * 8 + ch) * 16));
    asm volatile("cp.async.wait_all;" ::: "memory");
    __syncwarp();
    if (r >= 0 && r < 64)
        sts128(sb + SM_REGION + w * PAGE + (ch >> 3) * 8192 + r * 128 + (((ch & 7) ^ (r & 7)) << 4), t.x, t.y, t.z, t.w);
    __syncwarp();
    if (lane == 0) mbar_arrive(sb + BAR_G + w * 8);
    PROF(20, 2);
}

__device__ __noinline__ void sync_helper(uint32_t sb, int lane, int pair, int c) {
    const unsigned e1 = __ldcg(&g_sync.done) / NCTA + 1;
    const int ib = out_rows(pair);
    int e = 0, b = 0;
#pragma unroll 1
    for (uint32_t n = 0; (e < 9 || b < 7) && n < SPIN_LIMIT; n++) {
        if (e < 9 && __all_sync(~0u, mbar_test(sb + BAR_DONE + (e & 1) * 8, (e >> 1) & 1))) {
            const int rnd = e > 4, ev = (e - 1) & 3;
            unsigned* flag = e == 0 ? &g_sync.ln
                           : ev < 2 ? ptr_off(g_sync.kv, (rnd * 16 + kv_head(pair) + 8 * ev) * 32)
                                    : ptr_off(g_sync.ctx, (query_rowblock(pair, c, lane & 1, ev & 1) * NH + rnd * 16 + (pair >> 2)) * 4);
            asm volatile("fence.proxy.async.global;\nfence.release.gpu;" ::: "memory");
            if (lane < ((e == 0 || ev < 2) ? 1 : 2)) asm volatile("red.relaxed.gpu.global.add.u32 [%0], 1;" ::"l"(flag) : "memory");
            PROF(10 + e, 2);
            e++;
        }
        if (b < 7 && e > 0 && (b < 4 || (n & POLL_MASK) == 0)) {
            const int i = b == 4 ? lane >> 1 : 8 * b - 24 + ((lane >> 1) & 7);
            const unsigned* cnt = b == 0 ? &g_sync.ln
                                : b == 2 ? ptr_off(g_sync.kvfree, (kv_head(pair) + 8 * (lane & 1)) * 32)
                                : b < 4 ? ptr_off(g_sync.kv, ((b >> 1) * 16 + (pair >> 2)) * 32)
                                        : ptr_off(g_sync.ctx, ((4 * ib + 2 * c + (lane & 1)) * NH + outproj_head(i & 31, ib)) * 4);
            if (__all_sync(~0u, (int)(ld_relaxed(cnt) - e1 * (b == 0 ? NMAIN : b == 2 ? 8 : b < 4 ? 16 : 1)) >= 0)) {
                asm volatile("fence.acquire.gpu;\nfence.proxy.async.global;" ::: "memory");
                __syncwarp();
                if (lane == 0) mbar_arrive(sb + BAR_DEP + b * 8);
                PROF(1 + b, 2);
                b++;
            }
        }
        __nanosleep(150);
    }
}

__device__ __forceinline__ unsigned long long block_max_key(unsigned long long k, unsigned long long* red, int tid) {
#pragma unroll
    for (int o = 16; o; o >>= 1) {
        unsigned long long t = __shfl_xor_sync(~0u, k, o);
        k = t > k ? t : k;
    }
    bar_sync(1, 256);
    if ((tid & 31) == 0) red[tid >> 5] = k;
    bar_sync(1, 256);
    k = red[0];
#pragma unroll
    for (int i = 1; i < 8; i++) k = red[i] > k ? red[i] : k;
    return k;
}

constexpr int FS = FF / 4;
constexpr int FSTAGE = 32768, FNST = 6;
constexpr int FN1 = 2 * (DM / 16), FN2 = FS / 16;

__device__ __forceinline__ void ffn_producer(uint32_t sb, int s, const CUtensorMap* m_gate, const CUtensorMap* m_up,
                                             const CUtensorMap* m_down) {
    wait_counter(&g_sync.ln, (__ldcg(&g_sync.done) / NCTA + 1) * NMAIN);
    int slot = 0, ph = 1;
#pragma unroll 1
    for (int st = 0; st < FN1 + FN2; st++) {
        mbar_sleep(sb + BAR_EMPTY + slot * 8, ph);
        const uint32_t bar = sb + BAR_FULL + slot * 8;
        const bool up = st < FN1;
        mbar_expect_tx(bar, up ? FS * 32 : DM * 32);
        tma_3d_hint(sb + slot * FSTAGE, up ? ((st & 1) ? m_up : m_gate) : m_down, 0,
                    up ? (st >> 1) * 16 : s * FS + (st - FN1) * 16, up ? s * (FS / 64) : 0, bar, POL_FIRST);
        if (++slot == FNST) { slot = 0; ph ^= 1; }
    }
}

__device__ __forceinline__ void ffn_cta(uint8_t* smem, uint32_t sb, int s, unsigned epoch, const __nv_bfloat16* w_r) {
    const int tid = threadIdx.x, lane = tid & 31;
    const int warp = __shfl_sync(~0u, tid >> 5, 0), w = warp >> 2;
    constexpr uint32_t XB = FNST * FSTAGE, HB = XB + 16384, AUX = HB + 14336;
    unsigned long long* red = reinterpret_cast<unsigned long long*>(smem + AUX);
    unsigned* flag = reinterpret_cast<unsigned*>(smem + AUX + 128);
    const unsigned e1 = epoch + 1;
    for (int i = tid; i < (16384 + 14336) / 16; i += 256) reinterpret_cast<uint4*>(smem + XB)[i] = make_uint4(0, 0, 0, 0);
    {
        float wf[32];
#pragma unroll
        for (int i = 0; i < 4; i++) {
            const uint4 t = __ldg(reinterpret_cast<const uint4*>(w_r) + lane + 32 * i);
            const uint32_t tu[4] = {t.x, t.y, t.z, t.w};
#pragma unroll
            for (int k = 0; k < 4; k++) { wf[8 * i + 2 * k] = bf_lo(tu[k]); wf[8 * i + 2 * k + 1] = bf_hi(tu[k]); }
        }
        if (tid == 0) wait_counter(&g_sync.ln, e1 * NMAIN);
        bar_sync(1, 256);
#pragma unroll 1
        for (int r0 = s * (SEQ / 4) + warp * (SEQ / 32); r0 < s * (SEQ / 4) + (warp + 1) * (SEQ / 32); r0 += 4) {
            uint4 t[4][4];
#pragma unroll
            for (int r = 0; r < 4; r++)
#pragma unroll
                for (int i = 0; i < 4; i++) t[r][i] = __ldcg(reinterpret_cast<const uint4*>(g_xn + image_offset(r0 + r, lane) + i * 131072));
            float acc[4];
#pragma unroll
            for (int r = 0; r < 4; r++) {
                float a = 0.f, b = 0.f;
#pragma unroll
                for (int i = 0; i < 4; i++) {
                    const uint32_t tu[4] = {t[r][i].x, t[r][i].y, t[r][i].z, t[r][i].w};
#pragma unroll
                    for (int k = 0; k < 4; k++) {
                        a = fmaf(bf_lo(tu[k]), wf[8 * i + 2 * k], a);
                        b = fmaf(bf_hi(tu[k]), wf[8 * i + 2 * k + 1], b);
                    }
                }
                acc[r] = a + b;
            }
#pragma unroll
            for (int o = 16; o; o >>= 1)
#pragma unroll
                for (int r = 0; r < 4; r++) acc[r] += __shfl_xor_sync(~0u, acc[r], o);
            if (lane < 4) __stcg(&g_r[r0 + lane], bf_round(lane == 0 ? acc[0] : lane == 1 ? acc[1] : lane == 2 ? acc[2] : acc[3]));
        }
        __threadfence();
        bar_sync(1, 256);
        if (tid == 0) {
            red_release(&g_sync.router);
            wait_counter(&g_sync.router, e1 * 4);
        }
        bar_sync(1, 256);
    }
    unsigned long long keys[8];
    unsigned long long best = 0;
#pragma unroll
    for (int i = 0; i < 8; i++) {
        int idx = tid + 256 * i;
        uint32_t b = __float_as_uint(__ldcg(&g_r[idx]) + 0.0f);
        b = (b & 0x80000000u) ? ~b : (b | 0x80000000u);
        keys[i] = ((unsigned long long)b << 32) | (unsigned)(SEQ - 1 - idx);
        best = keys[i] > best ? keys[i] : best;
    }
    const unsigned long long k0 = block_max_key(best, red, tid);
    best = 0;
#pragma unroll
    for (int i = 0; i < 8; i++) best = (keys[i] != k0 && keys[i] > best) ? keys[i] : best;
    const unsigned long long k1 = block_max_key(best, red, tid);
    const int row = SEQ - 1 - (int)((w ? k1 : k0) & 0xffffffffu);
    const int ch = tid & 127;
    const uint4 xrow = __ldcg(reinterpret_cast<const uint4*>(g_xn + image_offset(row, ch)));
    *reinterpret_cast<uint4*>(smem + XB + (ch >> 3) * 1024 + w * 128 + (((ch & 7) ^ w) << 4)) = xrow;
    fence_async_smem();
    bar_sync(1, 256);
    PROF(20, tid >> 7);
    int slot = 0, ph = 0, prev = 0;
    auto next_stage = [&](bool has_prev) {
        wg_commit();
        wg_wait<1>();
        if (has_prev && lane < 2) mbar_arrive(sb + BAR_EMPTY + prev * 8);
        prev = slot;
        if (++slot == FNST) { slot = 0; ph ^= 1; }
    };
    {
        float ag[28], au[28];
#pragma unroll
        for (int i = 0; i < 28; i++) ag[i] = au[i] = 0.f;
#pragma unroll 1
        for (int ks = 0; ks < DM / 16; ks++) {
            const uint64_t db = make_desc(sb + XB + (ks >> 2) * 1024 + (ks & 3) * 32, 16);
            mbar_wait(sb + BAR_FULL + slot * 8, ph);
            uint64_t da = make_desc(sb + slot * FSTAGE + w * (7 * 2048), 16);
            wg_fence();
#pragma unroll
            for (int b = 0; b < 7; b++) wgmma_n8_ta(ag + 4 * b, da + b * 128, db);
            next_stage(ks > 0);
            mbar_wait(sb + BAR_FULL + slot * 8, ph);
            da = make_desc(sb + slot * FSTAGE + w * (7 * 2048), 16);
            wg_fence();
#pragma unroll
            for (int b = 0; b < 7; b++) wgmma_n8_ta(au + 4 * b, da + b * 128, db);
            next_stage(true);
        }
        wg_wait<0>();
        reg_fence(ag);
        reg_fence(au);
        if ((lane & 3) == 0) {
#pragma unroll
            for (int i = 0; i < 28; i++) {
                const int f = (warp & 3) * 16 + (lane >> 2) + (i & 2) * 4, tok = i & 1;
                const float h = bf_round(silu_f(bf_round(ag[i]))) * bf_round(au[i]);
                *reinterpret_cast<__nv_bfloat16*>(smem + HB + (w * 7 + (i >> 2)) * 1024 + tok * 128 + (((f >> 3) ^ tok) << 4) + (f & 7) * 2) =
                    __float2bfloat16_rn(h);
            }
        }
    }
    fence_async_smem();
    bar_sync(1, 256);
    PROF(21, tid >> 7);
    {
        float ay[32];
#pragma unroll
        for (int i = 0; i < 32; i++) ay[i] = 0.f;
#pragma unroll 1
        for (int ks = 0; ks < FN2; ks++) {
            const uint64_t db = make_desc(sb + HB + (ks >> 2) * 1024 + (ks & 3) * 32, 16);
            mbar_wait(sb + BAR_FULL + slot * 8, ph);
            const uint64_t da = make_desc(sb + slot * FSTAGE + w * (8 * 2048), 16);
            wg_fence();
#pragma unroll
            for (int b = 0; b < 8; b++) wgmma_n8_ta(ay + 4 * b, da + b * 128, db);
            next_stage(true);
        }
        wg_wait<0>();
        reg_fence(ay);
        if ((lane & 3) == 0) {
#pragma unroll
            for (int i = 0; i < 32; i++)
                g_ypart[(s * 2 + (i & 1)) * DM + (w * 8 + (i >> 2)) * 64 + (warp & 3) * 16 + (lane >> 2) + (i & 2) * 4] = ay[i];
        }
    }
    PROF(23, tid >> 7);
    __threadfence();
    bar_sync(1, 256);
    if (tid == 0) {
        *flag = atomicAdd(&g_sync.ffn_ticket, 1u) == epoch * 4 + 3;
        __threadfence();
    }
    bar_sync(1, 256);
    if (*flag) {
        const float sg = bf_round(__fdividef(1.0f, 1.0f + __expf(-__ldcg(&g_r[row]))));
        const uint32_t xu[4] = {xrow.x, xrow.y, xrow.z, xrow.w};
        uint32_t o[4];
#pragma unroll
        for (int k = 0; k < 4; k++) {
            float y0 = 0.f, y1 = 0.f;
#pragma unroll
            for (int q = 0; q < 4; q++) {
                const float2 y = __ldcg(reinterpret_cast<const float2*>(&g_ypart[(q * 2 + w) * DM + ch * 8 + 2 * k]));
                y0 += y.x; y1 += y.y;
            }
            o[k] = pack_bf16(bf_lo(xu[k]) + bf_round(bf_round(y0) * sg), bf_hi(xu[k]) + bf_round(bf_round(y1) * sg));
        }
        g_routed[w * 128 + ch] = make_uint4(o[0], o[1], o[2], o[3]);
        if (ch == 0) g_sel[w] = row;
        bar_sync(1, 256);
        if (tid == 0) red_release(&g_sync.ffn_done);
    }
}

__device__ __forceinline__ uint32_t slab_addr(uint32_t stg, int lane, int s) {
    const int row = ((lane >> 3) & 1) * 8 + (lane & 7);
    const int chunk = 2 * (s & 3) + (lane >> 4);
    return stg + row * 128 + (s >> 2) * 8192 + ((chunk ^ (lane & 7)) << 4);
}

constexpr float SM_SCALE = 0.08838834764831845f * 1.4426950408889634f;
constexpr float SUM_HI = 1048576.f, SUM_LO = 1.0f / 1048576.f;

template <int I0, int I1, int J0>
__device__ __forceinline__ void mask_range(float (&S)[64], float limf) {
#pragma unroll
    for (int i = I0; i < I1; i++) {
        const int j = i >> 2;
        float t;
        asm("add.sat.f32 %0, %1, %2;" : "=f"(t) : "f"((float)(32 * (j >> 2) + 2 * (j & 3) + (i & 1) - (i & 2) * 4)), "f"(-limf));
        S[4 * J0 + i] = fmaf(t, -1e30f, S[4 * J0 + i]);
    }
}
template <int J0>
__device__ __forceinline__ void mask_half(float (&S)[64], float limf, int v) {
    asm volatile("" : "+f"(limf));
    if (v < 2) {
        mask_range<0, 16, J0>(S, limf);
#pragma unroll
        for (int i = 16; i < 32; i++) S[4 * J0 + i] = -1e30f;
    } else {
        mask_range<16, 32, J0>(S, limf);
    }
}
__device__ __forceinline__ void issue_qk(float (&S)[64], const uint32_t (&Q)[32], uint32_t d0) {
#pragma unroll
    for (int s = 0; s < 8; s++)
        wgmma_n128_rs<1>(S, Q[4 * s], Q[4 * s + 1], Q[4 * s + 2], Q[4 * s + 3], d0 + s * 128, s > 0);
}
__device__ __forceinline__ void issue_qk_half(float (&T)[32], const uint32_t (&Q)[32], uint32_t d0) {
#pragma unroll
    for (int s = 0; s < 8; s++) wgmma_n64_rs_tb(T, Q[4 * s], Q[4 * s + 1], Q[4 * s + 2], Q[4 * s + 3], d0 + s * 128, s > 0);
}
template <int H>
__device__ __forceinline__ void issue_pv(float (&O)[64], const uint32_t (&Pm)[32], uint32_t d0, int acc) {
#pragma unroll
    for (int s = 4 * H; s < 4 * H + 4; s++)
        wgmma_n128_rs<0>(O, Pm[4 * s], Pm[4 * s + 1], Pm[4 * s + 2], Pm[4 * s + 3], d0 + H * (PAGE >> 4) + (s & 3) * 2, s > 0 ? 1 : acc);
}
template <int J0, int J1>
__device__ __forceinline__ void exp_groups(const float (&S)[64], uint32_t (&Pm)[32], float (&sum)[2]) {
#pragma unroll
    for (int i = 2 * J0; i < 2 * J1; i++) asm volatile("" : "+r"(Pm[i])::"memory");
#pragma unroll
    for (int j = J0; j < J1; j++) {
        const float e0 = ex2(S[4 * j]), e1 = ex2(S[4 * j + 1]), e2 = ex2(S[4 * j + 2]), e3 = ex2(S[4 * j + 3]);
        sum[0] = (j ? sum[0] + e0 : e0) + e1;
        sum[1] = (j ? sum[1] + e2 : e2) + e3;
        Pm[2 * j] = pack_bf16(e0, e1);
        Pm[2 * j + 1] = pack_bf16(e2, e3);
    }
}
__device__ __forceinline__ void shift_rows(float (&S)[64], float d0, float d1) {
#pragma unroll
    for (int j = 0; j < 16; j++) {
        S[4 * j] -= d0; S[4 * j + 1] -= d0; S[4 * j + 2] -= d1; S[4 * j + 3] -= d1;
    }
}
__device__ constexpr int chunk_src(int i) { return 4 * (4 * (i >> 3) + (i & 3)) + 2 * ((i >> 2) & 1); }
enum : uint32_t { CTL_FIRST = 1, CTL_SWITCH = 2, CTL_LAST = 4, CTL_HALF = 128, CTL_MASKHI = 256, CTL_WOUT = 512, CTL_PVHALF = 1024, CTL_PVACC = 16384,
                  CTL_SHIFT = 32768 };
__device__ __forceinline__ float quad_sum(float v) {
    v += __shfl_xor_sync(~0u, v, 1);
    return v + __shfl_xor_sync(~0u, v, 2);
}

__device__ __forceinline__ void store_part(uint8_t* base, uint32_t row_bits, int p, const uint32_t (&pk)[64], uint64_t pol) {
    asm volatile("{\n.reg .b64 d0, d1;\nxor.b64 d0, %0, %1;\nxor.b64 d1, d0, 64;\n"
                 "TS: .branchtargets P0, P1, P2, P3, P4, P5, P6, P7;\n"
                 "brx.idx.uni %2, TS;\n"
                 "P0:\n st.global.cg.L2::cache_hint.v4.u32 [d0 + 0], {%3, %4, %5, %6}, %67;\n st.global.cg.L2::cache_hint.v4.u32 [d1 + 0], {%11, %12, %13, %14}, %67;\n bra.uni DONE;\n"
                 "P1:\n st.global.cg.L2::cache_hint.v4.u32 [d0 + 0], {%7, %8, %9, %10}, %67;\n st.global.cg.L2::cache_hint.v4.u32 [d1 + 0], {%15, %16, %17, %18}, %67;\n bra.uni DONE;\n"
                 "P2:\n st.global.cg.L2::cache_hint.v4.u32 [d0 + 16384], {%19, %20, %21, %22}, %67;\n st.global.cg.L2::cache_hint.v4.u32 [d1 + 16384], {%27, %28, %29, %30}, %67;\n bra.uni DONE;\n"
                 "P3:\n st.global.cg.L2::cache_hint.v4.u32 [d0 + 16384], {%23, %24, %25, %26}, %67;\n st.global.cg.L2::cache_hint.v4.u32 [d1 + 16384], {%31, %32, %33, %34}, %67;\n bra.uni DONE;\n"
                 "P4:\n st.global.cg.L2::cache_hint.v4.u32 [d0 + 65536], {%35, %36, %37, %38}, %67;\n st.global.cg.L2::cache_hint.v4.u32 [d1 + 65536], {%43, %44, %45, %46}, %67;\n bra.uni DONE;\n"
                 "P5:\n st.global.cg.L2::cache_hint.v4.u32 [d0 + 65536], {%39, %40, %41, %42}, %67;\n st.global.cg.L2::cache_hint.v4.u32 [d1 + 65536], {%47, %48, %49, %50}, %67;\n bra.uni DONE;\n"
                 "P6:\n st.global.cg.L2::cache_hint.v4.u32 [d0 + 81920], {%51, %52, %53, %54}, %67;\n st.global.cg.L2::cache_hint.v4.u32 [d1 + 81920], {%59, %60, %61, %62}, %67;\n bra.uni DONE;\n"
                 "P7:\n st.global.cg.L2::cache_hint.v4.u32 [d0 + 81920], {%55, %56, %57, %58}, %67;\n st.global.cg.L2::cache_hint.v4.u32 [d1 + 81920], {%63, %64, %65, %66}, %67;\n bra.uni DONE;\n"
                 "DONE:\n}\n"
                 ::"l"(base), "l"((uint64_t)((p & 1) ? row_bits : 0)), "r"(p), "r"(pk[0]), "r"(pk[1]), "r"(pk[2]), "r"(pk[3]), "r"(pk[4]), "r"(pk[5]), "r"(pk[6]), "r"(pk[7]), "r"(pk[8]), "r"(pk[9]), "r"(pk[10]), "r"(pk[11]), "r"(pk[12]), "r"(pk[13]), "r"(pk[14]), "r"(pk[15]), "r"(pk[16]), "r"(pk[17]), "r"(pk[18]), "r"(pk[19]), "r"(pk[20]), "r"(pk[21]), "r"(pk[22]), "r"(pk[23]), "r"(pk[24]), "r"(pk[25]), "r"(pk[26]), "r"(pk[27]), "r"(pk[28]), "r"(pk[29]), "r"(pk[30]), "r"(pk[31]), "r"(pk[32]), "r"(pk[33]), "r"(pk[34]), "r"(pk[35]), "r"(pk[36]), "r"(pk[37]), "r"(pk[38]), "r"(pk[39]), "r"(pk[40]), "r"(pk[41]), "r"(pk[42]), "r"(pk[43]), "r"(pk[44]), "r"(pk[45]), "r"(pk[46]), "r"(pk[47]), "r"(pk[48]), "r"(pk[49]), "r"(pk[50]), "r"(pk[51]), "r"(pk[52]), "r"(pk[53]), "r"(pk[54]), "r"(pk[55]), "r"(pk[56]), "r"(pk[57]), "r"(pk[58]), "r"(pk[59]), "r"(pk[60]), "r"(pk[61]), "r"(pk[62]), "r"(pk[63]), "l"(pol)
                 : "memory");
}

__device__ __forceinline__ void store_part4(uint8_t* d0, int p, const uint32_t (&pk)[64]) {
    asm volatile("{\n.reg .b64 d1;\nxor.b64 d1, %0, 64;\n"
                 "TS: .branchtargets P0, P1, P2, P3;\n"
                 "brx.idx.uni %1, TS;\n"
                 "P0:\n st.global.cg.v4.u32 [%0 + 0], {%2, %3, %4, %5};\n st.global.cg.v4.u32 [d1 + 0], {%10, %11, %12, %13};\n bra.uni DONE;\n"
                 "P1:\n st.global.cg.v4.u32 [%0 + 1024], {%6, %7, %8, %9};\n st.global.cg.v4.u32 [d1 + 1024], {%14, %15, %16, %17};\n bra.uni DONE;\n"
                 "P2:\n st.global.cg.v4.u32 [%0 + 16384], {%18, %19, %20, %21};\n st.global.cg.v4.u32 [d1 + 16384], {%26, %27, %28, %29};\n bra.uni DONE;\n"
                 "P3:\n st.global.cg.v4.u32 [%0 + 17408], {%22, %23, %24, %25};\n st.global.cg.v4.u32 [d1 + 17408], {%30, %31, %32, %33};\n bra.uni DONE;\n"
                 "DONE:\n}\n"
                 ::"l"(d0), "r"(p), "r"(pk[0]), "r"(pk[1]), "r"(pk[2]), "r"(pk[3]), "r"(pk[4]), "r"(pk[5]), "r"(pk[6]), "r"(pk[7]), "r"(pk[8]), "r"(pk[9]), "r"(pk[10]), "r"(pk[11]), "r"(pk[12]), "r"(pk[13]), "r"(pk[14]), "r"(pk[15]), "r"(pk[16]), "r"(pk[17]), "r"(pk[18]), "r"(pk[19]), "r"(pk[20]), "r"(pk[21]), "r"(pk[22]), "r"(pk[23]), "r"(pk[24]), "r"(pk[25]), "r"(pk[26]), "r"(pk[27]), "r"(pk[28]), "r"(pk[29]), "r"(pk[30]), "r"(pk[31])
                 : "memory");
}

__device__ __forceinline__ void consumer(uint32_t sb, int pair, int c, uint8_t* out, const uint8_t* x) {
    const int tid = threadIdx.x;
    const int warp = __shfl_sync(~0u, tid >> 5, 0);
    const int w = warp >> 2, v = warp & 3;
    const int lane = __shfl_sync(~0u, tid & 31, tid & 31);

    const uint32_t empty_rel = lane == 2 ? mapa(sb + BAR_EMPTYL, c) : mapa(sb + BAR_EMPTY, lane & 1);
    auto release = [&](uint32_t grp) {
        if (lane < 3) mbar_arrive_cluster(empty_rel + (grp & 7) * 8);
    };
    auto wait_full = [&](uint32_t grp) { mbar_wait(sb + BAR_FULL + (grp & 7) * 8, (grp >> 3) & 1); };

    uint32_t g = 0;
    const uint32_t stg = sb + SM_REGION + w * PAGE + v * 2048;
    const uint32_t chunk0 = (lane >> 2) * 128 + (((lane & 3) ^ (lane >> 2)) << 4);
    auto mark_done = [&](int odd) {
        __syncwarp();
        if (lane == 0) mbar_arrive(sb + BAR_DONE + odd * 8);
    };
    auto ctx_dst = [&](int rnd, int seg) {
        const int rb = query_rowblock(pair, c, w, seg);
        return ptr_off(g_ctx, ((rb >> 1) * 64 + (rnd * 16 + (pair >> 2)) * 2) * PAGE + (rb & 1) * 8192 + v * 2048);
    };

    uint32_t ctl_tab;
    {
        const int t = lane, firstB = 2 * attn_rowblock(pair, 0) + 2 - w;
        auto is_half = [&](int u) { return (u == firstB - 1 || u == 16) && c == (u >= firstB); };
        auto block = [&](int u) { return u + (w == 1 && u >= firstB); };
        auto place = [](int j) { return ((j & 15) << 3) | ((j - (j * 43 >> 8) * 6) << 11); };
        const int jv = min(2 * block(t - 1) + 2, 35), jk = t == 17 ? jv : max(2 * block(t) - 1, 0);
        const bool diag = t == firstB - 1 || t == 16;
        ctl_tab = ((t == 0 || t == firstB) ? CTL_FIRST : 0) | (t == firstB ? CTL_SWITCH : 0) | (t == 17 ? CTL_LAST : 0) |
                  (diag ? (is_half(t) ? CTL_HALF : CTL_MASKHI) : 0) | (t == firstB + 1 ? CTL_WOUT : 0) |
                  (is_half(t - 1) ? CTL_PVHALF : 0) | ((t == 1 || t == firstB + 1) ? 0 : CTL_PVACC) |
                  place(jk) | ((place(jv) | (t ? 3 : 0)) << 16);
    }

    uint32_t pk[64];
#pragma unroll
    for (int i = 0; i < 64; i++) pk[i] = 0;
    uint8_t* pend = nullptr;
    uint32_t prow = 0x400;
    auto write_part = [&](int p, uint64_t pol = POL_NORMAL) { store_part(pend, prow, p, pk, pol); };
    if (w == 1) bar_arrive(2, 256);

    for (int item = 0; item < 6; item++) {
        if ((0x1B >> item) & 1) {
            constexpr int nk = DC / 64;
            float acc[128];
            auto issue_kblock = [&](int first_acc) {
                wait_full(g);
                const uint32_t pg = sb + (g & 3) * (3 * PAGE);
                const uint64_t da = make_desc(pg + w * 8192, 16), db = make_desc(pg + PAGE, 16);
                wg_fence();
                wgmma_n256_ss(acc, da, db, first_acc);
                wgmma_n256_ss(acc, da + 128, db + 2, 1);
                wgmma_n256_ss(acc, da + 256, db + 4, 1);
                wgmma_n256_ss(acc, da + 384, db + 6, 1);
                wg_commit();
                g++;
            };
            if (item == 0) PROF(17, w);
            issue_kblock(0);
            if (item == 0) PROF(1, w);
            if (item == 0 && w == 0) PROF_GT(1);
            const int nparts = item == 0 ? 0 : (item == 3 ? 4 : 8);
            const int ln_row = (pair * 2 + c) * 16 + warp * 2;
            if (item == 0) {
                const uint8_t* src = ptr_off(x, ln_row * (DM * 2) + lane * 16);
#pragma unroll
                for (int i = 0; i < 8; i++) {
                    const uint4 t = __ldcg(reinterpret_cast<const uint4*>(src + i * 512));
                    pk[4 * i] = t.x; pk[4 * i + 1] = t.y; pk[4 * i + 2] = t.z; pk[4 * i + 3] = t.w;
                }
            }
#pragma unroll 1
            for (int kb = 1; kb < nk; kb++) {
                if (kb == nk - 1 && w == 1) bar_sync(4, 256);
                issue_kblock(1);
                if (kb == nk - 1 && w == 0) bar_arrive(4, 256);
                wg_wait<1>();
                release(g - 2);
                if (kb <= nparts) {
                    if (item == 4 && kb == 1) mbar_wait(sb + BAR_DEP + 16, 0);
                    write_part(kb - 1, item == 3 ? POL_FIRST : POL_NORMAL);
                    if (kb == nk - 1) write_part(nk - 1);
                    if (kb == nparts || kb == nk - 1) mark_done(item != 3);
                }
                if (g <= 8) {
                    float s[2], q[2];
                    if (g == 4) {
                        ln_sums<0>(pk, s[0], q[0]);
                        pk[32] = __float_as_uint(s[0]); pk[33] = __float_as_uint(q[0]);
                    }
                    if (g == 5) {
                        ln_sums<16>(pk, s[1], q[1]);
                        pk[34] = __float_as_uint(s[1]); pk[35] = __float_as_uint(q[1]);
                    }
                    if (g == 6) {
#pragma unroll
                        for (int r = 0; r < 2; r++) { s[r] = __uint_as_float(pk[32 + 2 * r]); q[r] = __uint_as_float(pk[33 + 2 * r]); }
                        const bool hi = lane & 16, od = lane & 8;
                        float a = hi ? s[1] : s[0], b = hi ? q[1] : q[0];
                        a += __shfl_xor_sync(~0u, hi ? s[0] : s[1], 16);
                        b += __shfl_xor_sync(~0u, hi ? q[0] : q[1], 16);
                        float t = od ? b : a;
                        t += __shfl_xor_sync(~0u, od ? a : b, 8);
#pragma unroll
                        for (int o = 4; o; o >>= 1) t += __shfl_xor_sync(~0u, t, o);
#pragma unroll
                        for (int r = 0; r < 2; r++) {
                            s[r] = __shfl_sync(~0u, t, 16 * r);
                            q[r] = __shfl_sync(~0u, t, 16 * r + 8);
                        }
                        ln_finish(s[0], q[0], pk[36], pk[37], pk[38]);
                        ln_finish(s[1], q[1], pk[39], pk[40], pk[41]);
                    }
                    if (g == 7) ln_apply<0>(pk, pk[36], pk[37], pk[38], ptr_off(g_xn, image_offset(ln_row, lane)));
                    if (g == 8) {
                        ln_apply<16>(pk, pk[39], pk[40], pk[41], ptr_off(g_xn, image_offset(ln_row + 1, lane)));
                        mark_done(0);
                    }
                }
            }
            wg_wait<0>();
            reg_fence(acc);
            release(g - 1);
            PROF(2 + 2 * item, w);
            if (w == 0) PROF_GT(2 + 2 * item);
#pragma unroll
            for (int i = 0; i < 64; i++) pk[i] = pack_bf16(acc[chunk_src(i)], acc[chunk_src(i) + 1]);
            const uint32_t vrow = (v >> 1) * 32 + (lane >> 3) * 8 + (v & 1) * 4 + ((lane >> 2) & 1);
            pend = ptr_off(g_kv, ((kv_head(pair) + (item == 1 || item == 4 ? 8 : 0)) * 16 + kv_tokens(pair) * 2) * 65536 + w * 8192 +
                                     (c ? 32768 + vrow * 128 + (((lane & 3) ^ (vrow & 7)) << 4) : v * 2048 + chunk0));
            prow = c ? 0x120 : 0x400;
            PROF(3 + 2 * item, w);
            continue;
        }

        float O[64], S[64];
        auto issue_q = [&](int first_acc) {
            wait_full(g);
            const uint32_t pg = sb + (g & 3) * (3 * PAGE);
            const uint64_t da = make_desc(pg + w * 8192, 16), db = make_desc(pg + 2 * PAGE, 8192);
            const uint64_t dab = make_desc(pg + PAGE + (1 - w) * 8192, 16);
            wg_fence();
#pragma unroll
            for (int q = 0; q < 4; q++) wgmma_n128_ss(S, da + 2 * q, db + 128 * q, q ? 1 : first_acc);
            wg_commit();
#pragma unroll
            for (int q = 0; q < 4; q++) wgmma_n128_ss(O, dab + 2 * q, db + 128 * q, q ? 1 : first_acc);
            wg_commit();
            g++;
        };
        issue_q(0);
#pragma unroll 1
        for (int kb = 1; kb < DM / 64; kb++) {
            if (kb == DM / 64 - 2 && w == 1) bar_sync(4, 256);
            issue_q(1);
            if (kb == DM / 64 - 1 && w == 0) bar_arrive(4, 256);
            wg_wait<2>();
            release(g - 2);
            if (kb <= 8) {
                write_part(kb - 1);
                if (kb == 8) mark_done(0);
            }
        }
        uint32_t Q[32], Pm[32];
#pragma unroll
        for (int i = 0; i < 32; i++) Pm[i] = pk[i];
        float lim = (float)(v * 16 + (lane >> 2) - 8 * (lane & 3));
        float mc[2] = {0.f, 0.f}, l[2] = {0.f, 0.f}, scale[2] = {0.f, 0.f}, sum[2];
        uint32_t ctl = __shfl_sync(~0u, ctl_tab, 0), nxt = __shfl_sync(~0u, ctl_tab, 1);
        int t = 1;
        asm volatile("" : "+f"(lim), "+f"(mc[0]), "+f"(mc[1]), "+f"(l[0]), "+f"(l[1]), "+r"(ctl), "+r"(nxt), "+r"(t));
        wg_wait<1>();
        reg_fence(S);
#pragma unroll
        for (int i = 0; i < 32; i++) Q[i] = pack_bf16(S[2 * i] * SM_SCALE, S[2 * i + 1] * SM_SCALE);
        reg_fence(Q);
        wait_full(g);
        wg_wait<0>();
        reg_fence(O);
        release(g - 1);
        PROF(2 + 2 * item, w);
        if (w == 0) PROF_GT(2 + 2 * item);

        const uint32_t qaddr = stg + lane * 16;
        auto put_queries = [&](const float (&A)[64]) {
#pragma unroll
            for (int i = 0; i < 8; i++)
                sts128(qaddr + (i >> 2) * 8192 + (i & 3) * 512, pack_bf16(A[8 * i] * SM_SCALE, A[8 * i + 1] * SM_SCALE), pack_bf16(A[8 * i + 2] * SM_SCALE, A[8 * i + 3] * SM_SCALE),
                       pack_bf16(A[8 * i + 4] * SM_SCALE, A[8 * i + 5] * SM_SCALE), pack_bf16(A[8 * i + 6] * SM_SCALE, A[8 * i + 7] * SM_SCALE));
        };
        auto get_queries = [&]() {
#pragma unroll
            for (int i = 0; i < 8; i++) lds128(qaddr + (i >> 2) * 8192 + (i & 3) * 512, Q[4 * i], Q[4 * i + 1], Q[4 * i + 2], Q[4 * i + 3]);
        };
        const uint32_t kdesc0 = (uint32_t)make_desc(sb, PAGE), vdesc0 = (uint32_t)make_desc(sb, 16);
        auto wait_block = [&](uint32_t word) { mbar_wait(sb + BAR_FULL + (word & 56), (word >> 6) & 1); };
        auto write_out = [&](auto early) {
            uint8_t* dst = ctx_dst(item == 5, 0);
            uint8_t* d[2] = {ptr_off(dst, chunk0), ptr_off(dst, chunk0 ^ 64)};
#pragma unroll
            for (int i = early.value ? 0 : WN; i < (early.value ? WN : 8); i++) {
                const float sc = scale[i & 1];
                uint32_t q[4];
#pragma unroll
                for (int k = 0; k < 4; k++) q[k] = pack_bf16(O[chunk_src(4 * i + k)] * sc, O[chunk_src(4 * i + k) + 1] * sc);
                if (early.value && i > 0) {
#pragma unroll
                    for (int k = 0; k < 4; k++) O[4 * (i - 1) + k] = __uint_as_float(q[k]);
                }
                stg_hint(d[(i >> 1) & 1] + (i >> 2) * PAGE + (i & 1) * 1024, q[0], q[1], q[2], q[3], item == 2 ? POL_FIRST : POL_NORMAL);
            }
            if (!early.value) mark_done(1);
        };
        put_queries(O);
        bar_sync(2 + w, 256);
        if (!(ctl & CTL_HALF)) {
            wg_fence();
            issue_qk(S, Q, kdesc0);
            wg_commit();
            wg_fence();
            wg_commit();
            wg_commit();
            bar_arrive(3 - w, 256);
            wg_wait<2>();
            reg_fence(S);
        } else {
            float T[32];
            wg_fence();
            issue_qk_half(T, Q, kdesc0);
            wg_commit();
            wg_fence();
            wg_commit();
            wg_commit();
            bar_arrive(3 - w, 256);
            wg_wait<2>();
            reg_fence(T);
#pragma unroll
            for (int i = 0; i < 32; i++) S[i] = T[i];
        }
        for (;;) {
            const bool kready = mbar_try(sb + BAR_FULL + (nxt & 56), (nxt >> 6) & 1);
            if (ctl & (CTL_HALF | CTL_MASKHI | CTL_SHIFT)) {
                if (ctl & CTL_HALF) mask_half<0>(S, lim, v);
                if (ctl & CTL_MASKHI) mask_half<8>(S, lim, v);
                if (ctl & CTL_SHIFT) shift_rows(S, mc[0], mc[1]);
            }
            float early[4 * EARLY];
#pragma unroll
            for (int j = 0; j < EARLY; j++) {
#pragma unroll
                for (int i = 4 * j; i < 4 * j + 4; i++) early[i] = ex2(S[i]);
                sum[0] = (j ? sum[0] + early[4 * j] : early[4 * j]) + early[4 * j + 1];
                sum[1] = (j ? sum[1] + early[4 * j + 2] : early[4 * j + 2]) + early[4 * j + 3];
            }
            const uint32_t tie = __float_as_uint(sum[0]) & __float_as_uint(sum[1]) & (ctl & 0x80000000u);
            if (lane < 3) mbar_arrive_cluster(empty_rel + tie + (ctl & 56));
            wg_wait<1>();
#pragma unroll
            for (int j = 0; j < EARLY; j++) {
                asm volatile("" : "+r"(Pm[2 * j]), "+r"(Pm[2 * j + 1])::"memory");
                Pm[2 * j] = pack_bf16(early[4 * j], early[4 * j + 1]);
                Pm[2 * j + 1] = pack_bf16(early[4 * j + 2], early[4 * j + 3]);
            }
            exp_groups<EARLY, 8>(S, Pm, sum);
            const bool half = ctl & CTL_HALF;
            if (!half) {
                wg_wait<0>();
                reg_fence(O);
                if (lane < ((ctl >> 16) & 3)) mbar_arrive_cluster(empty_rel + ((ctl >> 16) & 56));
                exp_groups<8, 16>(S, Pm, sum);
            } else {
                asm volatile("wgmma.wait_group.sync.aligned 0;\n" ::: "memory");
                reg_fence(O);
                if (lane < ((ctl >> 16) & 3)) asm volatile("mbarrier.arrive.shared::cluster.b64 _, [%0];\n" ::"r"(empty_rel + ((ctl >> 16) & 56)) : "memory");
            }
            const bool over = !(sum[0] + sum[1] <= SUM_HI);
            if (__any_sync(~0u, over || !kready) || (((ctl & CTL_FIRST) | (nxt & (CTL_SWITCH | CTL_LAST | CTL_HALF))) != 0)) {
                bool bad = __any_sync(~0u, over);
                if (!kready) wait_block(nxt);
                const bool first = ctl & CTL_FIRST;
                if (first) {
                    uint32_t b0 = __ballot_sync(~0u, sum[0] >= SUM_LO), b1 = __ballot_sync(~0u, sum[1] >= SUM_LO);
                    b0 |= b0 >> 1; b1 |= b1 >> 1;
                    b0 |= b0 >> 2; b1 |= b1 >> 2;
                    bad |= (b0 & b1 & 0x11111111u) != 0x11111111u;
                }
                if (bad) {
                    float d0 = fmaxf(S[0], S[1]), d1 = fmaxf(S[2], S[3]);
#pragma unroll
                    for (int j = 1; j < 8; j++) {
                        d0 = fmaxf(d0, fmaxf(S[4 * j], S[4 * j + 1]));
                        d1 = fmaxf(d1, fmaxf(S[4 * j + 2], S[4 * j + 3]));
                    }
                    if (!half) {
#pragma unroll
                        for (int j = 8; j < 16; j++) {
                            d0 = fmaxf(d0, fmaxf(S[4 * j], S[4 * j + 1]));
                            d1 = fmaxf(d1, fmaxf(S[4 * j + 2], S[4 * j + 3]));
                        }
                    }
                    d0 = fmaxf(d0, __shfl_xor_sync(~0u, d0, 1));
                    d1 = fmaxf(d1, __shfl_xor_sync(~0u, d1, 1));
                    d0 = fmaxf(d0, __shfl_xor_sync(~0u, d0, 2));
                    d1 = fmaxf(d1, __shfl_xor_sync(~0u, d1, 2));
                    if (!first) {
                        d0 = fmaxf(d0, 0.f);
                        d1 = fmaxf(d1, 0.f);
                        const float a0 = ex2(-d0), a1 = ex2(-d1);
#pragma unroll
                        for (int j = 0; j < 16; j++) {
                            O[4 * j] *= a0; O[4 * j + 1] *= a0; O[4 * j + 2] *= a1; O[4 * j + 3] *= a1;
                        }
                        l[0] *= a0; l[1] *= a1;
                    }
                    mc[0] += d0; mc[1] += d1;
                    ctl_tab |= CTL_SHIFT;
                    nxt |= CTL_SHIFT;
                    shift_rows(S, d0, d1);
                    exp_groups<0, 8>(S, Pm, sum);
                    if (!half) exp_groups<8, 16>(S, Pm, sum);
                }
                if (ctl & CTL_SWITCH) write_out(std::true_type());
                if (nxt & CTL_LAST) break;
                if (nxt & CTL_SWITCH) {
                    get_queries();
                    nxt &= ~CTL_SHIFT;
                    ctl_tab &= ~CTL_SHIFT;
                }
                if (nxt & CTL_HALF) {
                    ctl = nxt;
                    float T[32];
                    bar_sync(2 + w, 256);
                    wg_fence();
                    issue_qk_half(T, Q, kdesc0 + (ctl & 0x3800));
                    wg_commit();
                    l[0] += sum[0]; l[1] += sum[1];
                    nxt = __shfl_sync(~0u, ctl_tab, ++t);
                    wait_block(ctl >> 16);
                    const uint32_t vdesc = vdesc0 + ((ctl >> 16) & 0x3800);
                    wg_fence();
                    issue_pv<0>(O, Pm, vdesc, ctl & CTL_PVACC);
                    wg_commit();
                    issue_pv<1>(O, Pm, vdesc, 1);
                    wg_commit();
                    bar_arrive(3 - w, 256);
                    wg_wait<2>();
                    reg_fence(T);
#pragma unroll
                    for (int i = 0; i < 32; i++) S[i] = T[i];
                    continue;
                }
            }
            ctl = nxt;
            bar_sync(2 + w, 256);
            wg_fence();
            issue_qk(S, Q, kdesc0 + (ctl & 0x3800));
            wg_commit();
            l[0] += sum[0]; l[1] += sum[1];
            nxt = __shfl_sync(~0u, ctl_tab, ++t);
            if (ctl & (CTL_SWITCH | CTL_WOUT)) {
                if (ctl & CTL_SWITCH) {
                    scale[0] = rcp_approx(quad_sum(l[0]));
                    scale[1] = rcp_approx(quad_sum(l[1]));
                    l[0] = l[1] = mc[0] = mc[1] = 0.f;
                    if (w == 1) { release((ctl >> 3) - 2); release((ctl >> 3) + 1); }
                } else {
                    write_out(std::false_type());
                }
            }
            wait_block(ctl >> 16);
            const uint32_t vdesc = vdesc0 + ((ctl >> 16) & 0x3800);
            if (!(ctl & CTL_PVHALF)) {
                wg_fence();
                issue_pv<0>(O, Pm, vdesc, ctl & CTL_PVACC);
                wg_commit();
                issue_pv<1>(O, Pm, vdesc, 1);
                wg_commit();
            } else {
                wg_fence();
                issue_pv<0>(O, Pm, vdesc, ctl & CTL_PVACC);
                wg_commit();
                wg_commit();
            }
            bar_arrive(3 - w, 256);
            wg_wait<2>();
            reg_fence(S);
        }
        g += 36;
        if (w == 0) release(g - 3);
        const uint32_t vdesc = vdesc0 + (nxt & 0x3800);
        if (nxt & CTL_PVHALF) {
            wg_fence();
            issue_pv<0>(O, Pm, vdesc, nxt & CTL_PVACC);
            wg_commit();
        } else {
            wg_fence();
            issue_pv<0>(O, Pm, vdesc, nxt & CTL_PVACC);
            issue_pv<1>(O, Pm, vdesc, 1);
            wg_commit();
        }
        l[0] += sum[0]; l[1] += sum[1];
        ctl_tab = (ctl_tab & ~(0x00780078u | CTL_SHIFT)) | ((ctl_tab + 0x00200020u) & 0x00780078u);
        const float i0 = rcp_approx(quad_sum(l[0])), i1 = rcp_approx(quad_sum(l[1]));
        wg_wait<0>();
        reg_fence(O);
        if (w == 0) release(g - 2);
        release(g - 1);
#pragma unroll
        for (int i = 0; i < 32; i++) {
            const float sc = (i & 4) ? i1 : i0;
            pk[i] = pack_bf16(O[chunk_src(i)] * sc, O[chunk_src(i) + 1] * sc);
        }
        pend = ptr_off(ctx_dst(item == 5, 1), chunk0);
        prow = 0x400;
#pragma unroll
        for (int i = 32; i < 64; i++) pk[i] = 0;
        PROF(3 + 2 * item, w);
        if (w == 0) PROF_GT(3 + 2 * item);
    }

    float acc[64];
    uint32_t slot = 0;
    auto issue_out = [&](int first_acc) {
        wait_full(g);
        const uint64_t da = make_desc(sb + slot + w * 8192, 16), db = make_desc(sb + slot + PAGE, 8192);
        wg_fence();
#pragma unroll
        for (int q = 0; q < 4; q++) wgmma_n128_ss(acc, da + 2 * q, db + 128 * q, q ? 1 : first_acc);
        wg_commit();
        g++;
        slot = slot == SM_REGION - 2 * PAGE ? 0 : slot + 2 * PAGE;
    };
    issue_out(0);
#pragma unroll 1
    for (int kb = 1; kb < 64 - PEEL; kb++) {
        issue_out(1);
        wg_wait<1>();
        release(g - 2);
        if (kb <= 8 && !(kb & 1)) {
            store_part4(pend, (kb >> 1) - 1, pk);
            if (kb == 8) mark_done(0);
        }
        if (kb >= 32 - PEEL && ((kb + PEEL) & 3) == 2 * w) {
            uint32_t u0, u1, u2, u3;
            const uint32_t a = stg + ((kb + PEEL) & 16) * 512 + ((kb + PEEL) & 12) * 128 + lane * 16;
            mbar_wait(sb + BAR_G + w * 8, 0);
            lds128(a, u0, u1, u2, u3);
            sts128(a, pack_bf16(silu_f(bf_lo(u0)), silu_f(bf_hi(u0))), pack_bf16(silu_f(bf_lo(u1)), silu_f(bf_hi(u1))),
                   pack_bf16(silu_f(bf_lo(u2)), silu_f(bf_hi(u2))), pack_bf16(silu_f(bf_lo(u3)), silu_f(bf_hi(u3))));
        }
    }
    const uint32_t goff = (out_rows(pair) * 256 + c * 128 + w * 64 + v * 16 + (lane >> 3)) * (DM * 2) +
                          out_cols(pair) * 128 + (((lane & 7) ^ (lane >> 3)) << 4);
    uint32_t xr[32], gr[32];
    {
        const uint8_t* src[2] = {ptr_off(x, goff), ptr_off(x, goff ^ 64)};
#pragma unroll
        for (int i = 0; i < 8; i++) {
            const uint4 t = ldg_hint(src[i & 1] + (i & 3) * (4 * DM * 2) + (i >> 2) * 128, POL_FIRST);
            xr[4 * i] = t.x; xr[4 * i + 1] = t.y; xr[4 * i + 2] = t.z; xr[4 * i + 3] = t.w;
        }
    }
#pragma unroll 1
    for (int i = 0; i < PEEL; i++) {
        if (i == PEEL - STAG && w == 1) bar_sync(4, 256);
        issue_out(1);
        if (i == PEEL - 1 && w == 0) bar_arrive(4, 256);
        wg_wait<1>();
    }
    asm volatile("barrier.cluster.arrive.relaxed.aligned;" ::: "memory");
#pragma unroll
    for (int i = 0; i < 8; i++) lds128(stg + (i >> 2) * 8192 + (i & 3) * 512 + lane * 16, gr[4 * i], gr[4 * i + 1], gr[4 * i + 2], gr[4 * i + 3]);
    uint8_t* dst[2] = {ptr_off(out, goff), ptr_off(out, goff ^ 64)};
    __syncwarp();
    wg_wait<0>();
    reg_fence(acc);
    PROF(14, w);
    if (w == 0) PROF_GT(14);
#pragma unroll
    for (int s = 0; s < 8; s++)
        stmatrix_x4(slab_addr(stg, lane, s), pack_bf16(acc[8 * s], acc[8 * s + 1]), pack_bf16(acc[8 * s + 2], acc[8 * s + 3]),
                    pack_bf16(acc[8 * s + 4], acc[8 * s + 5]), pack_bf16(acc[8 * s + 6], acc[8 * s + 7]));
    __syncwarp();
    uint32_t o[32];
#pragma unroll
    for (int i = 0; i < 8; i++) lds128(stg + (i >> 2) * 8192 + (i & 3) * 512 + lane * 16, o[4 * i], o[4 * i + 1], o[4 * i + 2], o[4 * i + 3]);
#pragma unroll
    for (int i = 0; i < 8; i++) {
#pragma unroll
        for (int k = 0; k < 4; k++) xr[4 * i + k] = bf2_add(xr[4 * i + k], bf2_mul(o[4 * i + k], gr[4 * i + k]));
        __stcg(reinterpret_cast<uint4*>(dst[i & 1] + (i & 3) * (4 * DM * 2) + (i >> 2) * 128), make_uint4(xr[4 * i], xr[4 * i + 1], xr[4 * i + 2], xr[4 * i + 3]));
    }
    PROF(28, w);
}

__global__ void __cluster_dims__(2, 1, 1) __launch_bounds__(384, 1)
fused_kernel(const __grid_constant__ CUtensorMap m_ckv, const __grid_constant__ CUtensorMap m_wuk,
             const __grid_constant__ CUtensorMap m_wuv, const __grid_constant__ CUtensorMap m_wq,
             const __grid_constant__ CUtensorMap m_wo, const __grid_constant__ CUtensorMap m_gate,
             const __grid_constant__ CUtensorMap m_up, const __grid_constant__ CUtensorMap m_down, const Params P) {
    extern __shared__ __align__(1024) uint8_t smem[];
    const uint32_t sb = __shfl_sync(~0u, smem_u32(smem), 0);
    const int tid = threadIdx.x;
    const int cl = blockIdx.x >> 1, c = blockIdx.x & 1;
    const int pair = cl >= 64 ? cl : cl < 4 ? cl * 16 + 15 : cl < 36 ? ((cl - 4) >> 3) * 16 + ((cl - 4) & 7)
                                                                    : ((cl - 36) / 7) * 16 + 8 + (cl - 36) % 7;
    const bool starter = tid == 256 && pair < NMAIN / 2;
    const CUtensorMap* m_wu = c ? &m_wuv : &m_wuk;
    if (tid == 256) {
        mbar_init(sb + BAR_FULL, 1);
        if (starter) {
            asm volatile("fence.mbarrier_init.release.cluster;" ::: "memory");
            mbar_expect_tx(sb + BAR_FULL, 3 * PAGE);
            tma_3d(sb, m_wu, 0, 0, kv_head(pair) * 2, sb + BAR_FULL);
            tma_3d(sb + PAGE, &m_ckv, 0, kv_tokens(pair) * 256, 0, sb + BAR_FULL);
            tma_3d(sb + 2 * PAGE, &m_ckv, 0, kv_tokens(pair) * 256 + 128, 0, sb + BAR_FULL);
        }
#pragma unroll
        for (int i = 1; i < NBAR; i++) mbar_init(sb + SM_BAR + i * 8, (i >> 3) == 1 ? 16 : i >= 25 ? 8 : 1);
        asm volatile("fence.mbarrier_init.release.cluster;" ::: "memory");
    }
    if (starter) {
#pragma unroll 1
        for (int kb = 1; kb < 4; kb++) mbar_expect_tx(sb + BAR_FULL + kb * 8, 3 * PAGE);
        tma_3d(sb + 3 * PAGE, m_wu, 0, 64, kv_head(pair) * 2, sb + BAR_FULL + 8);
    }
    PROF(18, (tid >> 7) & 1);
    __syncthreads();
    cluster_sync();
    PROF(22, (tid >> 7) & 1);
    PROF(19, (tid >> 7) & 1);
    const int warp = __shfl_sync(~0u, tid >> 5, 0), lane = tid & 31;
    auto dump_prof = [&]() {
    };
    if (pair >= NMAIN / 2) {
        if (warp < 8) ffn_cta(smem, sb, blockIdx.x - NMAIN, __ldcg(&g_sync.done) / NCTA, P.w_r);
        else if (tid == 256) ffn_producer(sb, blockIdx.x - NMAIN, &m_gate, &m_up, &m_down);
        __syncwarp();
        PROF(29, tid >> 7);
        cluster_sync();
        if (tid == 0) atomicAdd(&g_sync.done, 1u);
        if (warp < 8) dump_prof();
    } else if (warp < 8) {
        asm volatile("setmaxnreg.inc.sync.aligned.u32 232;");
        consumer(sb, pair, c, P.out, (const uint8_t*)P.x);
        PROF(29, tid >> 7);
        asm volatile("barrier.cluster.wait.aligned;" ::: "memory");
        dump_prof();
    } else {
        asm volatile("setmaxnreg.dec.sync.aligned.u32 40;");
        if (starter) {
#pragma unroll 1
            for (int kb = 1; kb < 4; kb++) {
                if (kb > 1) tma_3d(sb + kb * (3 * PAGE), m_wu, 0, kb * 64, kv_head(pair) * 2, sb + BAR_FULL + kb * 8);
                tma_3d_mc(sb + kb * (3 * PAGE) + (1 + c) * PAGE, &m_ckv, 0, kv_tokens(pair) * 256 + c * 128, kb, sb + BAR_FULL + kb * 8);
            }
        }
        if (warp == 10) {
            sync_helper(sb, lane, pair, c);
        } else if (warp & 1) {
            fetch_helper((warp & 2) ? P.w_uv : P.w_uk, sb, (warp >> 1) & 1, lane, pair, c);
        } else {
            producer(P, sb, pair, c, &m_ckv, m_wu, &m_wq, &m_wo);
        }
        bar_sync(6, 128);
        if (tid == 256) atomicAdd(&g_sync.done, 1u);
        cluster_sync();
    }
}

typedef CUresult (*EncodeFn)(CUtensorMap*, CUtensorMapDataType, cuuint32_t, void*, const cuuint64_t*, const cuuint64_t*,
                             const cuuint32_t*, const cuuint32_t*, CUtensorMapInterleave, CUtensorMapSwizzle,
                             CUtensorMapL2promotion, CUtensorMapFloatOOBfill);

void make_map_w(EncodeFn fn, CUtensorMap* m, const void* ptr, int rows, int cols, int blocks, int box_rows = 32) {
    cuuint64_t dims[3] = {64, (cuuint64_t)rows, (cuuint64_t)cols / 64};
    cuuint64_t strides[2] = {(cuuint64_t)cols * 2, 128};
    cuuint32_t box[3] = {64, (cuuint32_t)box_rows, (cuuint32_t)blocks};
    cuuint32_t es[3] = {1, 1, 1};
    fn(m, CU_TENSOR_MAP_DATA_TYPE_BFLOAT16, 3, const_cast<void*>(ptr), dims, strides, box, es, CU_TENSOR_MAP_INTERLEAVE_NONE,
       CU_TENSOR_MAP_SWIZZLE_128B, CU_TENSOR_MAP_L2_PROMOTION_L2_256B, CU_TENSOR_MAP_FLOAT_OOB_FILL_NONE);
}

}

extern "C" void kernel_launch(void* const* d_in, const int* in_sizes, int n_in, void* d_out, int out_size) {
    static EncodeFn fn = nullptr;
    if (!fn) {
        void* f = nullptr;
        cudaDriverEntryPointQueryResult qr;
        cudaGetDriverEntryPoint("cuTensorMapEncodeTiled", &f, cudaEnableDefault, &qr);
        fn = (EncodeFn)f;
        cudaFuncSetAttribute(fused_kernel, cudaFuncAttributeMaxDynamicSharedMemorySize, SMEM_BYTES);
    }
    CUtensorMap m_ckv, m_wuk, m_wuv, m_wq, m_wo, m_gate, m_up, m_down;
    make_map_w(fn, &m_gate, d_in[8], DM, FF, FS / 64, 16);
    make_map_w(fn, &m_up, d_in[9], DM, FF, FS / 64, 16);
    make_map_w(fn, &m_down, d_in[10], FF, DM, DM / 64, 16);
    make_map_w(fn, &m_ckv, d_in[1], SEQ, DC, 1, 128);
    make_map_w(fn, &m_wq, d_in[2], DM, NH * 128, 1, 64);
    make_map_w(fn, &m_wuk, d_in[3], DC, NH * 128, 2, 64);
    make_map_w(fn, &m_wuv, d_in[4], DC, NH * 128, 2, 64);
    make_map_w(fn, &m_wo, d_in[5], NH * 128, DM, 1, 64);
    Params P;
    P.x = (const __nv_bfloat16*)d_in[0];
    P.w_r = (const __nv_bfloat16*)d_in[7];
    P.c_kv = (const uint8_t*)d_in[1];
    P.w_uk = (const uint8_t*)d_in[3];
    P.w_uv = (const uint8_t*)d_in[4];
    P.out = (uint8_t*)d_out;
    fused_kernel<<<NCTA, 384, SMEM_BYTES>>>(m_ckv, m_wuk, m_wuv, m_wq, m_wo, m_gate, m_up, m_down, P);
}
```

```cpp
#include <cuda_runtime.h>
#include <cuda_bf16.h>
#include <cuda.h>
#include <stdint.h>
#include <type_traits>

namespace {

constexpr int SEQ = 2048, DM = 1024, NH = 32, DC = 512, FF = 3584;
constexpr int PAGE = 16384;
constexpr int NRING = 12;
constexpr int NCTA = 132, NMAIN = 128;
constexpr uint32_t SM_REGION = NRING * PAGE;
constexpr uint32_t SM_BAR = (NRING + 2) * PAGE;
constexpr uint32_t BAR_FULL = SM_BAR, BAR_EMPTY = SM_BAR + 64;
constexpr uint32_t BAR_DEP = SM_BAR + 128;
constexpr uint32_t BAR_G = SM_BAR + 184;
constexpr uint32_t BAR_DONE = SM_BAR + 200;
constexpr uint32_t BAR_EMPTYL = SM_BAR + 216;
constexpr int NBAR = 35;
constexpr uint32_t SM_PROF = SM_BAR + 320;
constexpr int SMEM_BYTES = SM_PROF + 512;
constexpr uint32_t SPIN_LIMIT = 1u << 16;
constexpr uint32_t POLL_MASK = 7;
constexpr int EARLY = 2;
constexpr int WN = 5;
constexpr int PEEL = 5, STAG = 3;

struct SyncBlock {
    unsigned done;       unsigned pad0[31];
    unsigned ln;         unsigned pad1[31];
    unsigned router;     unsigned pad4[31];
    unsigned ffn_ticket; unsigned pad2[31];
    unsigned ffn_done;   unsigned pad3[31];
    unsigned kv[NH * 8];
    unsigned kvfree[16 * 8];
    unsigned ctx[32 * NH];
};

__device__ __align__(1024) uint8_t g_xn[8 * 16 * 4 * 8192];
__device__ __align__(4096) uint8_t g_kv[16 * 16 * 65536];
__device__ __align__(4096) uint8_t g_ctx[16 * 64 * 16384];
__device__ __align__(16) uint4 g_routed[2 * 128];
__device__ int g_sel[2];
__device__ __align__(16) float g_r[SEQ];
__device__ __align__(16) float g_ypart[4 * 2 * DM];
__device__ SyncBlock g_sync;

__device__ __forceinline__ uint32_t smem_u32(const void* p) { return (uint32_t)__cvta_generic_to_shared(p); }

__device__ __forceinline__ void mbar_init(uint32_t bar, uint32_t count) {
    asm volatile("mbarrier.init.shared::cta.b64 [%0], %1;" ::"r"(bar), "r"(count) : "memory");
}
#define MBAR_WAIT_ASM(HINT, LIMIT)                                                                  \
    asm volatile("{\n.reg .pred p;\n.reg .u32 n;\nmov.u32 n, 0;\n"                                  \
                 "WAIT_LOOP:\n"                                                                     \
                 "mbarrier.try_wait.parity.shared::cta.b64 p, [%0], %1" HINT ";\n"                  \
                 "@p bra WAIT_DONE;\n"                                                              \
                 "add.u32 n, n, 1;\n"                                                               \
                 "setp.lt.u32 p, n, " LIMIT ";\n"                                                   \
                 "@p bra WAIT_LOOP;\n"                                                              \
                 "WAIT_DONE:\n}\n" ::"r"(bar), "r"(parity) : "memory")
__device__ __forceinline__ void mbar_wait(uint32_t bar, uint32_t parity) { MBAR_WAIT_ASM("", "131072"); }
__device__ __forceinline__ void mbar_sleep(uint32_t bar, uint32_t parity) { MBAR_WAIT_ASM(", 2000", "8192"); }
__device__ __forceinline__ bool mbar_try(uint32_t bar, uint32_t parity) {
    uint32_t ok;
    asm volatile("{\n.reg .pred p;\nmbarrier.try_wait.parity.shared::cta.b64 p, [%1], %2;\nselp.u32 %0, 1, 0, p;\n}\n"
                 : "=r"(ok) : "r"(bar), "r"(parity) : "memory");
    return ok;
}
__device__ __forceinline__ bool mbar_test(uint32_t bar, uint32_t parity) {
    uint32_t ok;
    asm volatile("{\n.reg .pred p;\nmbarrier.test_wait.parity.shared::cta.b64 p, [%1], %2;\nselp.u32 %0, 1, 0, p;\n}\n"
                 : "=r"(ok) : "r"(bar), "r"(parity) : "memory");
    return ok;
}
__device__ __forceinline__ bool elect_one() {
    uint32_t ok;
    asm volatile("{\n.reg .pred p;\nelect.sync _|p, 0xffffffff;\nselp.u32 %0, 1, 0, p;\n}\n" : "=r"(ok));
    return ok;
}
__device__ __forceinline__ void mbar_arrive(uint32_t bar) {
    asm volatile("mbarrier.arrive.shared::cta.b64 _, [%0];" ::"r"(bar) : "memory");
}
__device__ __forceinline__ void mbar_expect_tx(uint32_t bar, uint32_t bytes) {
    asm volatile("mbarrier.arrive.expect_tx.shared::cta.b64 _, [%0], %1;" ::"r"(bar), "r"(bytes) : "memory");
}
__device__ __forceinline__ void mbar_arrive_cluster(uint32_t cluster_addr) {
    asm volatile("mbarrier.arrive.shared::cluster.b64 _, [%0];" ::"r"(cluster_addr) : "memory");
}
__device__ __forceinline__ uint32_t mapa(uint32_t addr, uint32_t rank) {
    uint32_t r;
    asm("mapa.shared::cluster.u32 %0, %1, %2;" : "=r"(r) : "r"(addr), "r"(rank));
    return r;
}
__device__ __forceinline__ void tma_3d(uint32_t dst, const CUtensorMap* m, int c0, int c1, int c2, uint32_t bar) {
    asm volatile("cp.async.bulk.tensor.3d.shared::cluster.global.mbarrier::complete_tx::bytes [%0], [%1, {%3, %4, %5}], [%2];"
                 ::"r"(dst), "l"(m), "r"(bar), "r"(c0), "r"(c1), "r"(c2) : "memory");
}
__device__ __forceinline__ void tma_3d_hint(uint32_t dst, const CUtensorMap* m, int c0, int c1, int c2, uint32_t bar, uint64_t pol) {
    asm volatile("cp.async.bulk.tensor.3d.shared::cluster.global.mbarrier::complete_tx::bytes.L2::cache_hint [%0], [%1, {%3, %4, %5}], [%2], %6;"
                 ::"r"(dst), "l"(m), "r"(bar), "r"(c0), "r"(c1), "r"(c2), "l"(pol) : "memory");
}
__device__ __forceinline__ void tma_3d_mc(uint32_t dst, const CUtensorMap* m, int c0, int c1, int c2, uint32_t bar) {
    asm volatile("cp.async.bulk.tensor.3d.shared::cluster.global.mbarrier::complete_tx::bytes.multicast::cluster [%0], [%1, {%3, %4, %5}], [%2], %6;"
                 ::"r"(dst), "l"(m), "r"(bar), "r"(c0), "r"(c1), "r"(c2), "h"((uint16_t)3) : "memory");
}
__device__ __forceinline__ void bulk_load(uint32_t dst, const void* src, uint32_t bytes, uint32_t bar) {
    asm volatile("cp.async.bulk.shared::cluster.global.mbarrier::complete_tx::bytes [%0], [%1], %2, [%3];"
                 ::"r"(dst), "l"(src), "r"(bytes), "r"(bar) : "memory");
}
__device__ __forceinline__ void cp_async16(uint32_t dst, const void* src) {
    asm volatile("cp.async.cg.shared.global [%0], [%1], 16;" ::"r"(dst), "l"(src) : "memory");
}
__device__ __forceinline__ void bulk_load_mc(uint32_t dst, const void* src, uint32_t bytes, uint32_t bar) {
    asm volatile("cp.async.bulk.shared::cluster.global.mbarrier::complete_tx::bytes.multicast::cluster [%0], [%1], %2, [%3], %4;"
                 ::"r"(dst), "l"(src), "r"(bytes), "r"(bar), "h"((uint16_t)3) : "memory");
}
__device__ __forceinline__ void fence_async_smem() { asm volatile("fence.proxy.async.shared::cta;" ::: "memory"); }
__device__ __forceinline__ void prefetch_map(const CUtensorMap* m) {
    asm volatile("prefetch.tensormap [%0];" ::"l"(m) : "memory");
}
__device__ __forceinline__ void red_release(unsigned* p) {
    asm volatile("red.release.gpu.global.add.u32 [%0], 1;" ::"l"(p) : "memory");
}
__device__ __forceinline__ unsigned ld_relaxed(const unsigned* p) {
    unsigned v;
    asm volatile("ld.relaxed.gpu.global.u32 %0, [%1];" : "=r"(v) : "l"(p) : "memory");
    return v;
}
__device__ __forceinline__ void wait_counter(const unsigned* p, unsigned target) {
    for (uint32_t n = 0; (int)(ld_relaxed(p) - target) < 0 && n < SPIN_LIMIT; n++) __nanosleep(100);
    asm volatile("fence.acquire.gpu;" ::: "memory");
    asm volatile("fence.proxy.async.global;" ::: "memory");
}
__device__ __forceinline__ void bar_sync(int id, int n) { asm volatile("bar.sync %0, %1;" ::"r"(id), "r"(n) : "memory"); }
__device__ __forceinline__ void bar_arrive(int id, int n) { asm volatile("bar.arrive %0, %1;" ::"r"(id), "r"(n) : "memory"); }
__device__ __forceinline__ void cluster_sync() {
    asm volatile("barrier.cluster.arrive.relaxed.aligned;\nbarrier.cluster.wait.aligned;" ::: "memory");
}
__device__ __forceinline__ void wg_fence() { asm volatile("wgmma.fence.sync.aligned;" ::: "memory"); }
__device__ __forceinline__ void wg_commit() { asm volatile("wgmma.commit_group.sync.aligned;" ::: "memory"); }
template <int N> __device__ __forceinline__ void wg_wait() { asm volatile("wgmma.wait_group.sync.aligned %0;" ::"n"(N) : "memory"); }
template <int N> __device__ __forceinline__ void reg_fence(float (&a)[N]) {
#pragma unroll
    for (int i = 0; i < N; i++) asm volatile("" : "+f"(a[i])::"memory");
}
template <int N> __device__ __forceinline__ void reg_fence(uint32_t (&a)[N]) {
#pragma unroll
    for (int i = 0; i < N; i++) asm volatile("" : "+r"(a[i])::"memory");
}
__device__ __forceinline__ uint32_t pack_bf16(float lo, float hi) {
    uint32_t r;
    asm("cvt.rn.bf16x2.f32 %0, %1, %2;" : "=r"(r) : "f"(hi), "f"(lo));
    return r;
}
__device__ __forceinline__ float bf_lo(uint32_t v) { return __uint_as_float(v << 16); }
__device__ __forceinline__ float bf_hi(uint32_t v) { return __uint_as_float(v & 0xffff0000u); }
__device__ __forceinline__ float bf_round(float v) { return __bfloat162float(__float2bfloat16_rn(v)); }
__device__ __forceinline__ float ex2(float v) {
    float r;
    asm("ex2.approx.ftz.f32 %0, %1;" : "=f"(r) : "f"(v));
    return r;
}
__device__ __forceinline__ float sqrt_approx(float v) {
    float r;
    asm("sqrt.approx.ftz.f32 %0, %1;" : "=f"(r) : "f"(v));
    return r;
}
__device__ __forceinline__ float rcp_approx(float v) {
    float r;
    asm("rcp.approx.ftz.f32 %0, %1;" : "=f"(r) : "f"(v));
    return r;
}
__device__ __forceinline__ float silu_f(float v) { return v * rcp_approx(1.0f + ex2(v * -1.4426950408889634f)); }
__device__ __forceinline__ void stmatrix_x4(uint32_t addr, uint32_t r0, uint32_t r1, uint32_t r2, uint32_t r3) {
    asm volatile("stmatrix.sync.aligned.m8n8.x4.shared.b16 [%0], {%1, %2, %3, %4};"
                 ::"r"(addr), "r"(r0), "r"(r1), "r"(r2), "r"(r3) : "memory");
}
__device__ __forceinline__ void sts128(uint32_t addr, uint32_t r0, uint32_t r1, uint32_t r2, uint32_t r3) {
    asm volatile("st.shared.v4.b32 [%0], {%1, %2, %3, %4};" ::"r"(addr), "r"(r0), "r"(r1), "r"(r2), "r"(r3) : "memory");
}
__device__ __forceinline__ void lds128(uint32_t addr, uint32_t& r0, uint32_t& r1, uint32_t& r2, uint32_t& r3) {
    asm volatile("ld.shared.v4.b32 {%0, %1, %2, %3}, [%4];" : "=r"(r0), "=r"(r1), "=r"(r2), "=r"(r3) : "r"(addr) : "memory");
}
__device__ __forceinline__ uint32_t bf2_mul(uint32_t a, uint32_t b) {
    uint32_t r;
    asm("mul.rn.bf16x2 %0, %1, %2;" : "=r"(r) : "r"(a), "r"(b));
    return r;
}
__device__ __forceinline__ uint32_t bf2_add(uint32_t a, uint32_t b) {
    uint32_t r;
    asm("add.rn.bf16x2 %0, %1, %2;" : "=r"(r) : "r"(a), "r"(b));
    return r;
}
constexpr uint64_t POL_FIRST = 0x12F0000000000000ull, POL_NORMAL = 0x1000000000000000ull;
__device__ __forceinline__ uint4 ldg_hint(const void* p, uint64_t pol) {
    uint4 v;
    asm volatile("ld.global.cg.L2::cache_hint.v4.u32 {%0, %1, %2, %3}, [%4], %5;" : "=r"(v.x), "=r"(v.y), "=r"(v.z), "=r"(v.w) : "l"(p), "l"(pol));
    return v;
}
__device__ __forceinline__ void stg_hint(void* p, uint32_t r0, uint32_t r1, uint32_t r2, uint32_t r3, uint64_t pol) {
    asm volatile("st.global.cg.L2::cache_hint.v4.u32 [%0], {%1, %2, %3, %4}, %5;" ::"l"(p), "r"(r0), "r"(r1), "r"(r2), "r"(r3), "l"(pol) : "memory");
}

__device__ __forceinline__ uint64_t make_desc(uint32_t addr, uint32_t lbo_bytes) {
    return (uint64_t)((addr & 0x3FFFF) >> 4) | ((uint64_t)(lbo_bytes >> 4) << 16) | ((uint64_t)(1024 >> 4) << 32) | (1ull << 62);
}

__device__ __forceinline__ void wgmma_n256_ss(float (&d)[128], uint64_t da, uint64_t db, int acc) {
    asm volatile(
        "{\n.reg .pred p;\nsetp.ne.b32 p, %130, 0;\n"
        "wgmma.mma_async.sync.aligned.m64n256k16.f32.bf16.bf16 {"
        "%0, %1, %2, %3, %4, %5, %6, %7, %8, %9, %10, %11, %12, %13, %14, %15, "
        "%16, %17, %18, %19, %20, %21, %22, %23, %24, %25, %26, %27, %28, %29, %30, %31, "
        "%32, %33, %34, %35, %36, %37, %38, %39, %40, %41, %42, %43, %44, %45, %46, %47, "
        "%48, %49, %50, %51, %52, %53, %54, %55, %56, %57, %58, %59, %60, %61, %62, %63, "
        "%64, %65, %66, %67, %68, %69, %70, %71, %72, %73, %74, %75, %76, %77, %78, %79, "
        "%80, %81, %82, %83, %84, %85, %86, %87, %88, %89, %90, %91, %92, %93, %94, %95, "
        "%96, %97, %98, %99, %100, %101, %102, %103, %104, %105, %106, %107, %108, %109, %110, %111, "
        "%112, %113, %114, %115, %116, %117, %118, %119, %120, %121, %122, %123, %124, %125, %126, %127"
        "}, %128, %129, p, 1, 1, 1, 0;\n}\n"
        :
        "+f"(d[0]), "+f"(d[1]), "+f"(d[2]), "+f"(d[3]), "+f"(d[4]), "+f"(d[5]), "+f"(d[6]), "+f"(d[7]),
        "+f"(d[8]), "+f"(d[9]), "+f"(d[10]), "+f"(d[11]), "+f"(d[12]), "+f"(d[13]), "+f"(d[14]), "+f"(d[15]),
        "+f"(d[16]), "+f"(d[17]), "+f"(d[18]), "+f"(d[19]), "+f"(d[20]), "+f"(d[21]), "+f"(d[22]), "+f"(d[23]),
        "+f"(d[24]), "+f"(d[25]), "+f"(d[26]), "+f"(d[27]), "+f"(d[28]), "+f"(d[29]), "+f"(d[30]), "+f"(d[31]),
        "+f"(d[32]), "+f"(d[33]), "+f"(d[34]), "+f"(d[35]), "+f"(d[36]), "+f"(d[37]), "+f"(d[38]), "+f"(d[39]),
        "+f"(d[40]), "+f"(d[41]), "+f"(d[42]), "+f"(d[43]), "+f"(d[44]), "+f"(d[45]), "+f"(d[46]), "+f"(d[47]),
        "+f"(d[48]), "+f"(d[49]), "+f"(d[50]), "+f"(d[51]), "+f"(d[52]), "+f"(d[53]), "+f"(d[54]), "+f"(d[55]),
        "+f"(d[56]), "+f"(d[57]), "+f"(d[58]), "+f"(d[59]), "+f"(d[60]), "+f"(d[61]), "+f"(d[62]), "+f"(d[63]),
        "+f"(d[64]), "+f"(d[65]), "+f"(d[66]), "+f"(d[67]), "+f"(d[68]), "+f"(d[69]), "+f"(d[70]), "+f"(d[71]),
        "+f"(d[72]), "+f"(d[73]), "+f"(d[74]), "+f"(d[75]), "+f"(d[76]), "+f"(d[77]), "+f"(d[78]), "+f"(d[79]),
        "+f"(d[80]), "+f"(d[81]), "+f"(d[82]), "+f"(d[83]), "+f"(d[84]), "+f"(d[85]), "+f"(d[86]), "+f"(d[87]),
        "+f"(d[88]), "+f"(d[89]), "+f"(d[90]), "+f"(d[91]), "+f"(d[92]), "+f"(d[93]), "+f"(d[94]), "+f"(d[95]),
        "+f"(d[96]), "+f"(d[97]), "+f"(d[98]), "+f"(d[99]), "+f"(d[100]), "+f"(d[101]), "+f"(d[102]), "+f"(d[103]),
        "+f"(d[104]), "+f"(d[105]), "+f"(d[106]), "+f"(d[107]), "+f"(d[108]), "+f"(d[109]), "+f"(d[110]), "+f"(d[111]),
        "+f"(d[112]), "+f"(d[113]), "+f"(d[114]), "+f"(d[115]), "+f"(d[116]), "+f"(d[117]), "+f"(d[118]), "+f"(d[119]),
        "+f"(d[120]), "+f"(d[121]), "+f"(d[122]), "+f"(d[123]), "+f"(d[124]), "+f"(d[125]), "+f"(d[126]), "+f"(d[127])
        : "l"(da), "l"(db), "r"(acc));
}

__device__ __forceinline__ void wgmma_n64_rs_tb(float* d, uint32_t a0, uint32_t a1, uint32_t a2, uint32_t a3, uint32_t db, int acc) {
    asm volatile(
        "{\n.reg .pred p;\n.reg .b64 db;\nsetp.ne.b32 p, %37, 0;\nmov.b64 db, {%36, 0x40000040};\n"
        "wgmma.mma_async.sync.aligned.m64n64k16.f32.bf16.bf16 {"
        "%0, %1, %2, %3, %4, %5, %6, %7, %8, %9, %10, %11, %12, %13, %14, %15, "
        "%16, %17, %18, %19, %20, %21, %22, %23, %24, %25, %26, %27, %28, %29, %30, %31"
        "}, {%32, %33, %34, %35}, db, p, 1, 1, 1;\n}\n"
        :
        "+f"(d[0]), "+f"(d[1]), "+f"(d[2]), "+f"(d[3]), "+f"(d[4]), "+f"(d[5]), "+f"(d[6]), "+f"(d[7]),
        "+f"(d[8]), "+f"(d[9]), "+f"(d[10]), "+f"(d[11]), "+f"(d[12]), "+f"(d[13]), "+f"(d[14]), "+f"(d[15]),
        "+f"(d[16]), "+f"(d[17]), "+f"(d[18]), "+f"(d[19]), "+f"(d[20]), "+f"(d[21]), "+f"(d[22]), "+f"(d[23]),
        "+f"(d[24]), "+f"(d[25]), "+f"(d[26]), "+f"(d[27]), "+f"(d[28]), "+f"(d[29]), "+f"(d[30]), "+f"(d[31])
        : "r"(a0), "r"(a1), "r"(a2), "r"(a3), "r"(db), "r"(acc));
}

template <int TB>
__device__ __forceinline__ void wgmma_n128_rs(float (&d)[64], uint32_t a0, uint32_t a1, uint32_t a2, uint32_t a3, uint32_t db, int acc) {
    asm volatile(
        "{\n.reg .pred p;\n.reg .b64 db;\nsetp.ne.b32 p, %69, 0;\nmov.b64 db, {%68, 0x40000040};\n"
        "wgmma.mma_async.sync.aligned.m64n128k16.f32.bf16.bf16 {"
        "%0, %1, %2, %3, %4, %5, %6, %7, %8, %9, %10, %11, %12, %13, %14, %15, "
        "%16, %17, %18, %19, %20, %21, %22, %23, %24, %25, %26, %27, %28, %29, %30, %31, "
        "%32, %33, %34, %35, %36, %37, %38, %39, %40, %41, %42, %43, %44, %45, %46, %47, "
        "%48, %49, %50, %51, %52, %53, %54, %55, %56, %57, %58, %59, %60, %61, %62, %63"
        "}, {%64, %65, %66, %67}, db, p, 1, 1, %70;\n}\n"
        :
        "+f"(d[0]), "+f"(d[1]), "+f"(d[2]), "+f"(d[3]), "+f"(d[4]), "+f"(d[5]), "+f"(d[6]), "+f"(d[7]),
        "+f"(d[8]), "+f"(d[9]), "+f"(d[10]), "+f"(d[11]), "+f"(d[12]), "+f"(d[13]), "+f"(d[14]), "+f"(d[15]),
        "+f"(d[16]), "+f"(d[17]), "+f"(d[18]), "+f"(d[19]), "+f"(d[20]), "+f"(d[21]), "+f"(d[22]), "+f"(d[23]),
        "+f"(d[24]), "+f"(d[25]), "+f"(d[26]), "+f"(d[27]), "+f"(d[28]), "+f"(d[29]), "+f"(d[30]), "+f"(d[31]),
        "+f"(d[32]), "+f"(d[33]), "+f"(d[34]), "+f"(d[35]), "+f"(d[36]), "+f"(d[37]), "+f"(d[38]), "+f"(d[39]),
        "+f"(d[40]), "+f"(d[41]), "+f"(d[42]), "+f"(d[43]), "+f"(d[44]), "+f"(d[45]), "+f"(d[46]), "+f"(d[47]),
        "+f"(d[48]), "+f"(d[49]), "+f"(d[50]), "+f"(d[51]), "+f"(d[52]), "+f"(d[53]), "+f"(d[54]), "+f"(d[55]),
        "+f"(d[56]), "+f"(d[57]), "+f"(d[58]), "+f"(d[59]), "+f"(d[60]), "+f"(d[61]), "+f"(d[62]), "+f"(d[63])
        : "r"(a0), "r"(a1), "r"(a2), "r"(a3), "r"(db), "r"(acc), "n"(TB));
}

__device__ __forceinline__ void wgmma_n128_ss(float* d, uint64_t da, uint64_t db, int acc) {
    asm volatile(
        "{\n.reg .pred p;\nsetp.ne.b32 p, %66, 0;\n"
        "wgmma.mma_async.sync.aligned.m64n128k16.f32.bf16.bf16 {"
        "%0, %1, %2, %3, %4, %5, %6, %7, %8, %9, %10, %11, %12, %13, %14, %15, "
        "%16, %17, %18, %19, %20, %21, %22, %23, %24, %25, %26, %27, %28, %29, %30, %31, "
        "%32, %33, %34, %35, %36, %37, %38, %39, %40, %41, %42, %43, %44, %45, %46, %47, "
        "%48, %49, %50, %51, %52, %53, %54, %55, %56, %57, %58, %59, %60, %61, %62, %63"
        "}, %64, %65, p, 1, 1, 0, 1;\n}\n"
        :
        "+f"(d[0]), "+f"(d[1]), "+f"(d[2]), "+f"(d[3]), "+f"(d[4]), "+f"(d[5]), "+f"(d[6]), "+f"(d[7]),
        "+f"(d[8]), "+f"(d[9]), "+f"(d[10]), "+f"(d[11]), "+f"(d[12]), "+f"(d[13]), "+f"(d[14]), "+f"(d[15]),
        "+f"(d[16]), "+f"(d[17]), "+f"(d[18]), "+f"(d[19]), "+f"(d[20]), "+f"(d[21]), "+f"(d[22]), "+f"(d[23]),
        "+f"(d[24]), "+f"(d[25]), "+f"(d[26]), "+f"(d[27]), "+f"(d[28]), "+f"(d[29]), "+f"(d[30]), "+f"(d[31]),
        "+f"(d[32]), "+f"(d[33]), "+f"(d[34]), "+f"(d[35]), "+f"(d[36]), "+f"(d[37]), "+f"(d[38]), "+f"(d[39]),
        "+f"(d[40]), "+f"(d[41]), "+f"(d[42]), "+f"(d[43]), "+f"(d[44]), "+f"(d[45]), "+f"(d[46]), "+f"(d[47]),
        "+f"(d[48]), "+f"(d[49]), "+f"(d[50]), "+f"(d[51]), "+f"(d[52]), "+f"(d[53]), "+f"(d[54]), "+f"(d[55]),
        "+f"(d[56]), "+f"(d[57]), "+f"(d[58]), "+f"(d[59]), "+f"(d[60]), "+f"(d[61]), "+f"(d[62]), "+f"(d[63])
        : "l"(da), "l"(db), "r"(acc));
}

__device__ __forceinline__ void wgmma_n8_ta(float* d, uint64_t da, uint64_t db) {
    asm volatile("wgmma.mma_async.sync.aligned.m64n8k16.f32.bf16.bf16 {%0, %1, %2, %3}, %4, %5, 1, 1, 1, 1, 0;\n"
                 : "+f"(d[0]), "+f"(d[1]), "+f"(d[2]), "+f"(d[3]) : "l"(da), "l"(db));
}

#define PROF(slot, role)
#undef PROF_GT
#define PROF_GT(slot)

struct Params {
    const __nv_bfloat16* x;
    const __nv_bfloat16* w_r;
    const uint8_t *c_kv, *w_uk, *w_uv;
    uint8_t* out;
};
__device__ __forceinline__ void lsu_prefetch(const void* p) { asm volatile("prefetch.global.L2 [%0];" ::"l"(p) : "memory"); }

template <typename T>
__device__ __forceinline__ T* ptr_off(T* base, uint32_t off) {
    uint32_t lo, hi;
    asm("mov.b64 {%0, %1}, %2;" : "=r"(lo), "=r"(hi) : "l"(base));
    asm("add.cc.u32 %0, %0, %2;\naddc.u32 %1, %1, 0;" : "+r"(lo), "+r"(hi) : "r"(off));
    T* r;
    asm("mov.b64 %0, {%1, %2};" : "=l"(r) : "r"(lo), "r"(hi));
    return r;
}
__device__ __forceinline__ int kv_head(int pair) { return pair & 7; }
__device__ __forceinline__ int kv_tokens(int pair) { return ((pair >> 3) & 1) * 4 + (pair >> 4); }
__device__ __forceinline__ int out_rows(int pair) { return pair & 7; }
__device__ __forceinline__ int out_cols(int pair) { return (pair >> 4) * 4 + ((pair >> 3) & 1) * 2; }
__device__ __forceinline__ int attn_rowblock(int pair, int seg) {
    int j = pair & 3, hl = pair >> 2;
    return (((hl & 1) | (j == 0)) ^ seg) ? j : 7 - j;
}
__device__ __forceinline__ int outproj_head(int i, int ib) {
    if (i < 16) return i;
    return 16 + 2 * (i & 7) + ((ib < 4) ^ ((i >> 3) & 1));
}

__device__ __forceinline__ void pin_value(uint32_t& v) { asm volatile("" : "+r"(v)); }
__device__ __forceinline__ void pin_value(int& v) { asm volatile("" : "+r"(v)); }
__device__ __forceinline__ void pin_value(const uint8_t*& v) { asm volatile("" : "+l"(v)); }

__device__ __forceinline__ void producer(const Params& P, uint32_t sb, int pair, int c,
                                         const CUtensorMap* m_ckv, const CUtensorMap* m_wu,
                                         const CUtensorMap* m_wq, const CUtensorMap* m_wo) {
    const int hl = pair >> 2;
    const int ibA = attn_rowblock(pair, 0), nA = 2 * ibA + 2;
    const int ib = out_rows(pair), mi = 2 * ib + c, nb = out_cols(pair);
    const bool leader = elect_one();
    uint32_t g = 4, tail = 0;
    if (leader) prefetch_map(m_wq);
    auto wait_released = [&](uint32_t need) {
#pragma unroll 1
        for (; tail <= need; tail++) mbar_wait(sb + BAR_EMPTY + (tail & 7) * 8, (tail >> 3) & 1);
    };
    auto wait_released_here = [&](uint32_t need) {
#pragma unroll 1
        for (; tail < need; tail++) mbar_wait(sb + BAR_EMPTY + (tail & 7) * 8, (tail >> 3) & 1);
        if (tail == need) mbar_wait(sb + BAR_EMPTYL + (need & 7) * 8, (need >> 3) & 1);
    };
    auto wait_released_peer = [&](uint32_t need) {
        if (tail == need) {
            uint32_t eb = sb + BAR_EMPTY + (need & 7) * 8, ep = (need >> 3) & 1;
            tail++;
            mbar_wait(eb, ep);
        }
    };
    auto full_bar = [&]() { return sb + BAR_FULL + (g & 7) * 8; };
    auto pin = [](auto&... v) { (pin_value(v), ...); };
#pragma unroll 1
    for (int rnd = 0; rnd < 2; rnd++) {
#pragma unroll 1
        for (int i = rnd ? 0 : 4; i < 16; i++) {
            int kb = i & 7, h2 = (kv_head(pair) + (i & 8) + rnd * 16) * 2, krow = kb * 64;
            uint32_t pg = sb + (i & 3) * (3 * PAGE), pb = pg + (1 + c) * PAGE, bar = full_bar();
            pin(kb, h2, krow, pg, pb, bar);
            const uint32_t need = g - 4 - (i < 2);
            wait_released_here(need);
            if (leader) {
                mbar_expect_tx(bar, 3 * PAGE);
                tma_3d(pg, m_wu, 0, krow, h2, bar);
            }
            wait_released_peer(need);
            if (leader) {
                tma_3d_mc(pb, m_ckv, 0, kv_tokens(pair) * 256 + c * 128, kb, bar);
                if (rnd == 1 && i == 3) asm volatile("red.relaxed.gpu.global.add.u32 [%0], 1;" ::"l"(ptr_off(g_sync.kvfree, hl * 32)) : "memory");
            }
            g++;
        }
        mbar_sleep(sb + BAR_DEP, 0);
        const uint8_t* xa = ptr_off(g_xn, ibA * (16 * 32768) + c * PAGE);
        const uint8_t* xb = ptr_off(g_xn, (7 - ibA) * (16 * 32768) + (1 - c) * PAGE);
#pragma unroll 1
        for (int kb = 0; kb < DM / 64; kb++) {
            uint32_t pg = sb + (kb & 3) * (3 * PAGE), pw = pg + 2 * PAGE + c * 8192, bar = full_bar(), p2 = pg + PAGE;
            int krow = kb * 64;
            pin(pg, pw, p2, bar, krow);
            wait_released_here(g - 4);
            if (leader) {
                mbar_expect_tx(bar, 3 * PAGE);
                bulk_load(pg, xa, PAGE, bar);
            }
            wait_released_peer(g - 4);
            if (leader) {
                tma_3d_mc(pw, m_wq, 0, krow, (rnd * 16 + hl) * 2 + c, bar);
                bulk_load(p2, xb, PAGE, bar);
            }
            g++;
            xa += 32768;
            xb += 32768;
        }
        mbar_sleep(sb + BAR_DEP + 8 + rnd * 16, 0);
        if (rnd == 1 && leader) prefetch_map(m_wo);
        uint32_t pg = sb + c * PAGE;
#pragma unroll 1
        for (int j = 0; j < 36; j++) {
            const bool isk = j == 0 || ((j & 1) && j != 35);
            const int t = isk ? (j + 1) >> 1 : (j - 1) >> 1;
            const uint8_t* src = ptr_off(g_kv, (hl * 16 + (t >= nA ? t - nA : t)) * 65536 + (isk ? 0 : 32768) + c * PAGE);
            uint32_t bar = full_bar(), need = g - 6 + (j < 2) + (j < 5);
            pin(src, bar, need);
            wait_released(need);
            if (leader) {
                mbar_expect_tx(bar, 2 * PAGE);
                bulk_load_mc(pg, src, PAGE, bar);
            }
            g++;
            if (rnd == 0 && j >= 22 && j < 34) {
                const int cta = pair * 2 + c, i = j - 22;
                const uint32_t l = (threadIdx.x & 31) * 128;
                if (i < 8) lsu_prefetch(ptr_off(i & 1 ? P.w_uv : P.w_uk, cta * 32768 + (i >> 1) * 8192 + 4096 + l));
                else lsu_prefetch(ptr_off(P.c_kv, cta * 16384 + (i - 8) * 4096 + l));
            }
            pg = pg >= sb + SM_REGION - 2 * PAGE ? pg - (SM_REGION - 2 * PAGE) : pg + 2 * PAGE;
        }
    }
    uint32_t pg = sb;
#pragma unroll 1
    for (int i = 0; i < 64; i++) {
        if ((i & 15) == 0 && i != 16) mbar_sleep(sb + BAR_DEP + 32 + (i >> 1) - (i ? 8 : 0), 0);
        const int kb = outproj_head(i >> 1, ib) * 2 + (i & 1);
        const uint8_t* src = ptr_off(g_ctx, (mi * 64 + kb) * PAGE);
        uint32_t bar = full_bar(), pw = pg + PAGE + c * 8192;
        int krow = kb * 64;
        pin(src, bar, pw, krow);
        wait_released_here(g - 6);
        if (leader) {
            mbar_expect_tx(bar, 2 * PAGE);
            bulk_load(pg, src, PAGE, bar);
        }
        wait_released_peer(g - 6);
        if (leader) tma_3d_mc(pw, m_wo, 0, krow, nb + c, bar);
        g++;
        pg = pg == sb + SM_REGION - 2 * PAGE ? sb : pg + 2 * PAGE;
    }
}

__device__ __forceinline__ uint32_t xn_block(int row64, int kb) {
    return (((row64 >> 2) * 16 + kb) * 4 + ((row64 & 1) * 2 + (((row64 >> 1) & 1) ^ 1))) * 8192;
}
__device__ __forceinline__ uint32_t image_offset(int row, int ch) {
    return xn_block(row >> 6, ch >> 3) + (row & 63) * 128 + (((ch & 7) ^ (row & 7)) << 4);
}
__device__ __forceinline__ uint32_t bf2_sub(uint32_t a, uint32_t b) {
    uint32_t r;
    asm("sub.rn.bf16x2 %0, %1, %2;" : "=r"(r) : "r"(a), "r"(b));
    return r;
}
__device__ __forceinline__ uint32_t bf2_fma(uint32_t a, uint32_t b, uint32_t c) {
    uint32_t r;
    asm("fma.rn.bf16x2 %0, %1, %2, %3;" : "=r"(r) : "r"(a), "r"(b), "r"(c));
    return r;
}
template <int N0, int N>
__device__ __forceinline__ void ln_sums(const uint32_t (&u)[N], float& sum, float& sq) {
    float s0 = 0.f, s1 = 0.f, q0 = 0.f, q1 = 0.f;
#pragma unroll
    for (int k = N0; k < N0 + 16; k++) {
        const float a = bf_lo(u[k]), b = bf_hi(u[k]);
        s0 += a; s1 += b;
        q0 = fmaf(a, a, q0); q1 = fmaf(b, b, q1);
    }
    sum = s0 + s1;
    sq = q0 + q1;
}
__device__ __forceinline__ void ln_finish(float sum, float sq, uint32_t& mean2, uint32_t& rhi2, uint32_t& rlo2) {
    const float ms = sum * (1.0f / DM);
    const float var = fmaxf(fmaf(-ms, ms, sq * (1.0f / DM)), 0.f);
    const float rden = rcp_approx(bf_round(sqrt_approx(bf_round(bf_round(var) + 1e-5f))));
    const float rhi = bf_round(rden);
    mean2 = pack_bf16(ms, ms);
    rhi2 = pack_bf16(rhi, rhi);
    rlo2 = pack_bf16(rden - rhi, rden - rhi);
}
template <int N0, int N>
__device__ __forceinline__ void ln_apply(uint32_t (&u)[N], uint32_t mean2, uint32_t rhi2, uint32_t rlo2, uint8_t* dst) {
#pragma unroll
    for (int i = 0; i < 4; i++) {
        uint32_t o[4];
#pragma unroll
        for (int k = 0; k < 4; k++) {
            const uint32_t d = bf2_sub(u[N0 + 4 * i + k], mean2);
            o[k] = bf2_fma(d, rhi2, bf2_mul(d, rlo2));
        }
#pragma unroll
        for (int k = 0; k < 4; k++) u[N0 + 4 * i + k] = o[k];
        __stcg(reinterpret_cast<uint4*>(dst + i * 131072), make_uint4(o[0], o[1], o[2], o[3]));
    }
}
__device__ __forceinline__ int query_rowblock(int pair, int c, int w, int seg) {
    const int qA = (w ? 0 : 2) + c;
    return 4 * attn_rowblock(pair, seg) + (seg ? 3 - qA : qA);
}

__device__ __noinline__ void fetch_helper(const uint8_t* w_u, uint32_t sb, int w, int lane, int pair, int c) {
    const uint32_t page = sb + SM_REGION + w * PAGE + lane * 16;
    mbar_sleep(sb + BAR_FULL + 5 * 8, 0);
#pragma unroll 1
    for (int i = 0; i < 2; i++) {
        lsu_prefetch(ptr_off(w_u, ((pair * 2 + c) * 4 + i * 2 + (lane >> 4)) * 8192 + 2048 + (lane & 15) * 128));
        __nanosleep(300);
    }
    const unsigned e1 = __ldcg(&g_sync.done) / NCTA + 1;
#pragma unroll 1
    for (int e = 1; e <= 7; e += 2) mbar_sleep(sb + BAR_DONE + 8, (e >> 1) & 1);
    const int rb = out_rows(pair) * 4 + c * 2 + w, kb0 = out_cols(pair);
    const uint8_t* src = ptr_off(g_xn, xn_block(rb, kb0) + lane * 16);
#pragma unroll 1
    for (int i = 0; i < 32; i += 4) {
#pragma unroll
        for (int k = 0; k < 4; k++) cp_async16(page + (i + k) * 512, src + (i + k) * 512 + (i >> 4) * (32768 - 8192));
        __nanosleep(200);
    }
    wait_counter(&g_sync.ffn_done, e1);
    const int r = __ldcg(ptr_off(g_sel, (lane >> 4) * 4)) - rb * 64, ch = lane & 15;
    const uint4 t = __ldcg(ptr_off(g_routed, ((lane >> 4) * 128 + kb0 * 8 + ch) * 16));
    asm volatile("cp.async.wait_all;" ::: "memory");
    __syncwarp();
    if (r >= 0 && r < 64)
        sts128(sb + SM_REGION + w * PAGE + (ch >> 3) * 8192 + r * 128 + (((ch & 7) ^ (r & 7)) << 4), t.x, t.y, t.z, t.w);
    __syncwarp();
    if (lane == 0) mbar_arrive(sb + BAR_G + w * 8);
    PROF(20, 2);
}

__device__ __noinline__ void sync_helper(uint32_t sb, int lane, int pair, int c) {
    const unsigned e1 = __ldcg(&g_sync.done) / NCTA + 1;
    const int ib = out_rows(pair);
    int e = 0, b = 0;
#pragma unroll 1
    for (uint32_t n = 0; (e < 9 || b < 7) && n < SPIN_LIMIT; n++) {
        if (e < 9 && __all_sync(~0u, mbar_test(sb + BAR_DONE + (e & 1) * 8, (e >> 1) & 1))) {
            const int rnd = e > 4, ev = (e - 1) & 3;
            unsigned* flag = e == 0 ? &g_sync.ln
                           : ev < 2 ? ptr_off(g_sync.kv, (rnd * 16 + kv_head(pair) + 8 * ev) * 32)
                                    : ptr_off(g_sync.ctx, (query_rowblock(pair, c, lane & 1, ev & 1) * NH + rnd * 16 + (pair >> 2)) * 4);
            asm volatile("fence.proxy.async.global;\nfence.release.gpu;" ::: "memory");
            if (lane < ((e == 0 || ev < 2) ? 1 : 2)) asm volatile("red.relaxed.gpu.global.add.u32 [%0], 1;" ::"l"(flag) : "memory");
            PROF(10 + e, 2);
            e++;
        }
        if (b < 7 && e > 0 && (b < 4 || (n & POLL_MASK) == 0)) {
            const int i = b == 4 ? lane >> 1 : 8 * b - 24 + ((lane >> 1) & 7);
            const unsigned* cnt = b == 0 ? &g_sync.ln
                                : b == 2 ? ptr_off(g_sync.kvfree, (kv_head(pair) + 8 * (lane & 1)) * 32)
                                : b < 4 ? ptr_off(g_sync.kv, ((b >> 1) * 16 + (pair >> 2)) * 32)
                                        : ptr_off(g_sync.ctx, ((4 * ib + 2 * c + (lane & 1)) * NH + outproj_head(i & 31, ib)) * 4);
            if (__all_sync(~0u, (int)(ld_relaxed(cnt) - e1 * (b == 0 ? NMAIN : b == 2 ? 8 : b < 4 ? 16 : 1)) >= 0)) {
                asm volatile("fence.acquire.gpu;\nfence.proxy.async.global;" ::: "memory");
                __syncwarp();
                if (lane == 0) mbar_arrive(sb + BAR_DEP + b * 8);
                PROF(1 + b, 2);
                b++;
            }
        }
        __nanosleep(150);
    }
}

__device__ __forceinline__ unsigned long long block_max_key(unsigned long long k, unsigned long long* red, int tid) {
#pragma unroll
    for (int o = 16; o; o >>= 1) {
        unsigned long long t = __shfl_xor_sync(~0u, k, o);
        k = t > k ? t : k;
    }
    bar_sync(1, 256);
    if ((tid & 31) == 0) red[tid >> 5] = k;
    bar_sync(1, 256);
    k = red[0];
#pragma unroll
    for (int i = 1; i < 8; i++) k = red[i] > k ? red[i] : k;
    return k;
}

constexpr int FS = FF / 4;
constexpr int FSTAGE = 32768, FNST = 6;
constexpr int FN1 = 2 * (DM / 16), FN2 = FS / 16;

__device__ __forceinline__ void ffn_producer(uint32_t sb, int s, const CUtensorMap* m_gate, const CUtensorMap* m_up,
                                             const CUtensorMap* m_down) {
    wait_counter(&g_sync.ln, (__ldcg(&g_sync.done) / NCTA + 1) * NMAIN);
    int slot = 0, ph = 1;
#pragma unroll 1
    for (int st = 0; st < FN1 + FN2; st++) {
        mbar_sleep(sb + BAR_EMPTY + slot * 8, ph);
        const uint32_t bar = sb + BAR_FULL + slot * 8;
        const bool up = st < FN1;
        mbar_expect_tx(bar, up ? FS * 32 : DM * 32);
        tma_3d_hint(sb + slot * FSTAGE, up ? ((st & 1) ? m_up : m_gate) : m_down, 0,
                    up ? (st >> 1) * 16 : s * FS + (st - FN1) * 16, up ? s * (FS / 64) : 0, bar, POL_FIRST);
        if (++slot == FNST) { slot = 0; ph ^= 1; }
    }
}

__device__ __forceinline__ void ffn_cta(uint8_t* smem, uint32_t sb, int s, unsigned epoch, const __nv_bfloat16* w_r) {
    const int tid = threadIdx.x, lane = tid & 31;
    const int warp = __shfl_sync(~0u, tid >> 5, 0), w = warp >> 2;
    constexpr uint32_t XB = FNST * FSTAGE, HB = XB + 16384, AUX = HB + 14336;
    unsigned long long* red = reinterpret_cast<unsigned long long*>(smem + AUX);
    unsigned* flag = reinterpret_cast<unsigned*>(smem + AUX + 128);
    const unsigned e1 = epoch + 1;
    for (int i = tid; i < (16384 + 14336) / 16; i += 256) reinterpret_cast<uint4*>(smem + XB)[i] = make_uint4(0, 0, 0, 0);
    {
        float wf[32];
#pragma unroll
        for (int i = 0; i < 4; i++) {
            const uint4 t = __ldg(reinterpret_cast<const uint4*>(w_r) + lane + 32 * i);
            const uint32_t tu[4] = {t.x, t.y, t.z, t.w};
#pragma unroll
            for (int k = 0; k < 4; k++) { wf[8 * i + 2 * k] = bf_lo(tu[k]); wf[8 * i + 2 * k + 1] = bf_hi(tu[k]); }
        }
        if (tid == 0) wait_counter(&g_sync.ln, e1 * NMAIN);
        bar_sync(1, 256);
#pragma unroll 1
        for (int r0 = s * (SEQ / 4) + warp * (SEQ / 32); r0 < s * (SEQ / 4) + (warp + 1) * (SEQ / 32); r0 += 4) {
            uint4 t[4][4];
#pragma unroll
            for (int r = 0; r < 4; r++)
#pragma unroll
                for (int i = 0; i < 4; i++) t[r][i] = __ldcg(reinterpret_cast<const uint4*>(g_xn + image_offset(r0 + r, lane) + i * 131072));
            float acc[4];
#pragma unroll
            for (int r = 0; r < 4; r++) {
                float a = 0.f, b = 0.f;
#pragma unroll
                for (int i = 0; i < 4; i++) {
                    const uint32_t tu[4] = {t[r][i].x, t[r][i].y, t[r][i].z, t[r][i].w};
#pragma unroll
                    for (int k = 0; k < 4; k++) {
                        a = fmaf(bf_lo(tu[k]), wf[8 * i + 2 * k], a);
                        b = fmaf(bf_hi(tu[k]), wf[8 * i + 2 * k + 1], b);
                    }
                }
                acc[r] = a + b;
            }
#pragma unroll
            for (int o = 16; o; o >>= 1)
#pragma unroll
                for (int r = 0; r < 4; r++) acc[r] += __shfl_xor_sync(~0u, acc[r], o);
            if (lane < 4) __stcg(&g_r[r0 + lane], bf_round(lane == 0 ? acc[0] : lane == 1 ? acc[1] : lane == 2 ? acc[2] : acc[3]));
        }
        __threadfence();
        bar_sync(1, 256);
        if (tid == 0) {
            red_release(&g_sync.router);
            wait_counter(&g_sync.router, e1 * 4);
        }
        bar_sync(1, 256);
    }
    unsigned long long keys[8];
    unsigned long long best = 0;
#pragma unroll
    for (int i = 0; i < 8; i++) {
        int idx = tid + 256 * i;
        uint32_t b = __float_as_uint(__ldcg(&g_r[idx]) + 0.0f);
        b = (b & 0x80000000u) ? ~b : (b | 0x80000000u);
        keys[i] = ((unsigned long long)b << 32) | (unsigned)(SEQ - 1 - idx);
        best = keys[i] > best ? keys[i] : best;
    }
    const unsigned long long k0 = block_max_key(best, red, tid);
    best = 0;
#pragma unroll
    for (int i = 0; i < 8; i++) best = (keys[i] != k0 && keys[i] > best) ? keys[i] : best;
    const unsigned long long k1 = block_max_key(best, red, tid);
    const int row = SEQ - 1 - (int)((w ? k1 : k0) & 0xffffffffu);
    const int ch = tid & 127;
    const uint4 xrow = __ldcg(reinterpret_cast<const uint4*>(g_xn + image_offset(row, ch)));
    *reinterpret_cast<uint4*>(smem + XB + (ch >> 3) * 1024 + w * 128 + (((ch & 7) ^ w) << 4)) = xrow;
    fence_async_smem();
    bar_sync(1, 256);
    PROF(20, tid >> 7);
    int slot = 0, ph = 0, prev = 0;
    auto next_stage = [&](bool has_prev) {
        wg_commit();
        wg_wait<1>();
        if (has_prev && lane < 2) mbar_arrive(sb + BAR_EMPTY + prev * 8);
        prev = slot;
        if (++slot == FNST) { slot = 0; ph ^= 1; }
    };
    {
        float ag[28], au[28];
#pragma unroll
        for (int i = 0; i < 28; i++) ag[i] = au[i] = 0.f;
#pragma unroll 1
        for (int ks = 0; ks < DM / 16; ks++) {
            const uint64_t db = make_desc(sb + XB + (ks >> 2) * 1024 + (ks & 3) * 32, 16);
            mbar_wait(sb + BAR_FULL + slot * 8, ph);
            uint64_t da = make_desc(sb + slot * FSTAGE + w * (7 * 2048), 16);
            wg_fence();
#pragma unroll
            for (int b = 0; b < 7; b++) wgmma_n8_ta(ag + 4 * b, da + b * 128, db);
            next_stage(ks > 0);
            mbar_wait(sb + BAR_FULL + slot * 8, ph);
            da = make_desc(sb + slot * FSTAGE + w * (7 * 2048), 16);
            wg_fence();
#pragma unroll
            for (int b = 0; b < 7; b++) wgmma_n8_ta(au + 4 * b, da + b * 128, db);
            next_stage(true);
        }
        wg_wait<0>();
        reg_fence(ag);
        reg_fence(au);
        if ((lane & 3) == 0) {
#pragma unroll
            for (int i = 0; i < 28; i++) {
                const int f = (warp & 3) * 16 + (lane >> 2) + (i & 2) * 4, tok = i & 1;
                const float h = bf_round(silu_f(bf_round(ag[i]))) * bf_round(au[i]);
                *reinterpret_cast<__nv_bfloat16*>(smem + HB + (w * 7 + (i >> 2)) * 1024 + tok * 128 + (((f >> 3) ^ tok) << 4) + (f & 7) * 2) =
                    __float2bfloat16_rn(h);
            }
        }
    }
    fence_async_smem();
    bar_sync(1, 256);
    PROF(21, tid >> 7);
    {
        float ay[32];
#pragma unroll
        for (int i = 0; i < 32; i++) ay[i] = 0.f;
#pragma unroll 1
        for (int ks = 0; ks < FN2; ks++) {
            const uint64_t db = make_desc(sb + HB + (ks >> 2) * 1024 + (ks & 3) * 32, 16);
            mbar_wait(sb + BAR_FULL + slot * 8, ph);
            const uint64_t da = make_desc(sb + slot * FSTAGE + w * (8 * 2048), 16);
            wg_fence();
#pragma unroll
            for (int b = 0; b < 8; b++) wgmma_n8_ta(ay + 4 * b, da + b * 128, db);
            next_stage(true);
        }
        wg_wait<0>();
        reg_fence(ay);
        if ((lane & 3) == 0) {
#pragma unroll
            for (int i = 0; i < 32; i++)
                g_ypart[(s * 2 + (i & 1)) * DM + (w * 8 + (i >> 2)) * 64 + (warp & 3) * 16 + (lane >> 2) + (i & 2) * 4] = ay[i];
        }
    }
    PROF(23, tid >> 7);
    __threadfence();
    bar_sync(1, 256);
    if (tid == 0) {
        *flag = atomicAdd(&g_sync.ffn_ticket, 1u) == epoch * 4 + 3;
        __threadfence();
    }
    bar_sync(1, 256);
    if (*flag) {
        const float sg = bf_round(__fdividef(1.0f, 1.0f + __expf(-__ldcg(&g_r[row]))));
        const uint32_t xu[4] = {xrow.x, xrow.y, xrow.z, xrow.w};
        uint32_t o[4];
#pragma unroll
        for (int k = 0; k < 4; k++) {
            float y0 = 0.f, y1 = 0.f;
#pragma unroll
            for (int q = 0; q < 4; q++) {
                const float2 y = __ldcg(reinterpret_cast<const float2*>(&g_ypart[(q * 2 + w) * DM + ch * 8 + 2 * k]));
                y0 += y.x; y1 += y.y;
            }
            o[k] = pack_bf16(bf_lo(xu[k]) + bf_round(bf_round(y0) * sg), bf_hi(xu[k]) + bf_round(bf_round(y1) * sg));
        }
        g_routed[w * 128 + ch] = make_uint4(o[0], o[1], o[2], o[3]);
        if (ch == 0) g_sel[w] = row;
        bar_sync(1, 256);
        if (tid == 0) red_release(&g_sync.ffn_done);
    }
}

__device__ __forceinline__ uint32_t slab_addr(uint32_t stg, int lane, int s) {
    const int row = ((lane >> 3) & 1) * 8 + (lane & 7);
    const int chunk = 2 * (s & 3) + (lane >> 4);
    return stg + row * 128 + (s >> 2) * 8192 + ((chunk ^ (lane & 7)) << 4);
}

constexpr float SM_SCALE = 0.08838834764831845f * 1.4426950408889634f;
constexpr float SUM_HI = 1048576.f, SUM_LO = 1.0f / 1048576.f;

template <int I0, int I1, int J0>
__device__ __forceinline__ void mask_range(float (&S)[64], float limf) {
#pragma unroll
    for (int i = I0; i < I1; i++) {
        const int j = i >> 2;
        float t;
        asm("add.sat.f32 %0, %1, %2;" : "=f"(t) : "f"((float)(32 * (j >> 2) + 2 * (j & 3) + (i & 1) - (i & 2) * 4)), "f"(-limf));
        S[4 * J0 + i] = fmaf(t, -1e30f, S[4 * J0 + i]);
    }
}
template <int J0>
__device__ __forceinline__ void mask_half(float (&S)[64], float limf, int v) {
    asm volatile("" : "+f"(limf));
    if (v < 2) {
        mask_range<0, 16, J0>(S, limf);
#pragma unroll
        for (int i = 16; i < 32; i++) S[4 * J0 + i] = -1e30f;
    } else {
        mask_range<16, 32, J0>(S, limf);
    }
}
__device__ __forceinline__ void issue_qk(float (&S)[64], const uint32_t (&Q)[32], uint32_t d0) {
#pragma unroll
    for (int s = 0; s < 8; s++)
        wgmma_n128_rs<1>(S, Q[4 * s], Q[4 * s + 1], Q[4 * s + 2], Q[4 * s + 3], d0 + s * 128, s > 0);
}
__device__ __forceinline__ void issue_qk_half(float (&T)[32], const uint32_t (&Q)[32], uint32_t d0) {
#pragma unroll
    for (int s = 0; s < 8; s++) wgmma_n64_rs_tb(T, Q[4 * s], Q[4 * s + 1], Q[4 * s + 2], Q[4 * s + 3], d0 + s * 128, s > 0);
}
template <int H>
__device__ __forceinline__ void issue_pv(float (&O)[64], const uint32_t (&Pm)[32], uint32_t d0, int acc) {
#pragma unroll
    for (int s = 4 * H; s < 4 * H + 4; s++)
        wgmma_n128_rs<0>(O, Pm[4 * s], Pm[4 * s + 1], Pm[4 * s + 2], Pm[4 * s + 3], d0 + H * (PAGE >> 4) + (s & 3) * 2, s > 0 ? 1 : acc);
}
template <int J0, int J1>
__device__ __forceinline__ void exp_groups(const float (&S)[64], uint32_t (&Pm)[32], float (&sum)[2]) {
#pragma unroll
    for (int i = 2 * J0; i < 2 * J1; i++) asm volatile("" : "+r"(Pm[i])::"memory");
#pragma unroll
    for (int j = J0; j < J1; j++) {
        const float e0 = ex2(S[4 * j]), e1 = ex2(S[4 * j + 1]), e2 = ex2(S[4 * j + 2]), e3 = ex2(S[4 * j + 3]);
        sum[0] = (j ? sum[0] + e0 : e0) + e1;
        sum[1] = (j ? sum[1] + e2 : e2) + e3;
        Pm[2 * j] = pack_bf16(e0, e1);
        Pm[2 * j + 1] = pack_bf16(e2, e3);
    }
}
__device__ __forceinline__ void shift_rows(float (&S)[64], float d0, float d1) {
#pragma unroll
    for (int j = 0; j < 16; j++) {
        S[4 * j] -= d0; S[4 * j + 1] -= d0; S[4 * j + 2] -= d1; S[4 * j + 3] -= d1;
    }
}
__device__ constexpr int chunk_src(int i) { return 4 * (4 * (i >> 3) + (i & 3)) + 2 * ((i >> 2) & 1); }
enum : uint32_t { CTL_FIRST = 1, CTL_SWITCH = 2, CTL_LAST = 4, CTL_HALF = 128, CTL_MASKHI = 256, CTL_WOUT = 512, CTL_PVHALF = 1024, CTL_PVACC = 16384,
                  CTL_SHIFT = 32768 };
__device__ __forceinline__ float quad_sum(float v) {
    v += __shfl_xor_sync(~0u, v, 1);
    return v + __shfl_xor_sync(~0u, v, 2);
}

__device__ __forceinline__ void store_part(uint8_t* base, uint32_t row_bits, int p, const uint32_t (&pk)[64], uint64_t pol) {
    asm volatile("{\n.reg .b64 d0, d1;\nxor.b64 d0, %0, %1;\nxor.b64 d1, d0, 64;\n"
                 "TS: .branchtargets P0, P1, P2, P3, P4, P5, P6, P7;\n"
                 "brx.idx.uni %2, TS;\n"
                 "P0:\n st.global.cg.L2::cache_hint.v4.u32 [d0 + 0], {%3, %4, %5, %6}, %67;\n st.global.cg.L2::cache_hint.v4.u32 [d1 + 0], {%11, %12, %13, %14}, %67;\n bra.uni DONE;\n"
                 "P1:\n st.global.cg.L2::cache_hint.v4.u32 [d0 + 0], {%7, %8, %9, %10}, %67;\n st.global.cg.L2::cache_hint.v4.u32 [d1 + 0], {%15, %16, %17, %18}, %67;\n bra.uni DONE;\n"
                 "P2:\n st.global.cg.L2::cache_hint.v4.u32 [d0 + 16384], {%19, %20, %21, %22}, %67;\n st.global.cg.L2::cache_hint.v4.u32 [d1 + 16384], {%27, %28, %29, %30}, %67;\n bra.uni DONE;\n"
                 "P3:\n st.global.cg.L2::cache_hint.v4.u32 [d0 + 16384], {%23, %24, %25, %26}, %67;\n st.global.cg.L2::cache_hint.v4.u32 [d1 + 16384], {%31, %32, %33, %34}, %67;\n bra.uni DONE;\n"
                 "P4:\n st.global.cg.L2::cache_hint.v4.u32 [d0 + 65536], {%35, %36, %37, %38}, %67;\n st.global.cg.L2::cache_hint.v4.u32 [d1 + 65536], {%43, %44, %45, %46}, %67;\n bra.uni DONE;\n"
                 "P5:\n st.global.cg.L2::cache_hint.v4.u32 [d0 + 65536], {%39, %40, %41, %42}, %67;\n st.global.cg.L2::cache_hint.v4.u32 [d1 + 65536], {%47, %48, %49, %50}, %67;\n bra.uni DONE;\n"
                 "P6:\n st.global.cg.L2::cache_hint.v4.u32 [d0 + 81920], {%51, %52, %53, %54}, %67;\n st.global.cg.L2::cache_hint.v4.u32 [d1 + 81920], {%59, %60, %61, %62}, %67;\n bra.uni DONE;\n"
                 "P7:\n st.global.cg.L2::cache_hint.v4.u32 [d0 + 81920], {%55, %56, %57, %58}, %67;\n st.global.cg.L2::cache_hint.v4.u32 [d1 + 81920], {%63, %64, %65, %66}, %67;\n bra.uni DONE;\n"
                 "DONE:\n}\n"
                 ::"l"(base), "l"((uint64_t)((p & 1) ? row_bits : 0)), "r"(p), "r"(pk[0]), "r"(pk[1]), "r"(pk[2]), "r"(pk[3]), "r"(pk[4]), "r"(pk[5]), "r"(pk[6]), "r"(pk[7]), "r"(pk[8]), "r"(pk[9]), "r"(pk[10]), "r"(pk[11]), "r"(pk[12]), "r"(pk[13]), "r"(pk[14]), "r"(pk[15]), "r"(pk[16]), "r"(pk[17]), "r"(pk[18]), "r"(pk[19]), "r"(pk[20]), "r"(pk[21]), "r"(pk[22]), "r"(pk[23]), "r"(pk[24]), "r"(pk[25]), "r"(pk[26]), "r"(pk[27]), "r"(pk[28]), "r"(pk[29]), "r"(pk[30]), "r"(pk[31]), "r"(pk[32]), "r"(pk[33]), "r"(pk[34]), "r"(pk[35]), "r"(pk[36]), "r"(pk[37]), "r"(pk[38]), "r"(pk[39]), "r"(pk[40]), "r"(pk[41]), "r"(pk[42]), "r"(pk[43]), "r"(pk[44]), "r"(pk[45]), "r"(pk[46]), "r"(pk[47]), "r"(pk[48]), "r"(pk[49]), "r"(pk[50]), "r"(pk[51]), "r"(pk[52]), "r"(pk[53]), "r"(pk[54]), "r"(pk[55]), "r"(pk[56]), "r"(pk[57]), "r"(pk[58]), "r"(pk[59]), "r"(pk[60]), "r"(pk[61]), "r"(pk[62]), "r"(pk[63]), "l"(pol)
                 : "memory");
}

__device__ __forceinline__ void store_part4(uint8_t* d0, int p, const uint32_t (&pk)[64]) {
    asm volatile("{\n.reg .b64 d1;\nxor.b64 d1, %0, 64;\n"
                 "TS: .branchtargets P0, P1, P2, P3;\n"
                 "brx.idx.uni %1, TS;\n"
                 "P0:\n st.global.cg.v4.u32 [%0 + 0], {%2, %3, %4, %5};\n st.global.cg.v4.u32 [d1 + 0], {%10, %11, %12, %13};\n bra.uni DONE;\n"
                 "P1:\n st.global.cg.v4.u32 [%0 + 1024], {%6, %7, %8, %9};\n st.global.cg.v4.u32 [d1 + 1024], {%14, %15, %16, %17};\n bra.uni DONE;\n"
                 "P2:\n st.global.cg.v4.u32 [%0 + 16384], {%18, %19, %20, %21};\n st.global.cg.v4.u32 [d1 + 16384], {%26, %27, %28, %29};\n bra.uni DONE;\n"
                 "P3:\n st.global.cg.v4.u32 [%0 + 17408], {%22, %23, %24, %25};\n st.global.cg.v4.u32 [d1 + 17408], {%30, %31, %32, %33};\n bra.uni DONE;\n"
                 "DONE:\n}\n"
                 ::"l"(d0), "r"(p), "r"(pk[0]), "r"(pk[1]), "r"(pk[2]), "r"(pk[3]), "r"(pk[4]), "r"(pk[5]), "r"(pk[6]), "r"(pk[7]), "r"(pk[8]), "r"(pk[9]), "r"(pk[10]), "r"(pk[11]), "r"(pk[12]), "r"(pk[13]), "r"(pk[14]), "r"(pk[15]), "r"(pk[16]), "r"(pk[17]), "r"(pk[18]), "r"(pk[19]), "r"(pk[20]), "r"(pk[21]), "r"(pk[22]), "r"(pk[23]), "r"(pk[24]), "r"(pk[25]), "r"(pk[26]), "r"(pk[27]), "r"(pk[28]), "r"(pk[29]), "r"(pk[30]), "r"(pk[31])
                 : "memory");
}

__device__ __forceinline__ void consumer(uint32_t sb, int pair, int c, uint8_t* out, const uint8_t* x) {
    const int tid = threadIdx.x;
    const int warp = __shfl_sync(~0u, tid >> 5, 0);
    const int w = warp >> 2, v = warp & 3;
    const int lane = __shfl_sync(~0u, tid & 31, tid & 31);

    const uint32_t empty_rel = lane == 2 ? mapa(sb + BAR_EMPTYL, c) : mapa(sb + BAR_EMPTY, lane & 1);
    auto release = [&](uint32_t grp) {
        if (lane < 3) mbar_arrive_cluster(empty_rel + (grp & 7) * 8);
    };
    auto wait_full = [&](uint32_t grp) { mbar_wait(sb + BAR_FULL + (grp & 7) * 8, (grp >> 3) & 1); };

    uint32_t g = 0;
    const uint32_t stg = sb + SM_REGION + w * PAGE + v * 2048;
    const uint32_t chunk0 = (lane >> 2) * 128 + (((lane & 3) ^ (lane >> 2)) << 4);
    auto mark_done = [&](int odd) {
        __syncwarp();
        if (lane == 0) mbar_arrive(sb + BAR_DONE + odd * 8);
    };
    auto ctx_dst = [&](int rnd, int seg) {
        const int rb = query_rowblock(pair, c, w, seg);
        return ptr_off(g_ctx, ((rb >> 1) * 64 + (rnd * 16 + (pair >> 2)) * 2) * PAGE + (rb & 1) * 8192 + v * 2048);
    };

    uint32_t ctl_tab;
    {
        const int t = lane, firstB = 2 * attn_rowblock(pair, 0) + 2 - w;
        auto is_half = [&](int u) { return (u == firstB - 1 || u == 16) && c == (u >= firstB); };
        auto block = [&](int u) { return u + (w == 1 && u >= firstB); };
        auto place = [](int j) { return ((j & 15) << 3) | ((j - (j * 43 >> 8) * 6) << 11); };
        const int jv = min(2 * block(t - 1) + 2, 35), jk = t == 17 ? jv : max(2 * block(t) - 1, 0);
        const bool diag = t == firstB - 1 || t == 16;
        ctl_tab = ((t == 0 || t == firstB) ? CTL_FIRST : 0) | (t == firstB ? CTL_SWITCH : 0) | (t == 17 ? CTL_LAST : 0) |
                  (diag ? (is_half(t) ? CTL_HALF : CTL_MASKHI) : 0) | (t == firstB + 1 ? CTL_WOUT : 0) |
                  (is_half(t - 1) ? CTL_PVHALF : 0) | ((t == 1 || t == firstB + 1) ? 0 : CTL_PVACC) |
                  place(jk) | ((place(jv) | (t ? 3 : 0)) << 16);
    }

    uint32_t pk[64];
#pragma unroll
    for (int i = 0; i < 64; i++) pk[i] = 0;
    uint8_t* pend = nullptr;
    uint32_t prow = 0x400;
    auto write_part = [&](int p, uint64_t pol = POL_NORMAL) { store_part(pend, prow, p, pk, pol); };
    if (w == 1) bar_arrive(2, 256);

    for (int item = 0; item < 6; item++) {
        if ((0x1B >> item) & 1) {
            constexpr int nk = DC / 64;
            float acc[128];
            auto issue_kblock = [&](int first_acc) {
                wait_full(g);
                const uint32_t pg = sb + (g & 3) * (3 * PAGE);
                const uint64_t da = make_desc(pg + w * 8192, 16), db = make_desc(pg + PAGE, 16);
                wg_fence();
                wgmma_n256_ss(acc, da, db, first_acc);
                wgmma_n256_ss(acc, da + 128, db + 2, 1);
                wgmma_n256_ss(acc, da + 256, db + 4, 1);
                wgmma_n256_ss(acc, da + 384, db + 6, 1);
                wg_commit();
                g++;
            };
            if (item == 0) PROF(17, w);
            issue_kblock(0);
            if (item == 0) PROF(1, w);
            if (item == 0 && w == 0) PROF_GT(1);
            const int nparts = item == 0 ? 0 : (item == 3 ? 4 : 8);
            const int ln_row = (pair * 2 + c) * 16 + warp * 2;
            if (item == 0) {
                const uint8_t* src = ptr_off(x, ln_row * (DM * 2) + lane * 16);
#pragma unroll
                for (int i = 0; i < 8; i++) {
                    const uint4 t = __ldcg(reinterpret_cast<const uint4*>(src + i * 512));
                    pk[4 * i] = t.x; pk[4 * i + 1] = t.y; pk[4 * i + 2] = t.z; pk[4 * i + 3] = t.w;
                }
            }
#pragma unroll 1
            for (int kb = 1; kb < nk; kb++) {
                if (kb == nk - 1 && w == 1) bar_sync(4, 256);
                issue_kblock(1);
                if (kb == nk - 1 && w == 0) bar_arrive(4, 256);
                wg_wait<1>();
                release(g - 2);
                if (kb <= nparts) {
                    if (item == 4 && kb == 1) mbar_wait(sb + BAR_DEP + 16, 0);
                    write_part(kb - 1, item == 3 ? POL_FIRST : POL_NORMAL);
                    if (kb == nk - 1) write_part(nk - 1);
                    if (kb == nparts || kb == nk - 1) mark_done(item != 3);
                }
                if (g <= 8) {
                    float s[2], q[2];
                    if (g == 4) {
                        ln_sums<0>(pk, s[0], q[0]);
                        pk[32] = __float_as_uint(s[0]); pk[33] = __float_as_uint(q[0]);
                    }
                    if (g == 5) {
                        ln_sums<16>(pk, s[1], q[1]);
                        pk[34] = __float_as_uint(s[1]); pk[35] = __float_as_uint(q[1]);
                    }
                    if (g == 6) {
#pragma unroll
                        for (int r = 0; r < 2; r++) { s[r] = __uint_as_float(pk[32 + 2 * r]); q[r] = __uint_as_float(pk[33 + 2 * r]); }
                        const bool hi = lane & 16, od = lane & 8;
                        float a = hi ? s[1] : s[0], b = hi ? q[1] : q[0];
                        a += __shfl_xor_sync(~0u, hi ? s[0] : s[1], 16);
                        b += __shfl_xor_sync(~0u, hi ? q[0] : q[1], 16);
                        float t = od ? b : a;
                        t += __shfl_xor_sync(~0u, od ? a : b, 8);
#pragma unroll
                        for (int o = 4; o; o >>= 1) t += __shfl_xor_sync(~0u, t, o);
#pragma unroll
                        for (int r = 0; r < 2; r++) {
                            s[r] = __shfl_sync(~0u, t, 16 * r);
                            q[r] = __shfl_sync(~0u, t, 16 * r + 8);
                        }
                        ln_finish(s[0], q[0], pk[36], pk[37], pk[38]);
                        ln_finish(s[1], q[1], pk[39], pk[40], pk[41]);
                    }
                    if (g == 7) ln_apply<0>(pk, pk[36], pk[37], pk[38], ptr_off(g_xn, image_offset(ln_row, lane)));
                    if (g == 8) {
                        ln_apply<16>(pk, pk[39], pk[40], pk[41], ptr_off(g_xn, image_offset(ln_row + 1, lane)));
                        mark_done(0);
                    }
                }
            }
            wg_wait<0>();
            reg_fence(acc);
            release(g - 1);
            PROF(2 + 2 * item, w);
            if (w == 0) PROF_GT(2 + 2 * item);
#pragma unroll
            for (int i = 0; i < 64; i++) pk[i] = pack_bf16(acc[chunk_src(i)], acc[chunk_src(i) + 1]);
            const uint32_t vrow = (v >> 1) * 32 + (lane >> 3) * 8 + (v & 1) * 4 + ((lane >> 2) & 1);
            pend = ptr_off(g_kv, ((kv_head(pair) + (item == 1 || item == 4 ? 8 : 0)) * 16 + kv_tokens(pair) * 2) * 65536 + w * 8192 +
                                     (c ? 32768 + vrow * 128 + (((lane & 3) ^ (vrow & 7)) << 4) : v * 2048 + chunk0));
            prow = c ? 0x120 : 0x400;
            PROF(3 + 2 * item, w);
            continue;
        }

        float O[64], S[64];
        auto issue_q = [&](int first_acc) {
            wait_full(g);
            const uint32_t pg = sb + (g & 3) * (3 * PAGE);
            const uint64_t da = make_desc(pg + w * 8192, 16), db = make_desc(pg + 2 * PAGE, 8192);
            const uint64_t dab = make_desc(pg + PAGE + (1 - w) * 8192, 16);
            wg_fence();
#pragma unroll
            for (int q = 0; q < 4; q++) wgmma_n128_ss(S, da + 2 * q, db + 128 * q, q ? 1 : first_acc);
            wg_commit();
#pragma unroll
            for (int q = 0; q < 4; q++) wgmma_n128_ss(O, dab + 2 * q, db + 128 * q, q ? 1 : first_acc);
            wg_commit();
            g++;
        };
        issue_q(0);
#pragma unroll 1
        for (int kb = 1; kb < DM / 64; kb++) {
            if (kb == DM / 64 - 2 && w == 1) bar_sync(4, 256);
            issue_q(1);
            if (kb == DM / 64 - 1 && w == 0) bar_arrive(4, 256);
            wg_wait<2>();
            release(g - 2);
            if (kb <= 8) {
                write_part(kb - 1);
                if (kb == 8) mark_done(0);
            }
        }
        uint32_t Q[32], Pm[32];
#pragma unroll
        for (int i = 0; i < 32; i++) Pm[i] = pk[32 + i];
        float lim = (float)(v * 16 + (lane >> 2) - 8 * (lane & 3));
        float mc[2] = {0.f, 0.f}, l[2] = {0.f, 0.f}, scale[2] = {0.f, 0.f}, sum[2];
        uint32_t ctl = __shfl_sync(~0u, ctl_tab, 0), nxt = __shfl_sync(~0u, ctl_tab, 1);
        int t = 1;
        asm volatile("" : "+f"(lim), "+f"(mc[0]), "+f"(mc[1]), "+f"(l[0]), "+f"(l[1]), "+r"(ctl), "+r"(nxt), "+r"(t));
        wg_wait<1>();
        reg_fence(S);
#pragma unroll
        for (int i = 0; i < 32; i++) Q[i] = pack_bf16(S[2 * i] * SM_SCALE, S[2 * i + 1] * SM_SCALE);
        reg_fence(Q);
        wait_full(g);
        wg_wait<0>();
        reg_fence(O);
        release(g - 1);
        PROF(2 + 2 * item, w);
        if (w == 0) PROF_GT(2 + 2 * item);

        const uint32_t qaddr = stg + lane * 16;
        auto put_queries = [&](const float (&A)[64]) {
#pragma unroll
            for (int i = 0; i < 8; i++)
                sts128(qaddr + (i >> 2) * 8192 + (i & 3) * 512, pack_bf16(A[8 * i] * SM_SCALE, A[8 * i + 1] * SM_SCALE), pack_bf16(A[8 * i + 2] * SM_SCALE, A[8 * i + 3] * SM_SCALE),
                       pack_bf16(A[8 * i + 4] * SM_SCALE, A[8 * i + 5] * SM_SCALE), pack_bf16(A[8 * i + 6] * SM_SCALE, A[8 * i + 7] * SM_SCALE));
        };
        auto get_queries = [&]() {
#pragma unroll
            for (int i = 0; i < 8; i++) lds128(qaddr + (i >> 2) * 8192 + (i & 3) * 512, Q[4 * i], Q[4 * i + 1], Q[4 * i + 2], Q[4 * i + 3]);
        };
        const uint32_t kdesc0 = (uint32_t)make_desc(sb, PAGE), vdesc0 = (uint32_t)make_desc(sb, 16);
        auto wait_block = [&](uint32_t word) { mbar_wait(sb + BAR_FULL + (word & 56), (word >> 6) & 1); };
        auto write_out = [&](auto early) {
            uint8_t* dst = ctx_dst(item == 5, 0);
            uint8_t* d[2] = {ptr_off(dst, chunk0), ptr_off(dst, chunk0 ^ 64)};
#pragma unroll
            for (int i = early.value ? 0 : WN; i < (early.value ? WN : 8); i++) {
                const float sc = scale[i & 1];
                uint32_t q[4];
#pragma unroll
                for (int k = 0; k < 4; k++) q[k] = pack_bf16(O[chunk_src(4 * i + k)] * sc, O[chunk_src(4 * i + k) + 1] * sc);
                if (early.value && i > 0) {
#pragma unroll
                    for (int k = 0; k < 4; k++) O[4 * (i - 1) + k] = __uint_as_float(q[k]);
                }
                stg_hint(d[(i >> 1) & 1] + (i >> 2) * PAGE + (i & 1) * 1024, q[0], q[1], q[2], q[3], item == 2 ? POL_FIRST : POL_NORMAL);
            }
            if (!early.value) mark_done(1);
        };
        put_queries(O);
        bar_sync(2 + w, 256);
        if (!(ctl & CTL_HALF)) {
            wg_fence();
            issue_qk(S, Q, kdesc0);
            wg_commit();
            wg_fence();
            wg_commit();
            wg_commit();
            bar_arrive(3 - w, 256);
            wg_wait<2>();
            reg_fence(S);
        } else {
            float T[32];
            wg_fence();
            issue_qk_half(T, Q, kdesc0);
            wg_commit();
            wg_fence();
            wg_commit();
            wg_commit();
            bar_arrive(3 - w, 256);
            wg_wait<2>();
            reg_fence(T);
#pragma unroll
            for (int i = 0; i < 32; i++) S[i] = T[i];
        }
        for (;;) {
            const bool kready = mbar_try(sb + BAR_FULL + (nxt & 56), (nxt >> 6) & 1);
            if (ctl & (CTL_HALF | CTL_MASKHI | CTL_SHIFT)) {
                if (ctl & CTL_HALF) mask_half<0>(S, lim, v);
                if (ctl & CTL_MASKHI) mask_half<8>(S, lim, v);
                if (ctl & CTL_SHIFT) shift_rows(S, mc[0], mc[1]);
            }
            float early[4 * EARLY];
#pragma unroll
            for (int j = 0; j < EARLY; j++) {
#pragma unroll
                for (int i = 4 * j; i < 4 * j + 4; i++) early[i] = ex2(S[i]);
                sum[0] = (j ? sum[0] + early[4 * j] : early[4 * j]) + early[4 * j + 1];
                sum[1] = (j ? sum[1] + early[4 * j + 2] : early[4 * j + 2]) + early[4 * j + 3];
            }
            const uint32_t tie = __float_as_uint(sum[0]) & __float_as_uint(sum[1]) & (ctl & 0x80000000u);
            if (lane < 3) mbar_arrive_cluster(empty_rel + tie + (ctl & 56));
            wg_wait<1>();
#pragma unroll
            for (int j = 0; j < EARLY; j++) {
                asm volatile("" : "+r"(Pm[2 * j]), "+r"(Pm[2 * j + 1])::"memory");
                Pm[2 * j] = pack_bf16(early[4 * j], early[4 * j + 1]);
                Pm[2 * j + 1] = pack_bf16(early[4 * j + 2], early[4 * j + 3]);
            }
            exp_groups<EARLY, 8>(S, Pm, sum);
            const bool half = ctl & CTL_HALF;
            if (!half) {
                wg_wait<0>();
                reg_fence(O);
                if (lane < ((ctl >> 16) & 3)) mbar_arrive_cluster(empty_rel + ((ctl >> 16) & 56));
                exp_groups<8, 16>(S, Pm, sum);
            } else {
                asm volatile("wgmma.wait_group.sync.aligned 0;\n" ::: "memory");
                reg_fence(O);
                if (lane < ((ctl >> 16) & 3)) asm volatile("mbarrier.arrive.shared::cluster.b64 _, [%0];\n" ::"r"(empty_rel + ((ctl >> 16) & 56)) : "memory");
            }
            const bool over = !(sum[0] + sum[1] <= SUM_HI);
            if (__any_sync(~0u, over || !kready) || (((ctl & CTL_FIRST) | (nxt & (CTL_SWITCH | CTL_LAST | CTL_HALF))) != 0)) {
                bool bad = __any_sync(~0u, over);
                if (!kready) wait_block(nxt);
                const bool first = ctl & CTL_FIRST;
                if (first) {
                    uint32_t b0 = __ballot_sync(~0u, sum[0] >= SUM_LO), b1 = __ballot_sync(~0u, sum[1] >= SUM_LO);
                    b0 |= b0 >> 1; b1 |= b1 >> 1;
                    b0 |= b0 >> 2; b1 |= b1 >> 2;
                    bad |= (b0 & b1 & 0x11111111u) != 0x11111111u;
                }
                if (bad) {
                    float d0 = fmaxf(S[0], S[1]), d1 = fmaxf(S[2], S[3]);
#pragma unroll
                    for (int j = 1; j < 8; j++) {
                        d0 = fmaxf(d0, fmaxf(S[4 * j], S[4 * j + 1]));
                        d1 = fmaxf(d1, fmaxf(S[4 * j + 2], S[4 * j + 3]));
                    }
                    if (!half) {
#pragma unroll
                        for (int j = 8; j < 16; j++) {
                            d0 = fmaxf(d0, fmaxf(S[4 * j], S[4 * j + 1]));
                            d1 = fmaxf(d1, fmaxf(S[4 * j + 2], S[4 * j + 3]));
                        }
                    }
                    d0 = fmaxf(d0, __shfl_xor_sync(~0u, d0, 1));
                    d1 = fmaxf(d1, __shfl_xor_sync(~0u, d1, 1));
                    d0 = fmaxf(d0, __shfl_xor_sync(~0u, d0, 2));
                    d1 = fmaxf(d1, __shfl_xor_sync(~0u, d1, 2));
                    if (!first) {
                        d0 = fmaxf(d0, 0.f);
                        d1 = fmaxf(d1, 0.f);
                        const float a0 = ex2(-d0), a1 = ex2(-d1);
#pragma unroll
                        for (int j = 0; j < 16; j++) {
                            O[4 * j] *= a0; O[4 * j + 1] *= a0; O[4 * j + 2] *= a1; O[4 * j + 3] *= a1;
                        }
                        l[0] *= a0; l[1] *= a1;
                    }
                    mc[0] += d0; mc[1] += d1;
                    ctl_tab |= CTL_SHIFT;
                    nxt |= CTL_SHIFT;
                    shift_rows(S, d0, d1);
                    exp_groups<0, 8>(S, Pm, sum);
                    if (!half) exp_groups<8, 16>(S, Pm, sum);
                }
                if (ctl & CTL_SWITCH) write_out(std::true_type());
                if (nxt & CTL_LAST) break;
                if (nxt & CTL_SWITCH) {
                    get_queries();
                    nxt &= ~CTL_SHIFT;
                    ctl_tab &= ~CTL_SHIFT;
                }
                if (nxt & CTL_HALF) {
                    ctl = nxt;
                    float T[32];
                    bar_sync(2 + w, 256);
                    wg_fence();
                    issue_qk_half(T, Q, kdesc0 + (ctl & 0x3800));
                    wg_commit();
                    l[0] += sum[0]; l[1] += sum[1];
                    nxt = __shfl_sync(~0u, ctl_tab, ++t);
                    wait_block(ctl >> 16);
                    const uint32_t vdesc = vdesc0 + ((ctl >> 16) & 0x3800);
                    wg_fence();
                    issue_pv<0>(O, Pm, vdesc, ctl & CTL_PVACC);
                    wg_commit();
                    issue_pv<1>(O, Pm, vdesc, 1);
                    wg_commit();
                    bar_arrive(3 - w, 256);
                    wg_wait<2>();
                    reg_fence(T);
#pragma unroll
                    for (int i = 0; i < 32; i++) S[i] = T[i];
                    continue;
                }
            }
            ctl = nxt;
            bar_sync(2 + w, 256);
            wg_fence();
            issue_qk(S, Q, kdesc0 + (ctl & 0x3800));
            wg_commit();
            l[0] += sum[0]; l[1] += sum[1];
            nxt = __shfl_sync(~0u, ctl_tab, ++t);
            if (ctl & (CTL_SWITCH | CTL_WOUT)) {
                if (ctl & CTL_SWITCH) {
                    scale[0] = rcp_approx(quad_sum(l[0]));
                    scale[1] = rcp_approx(quad_sum(l[1]));
                    l[0] = l[1] = mc[0] = mc[1] = 0.f;
                    if (w == 1) { release((ctl >> 3) - 2); release((ctl >> 3) + 1); }
                } else {
                    write_out(std::false_type());
                }
            }
            wait_block(ctl >> 16);
            const uint32_t vdesc = vdesc0 + ((ctl >> 16) & 0x3800);
            if (!(ctl & CTL_PVHALF)) {
                wg_fence();
                issue_pv<0>(O, Pm, vdesc, ctl & CTL_PVACC);
                wg_commit();
                issue_pv<1>(O, Pm, vdesc, 1);
                wg_commit();
            } else {
                wg_fence();
                issue_pv<0>(O, Pm, vdesc, ctl & CTL_PVACC);
                wg_commit();
                wg_commit();
            }
            bar_arrive(3 - w, 256);
            wg_wait<2>();
            reg_fence(S);
        }
        g += 36;
        const uint32_t vdesc = vdesc0 + (nxt & 0x3800);
        if (nxt & CTL_PVHALF) {
            wg_fence();
            issue_pv<0>(O, Pm, vdesc, nxt & CTL_PVACC);
            wg_commit();
        } else {
            wg_fence();
            issue_pv<0>(O, Pm, vdesc, nxt & CTL_PVACC);
            issue_pv<1>(O, Pm, vdesc, 1);
            wg_commit();
        }
        l[0] += sum[0]; l[1] += sum[1];
        ctl_tab = (ctl_tab & ~(0x00780078u | CTL_SHIFT)) | ((ctl_tab + 0x00200020u) & 0x00780078u);
        const float i0 = rcp_approx(quad_sum(l[0])), i1 = rcp_approx(quad_sum(l[1]));
        const uint32_t tie = __float_as_uint(i0) & __float_as_uint(i1) & (nxt & 0x80000000u);
        if (lane + tie < (w ? 0 : 3)) mbar_arrive_cluster(empty_rel + ((g - 3) & 7) * 8);
        wg_wait<0>();
        reg_fence(O);
        if (w == 0) release(g - 2);
        release(g - 1);
#pragma unroll
        for (int i = 0; i < 32; i++) {
            const float sc = (i & 4) ? i1 : i0;
            pk[i] = pack_bf16(O[chunk_src(i)] * sc, O[chunk_src(i) + 1] * sc);
        }
        pend = ptr_off(ctx_dst(item == 5, 1), chunk0);
        prow = 0x400;
#pragma unroll
        for (int i = 32; i < 64; i++) pk[i] = Pm[i - 32];
        PROF(3 + 2 * item, w);
        if (w == 0) PROF_GT(3 + 2 * item);
    }

    float acc[64];
    uint32_t slot = 0;
    auto issue_out = [&](int first_acc) {
        wait_full(g);
        const uint64_t da = make_desc(sb + slot + w * 8192, 16), db = make_desc(sb + slot + PAGE, 8192);
        wg_fence();
#pragma unroll
        for (int q = 0; q < 4; q++) wgmma_n128_ss(acc, da + 2 * q, db + 128 * q, q ? 1 : first_acc);
        wg_commit();
        g++;
        slot = slot == SM_REGION - 2 * PAGE ? 0 : slot + 2 * PAGE;
    };
    issue_out(0);
#pragma unroll 1
    for (int kb = 1; kb < 64 - PEEL; kb++) {
        issue_out(1);
        wg_wait<1>();
        release(g - 2);
        if (kb <= 8 && !(kb & 1)) {
            store_part4(pend, (kb >> 1) - 1, pk);
            if (kb == 8) mark_done(0);
        }
        if (kb >= 32 - PEEL && ((kb + PEEL) & 3) == 2 * w) {
            uint32_t u0, u1, u2, u3;
            const uint32_t a = stg + ((kb + PEEL) & 16) * 512 + ((kb + PEEL) & 12) * 128 + lane * 16;
            mbar_wait(sb + BAR_G + w * 8, 0);
            lds128(a, u0, u1, u2, u3);
            sts128(a, pack_bf16(silu_f(bf_lo(u0)), silu_f(bf_hi(u0))), pack_bf16(silu_f(bf_lo(u1)), silu_f(bf_hi(u1))),
                   pack_bf16(silu_f(bf_lo(u2)), silu_f(bf_hi(u2))), pack_bf16(silu_f(bf_lo(u3)), silu_f(bf_hi(u3))));
        }
    }
    const uint32_t goff = (out_rows(pair) * 256 + c * 128 + w * 64 + v * 16 + (lane >> 3)) * (DM * 2) +
                          out_cols(pair) * 128 + (((lane & 7) ^ (lane >> 3)) << 4);
    uint32_t xr[32], gr[32];
    {
        const uint8_t* src[2] = {ptr_off(x, goff), ptr_off(x, goff ^ 64)};
#pragma unroll
        for (int i = 0; i < 8; i++) {
            const uint4 t = ldg_hint(src[i & 1] + (i & 3) * (4 * DM * 2) + (i >> 2) * 128, POL_FIRST);
            xr[4 * i] = t.x; xr[4 * i + 1] = t.y; xr[4 * i + 2] = t.z; xr[4 * i + 3] = t.w;
        }
    }
#pragma unroll 1
    for (int i = 0; i < PEEL; i++) {
        if (i == PEEL - STAG && w == 1) bar_sync(4, 256);
        issue_out(1);
        if (i == PEEL - 1 && w == 0) bar_arrive(4, 256);
        wg_wait<1>();
    }
    asm volatile("barrier.cluster.arrive.relaxed.aligned;" ::: "memory");
#pragma unroll
    for (int i = 0; i < 8; i++) lds128(stg + (i >> 2) * 8192 + (i & 3) * 512 + lane * 16, gr[4 * i], gr[4 * i + 1], gr[4 * i + 2], gr[4 * i + 3]);
    uint8_t* dst[2] = {ptr_off(out, goff), ptr_off(out, goff ^ 64)};
    __syncwarp();
    wg_wait<0>();
    reg_fence(acc);
    PROF(14, w);
    if (w == 0) PROF_GT(14);
#pragma unroll
    for (int s = 0; s < 8; s++)
        stmatrix_x4(slab_addr(stg, lane, s), pack_bf16(acc[8 * s], acc[8 * s + 1]), pack_bf16(acc[8 * s + 2], acc[8 * s + 3]),
                    pack_bf16(acc[8 * s + 4], acc[8 * s + 5]), pack_bf16(acc[8 * s + 6], acc[8 * s + 7]));
    __syncwarp();
    uint32_t o[32];
#pragma unroll
    for (int i = 0; i < 8; i++) lds128(stg + (i >> 2) * 8192 + (i & 3) * 512 + lane * 16, o[4 * i], o[4 * i + 1], o[4 * i + 2], o[4 * i + 3]);
#pragma unroll
    for (int i = 0; i < 8; i++) {
#pragma unroll
        for (int k = 0; k < 4; k++) xr[4 * i + k] = bf2_add(xr[4 * i + k], bf2_mul(o[4 * i + k], gr[4 * i + k]));
        __stcg(reinterpret_cast<uint4*>(dst[i & 1] + (i & 3) * (4 * DM * 2) + (i >> 2) * 128), make_uint4(xr[4 * i], xr[4 * i + 1], xr[4 * i + 2], xr[4 * i + 3]));
    }
    PROF(28, w);
}

__global__ void __cluster_dims__(2, 1, 1) __launch_bounds__(384, 1)
fused_kernel(const __grid_constant__ CUtensorMap m_ckv, const __grid_constant__ CUtensorMap m_wuk,
             const __grid_constant__ CUtensorMap m_wuv, const __grid_constant__ CUtensorMap m_wq,
             const __grid_constant__ CUtensorMap m_wo, const __grid_constant__ CUtensorMap m_gate,
             const __grid_constant__ CUtensorMap m_up, const __grid_constant__ CUtensorMap m_down, const Params P) {
    extern __shared__ __align__(1024) uint8_t smem[];
    const uint32_t sb = __shfl_sync(~0u, smem_u32(smem), 0);
    const int tid = threadIdx.x;
    const int cl = blockIdx.x >> 1, c = blockIdx.x & 1;
    const int pair = cl >= 64 ? cl : cl < 4 ? cl * 16 + 15 : cl < 36 ? ((cl - 4) >> 3) * 16 + ((cl - 4) & 7)
                                                                    : ((cl - 36) / 7) * 16 + 8 + (cl - 36) % 7;
    const bool starter = tid == 256 && pair < NMAIN / 2;
    const CUtensorMap* m_wu = c ? &m_wuv : &m_wuk;
    if (tid == 256) {
        mbar_init(sb + BAR_FULL, 1);
        if (starter) {
            asm volatile("fence.mbarrier_init.release.cluster;" ::: "memory");
            mbar_expect_tx(sb + BAR_FULL, 3 * PAGE);
            tma_3d(sb, m_wu, 0, 0, kv_head(pair) * 2, sb + BAR_FULL);
            tma_3d(sb + PAGE, &m_ckv, 0, kv_tokens(pair) * 256, 0, sb + BAR_FULL);
            tma_3d(sb + 2 * PAGE, &m_ckv, 0, kv_tokens(pair) * 256 + 128, 0, sb + BAR_FULL);
        }
#pragma unroll
        for (int i = 1; i < NBAR; i++) mbar_init(sb + SM_BAR + i * 8, (i >> 3) == 1 ? 16 : i >= 25 ? 8 : 1);
        asm volatile("fence.mbarrier_init.release.cluster;" ::: "memory");
    }
    if (starter) {
#pragma unroll 1
        for (int kb = 1; kb < 4; kb++) mbar_expect_tx(sb + BAR_FULL + kb * 8, 3 * PAGE);
        tma_3d(sb + 3 * PAGE, m_wu, 0, 64, kv_head(pair) * 2, sb + BAR_FULL + 8);
    }
    PROF(18, (tid >> 7) & 1);
    __syncthreads();
    cluster_sync();
    PROF(22, (tid >> 7) & 1);
    PROF(19, (tid >> 7) & 1);
    const int warp = __shfl_sync(~0u, tid >> 5, 0), lane = tid & 31;
    auto dump_prof = [&]() {
    };
    if (pair >= NMAIN / 2) {
        if (warp < 8) ffn_cta(smem, sb, blockIdx.x - NMAIN, __ldcg(&g_sync.done) / NCTA, P.w_r);
        else if (tid == 256) ffn_producer(sb, blockIdx.x - NMAIN, &m_gate, &m_up, &m_down);
        __syncwarp();
        PROF(29, tid >> 7);
        cluster_sync();
        if (tid == 0) atomicAdd(&g_sync.done, 1u);
        if (warp < 8) dump_prof();
    } else if (warp < 8) {
        asm volatile("setmaxnreg.inc.sync.aligned.u32 232;");
        consumer(sb, pair, c, P.out, (const uint8_t*)P.x);
        PROF(29, tid >> 7);
        asm volatile("barrier.cluster.wait.aligned;" ::: "memory");
        dump_prof();
    } else {
        asm volatile("setmaxnreg.dec.sync.aligned.u32 40;");
        if (starter) {
#pragma unroll 1
            for (int kb = 1; kb < 4; kb++) {
                if (kb > 1) tma_3d(sb + kb * (3 * PAGE), m_wu, 0, kb * 64, kv_head(pair) * 2, sb + BAR_FULL + kb * 8);
                tma_3d_mc(sb + kb * (3 * PAGE) + (1 + c) * PAGE, &m_ckv, 0, kv_tokens(pair) * 256 + c * 128, kb, sb + BAR_FULL + kb * 8);
            }
        }
        if (warp == 10) {
            sync_helper(sb, lane, pair, c);
        } else if (warp & 1) {
            fetch_helper((warp & 2) ? P.w_uv : P.w_uk, sb, (warp >> 1) & 1, lane, pair, c);
        } else {
            producer(P, sb, pair, c, &m_ckv, m_wu, &m_wq, &m_wo);
        }
        bar_sync(6, 128);
        if (tid == 256) atomicAdd(&g_sync.done, 1u);
        cluster_sync();
    }
}

typedef CUresult (*EncodeFn)(CUtensorMap*, CUtensorMapDataType, cuuint32_t, void*, const cuuint64_t*, const cuuint64_t*,
                             const cuuint32_t*, const cuuint32_t*, CUtensorMapInterleave, CUtensorMapSwizzle,
                             CUtensorMapL2promotion, CUtensorMapFloatOOBfill);

void make_map_w(EncodeFn fn, CUtensorMap* m, const void* ptr, int rows, int cols, int blocks, int box_rows = 32) {
    cuuint64_t dims[3] = {64, (cuuint64_t)rows, (cuuint64_t)cols / 64};
    cuuint64_t strides[2] = {(cuuint64_t)cols * 2, 128};
    cuuint32_t box[3] = {64, (cuuint32_t)box_rows, (cuuint32_t)blocks};
    cuuint32_t es[3] = {1, 1, 1};
    fn(m, CU_TENSOR_MAP_DATA_TYPE_BFLOAT16, 3, const_cast<void*>(ptr), dims, strides, box, es, CU_TENSOR_MAP_INTERLEAVE_NONE,
       CU_TENSOR_MAP_SWIZZLE_128B, CU_TENSOR_MAP_L2_PROMOTION_L2_256B, CU_TENSOR_MAP_FLOAT_OOB_FILL_NONE);
}

}

extern "C" void kernel_launch(void* const* d_in, const int* in_sizes, int n_in, void* d_out, int out_size) {
    static EncodeFn fn = nullptr;
    if (!fn) {
        void* f = nullptr;
        cudaDriverEntryPointQueryResult qr;
        cudaGetDriverEntryPoint("cuTensorMapEncodeTiled", &f, cudaEnableDefault, &qr);
        fn = (EncodeFn)f;
        cudaFuncSetAttribute(fused_kernel, cudaFuncAttributeMaxDynamicSharedMemorySize, SMEM_BYTES);
    }
    CUtensorMap m_ckv, m_wuk, m_wuv, m_wq, m_wo, m_gate, m_up, m_down;
    make_map_w(fn, &m_gate, d_in[8], DM, FF, FS / 64, 16);
    make_map_w(fn, &m_up, d_in[9], DM, FF, FS / 64, 16);
    make_map_w(fn, &m_down, d_in[10], FF, DM, DM / 64, 16);
    make_map_w(fn, &m_ckv, d_in[1], SEQ, DC, 1, 128);
    make_map_w(fn, &m_wq, d_in[2], DM, NH * 128, 1, 64);
    make_map_w(fn, &m_wuk, d_in[3], DC, NH * 128, 2, 64);
    make_map_w(fn, &m_wuv, d_in[4], DC, NH * 128, 2, 64);
    make_map_w(fn, &m_wo, d_in[5], NH * 128, DM, 1, 64);
    Params P;
    P.x = (const __nv_bfloat16*)d_in[0];
    P.w_r = (const __nv_bfloat16*)d_in[7];
    P.c_kv = (const uint8_t*)d_in[1];
    P.w_uk = (const uint8_t*)d_in[3];
    P.w_uv = (const uint8_t*)d_in[4];
    P.out = (uint8_t*)d_out;
    fused_kernel<<<NCTA, 384, SMEM_BYTES>>>(m_ckv, m_wuk, m_wuv, m_wq, m_wo, m_gate, m_up, m_down, P);
}
```

```cpp
#include <cuda_runtime.h>
#include <cuda_bf16.h>
#include <cuda.h>
#include <stdint.h>
#include <type_traits>

namespace {

constexpr int SEQ = 2048, DM = 1024, NH = 32, DC = 512, FF = 3584;
constexpr int PAGE = 16384;
constexpr int NRING = 12;
constexpr int NCTA = 132, NMAIN = 128;
constexpr uint32_t SM_REGION = NRING * PAGE;
constexpr uint32_t SM_BAR = (NRING + 2) * PAGE;
constexpr uint32_t BAR_FULL = SM_BAR, BAR_EMPTY = SM_BAR + 64;
constexpr uint32_t BAR_DEP = SM_BAR + 128;
constexpr uint32_t BAR_G = SM_BAR + 184;
constexpr uint32_t BAR_DONE = SM_BAR + 200;
constexpr uint32_t BAR_EMPTYL = SM_BAR + 216;
constexpr int NBAR = 35;
constexpr uint32_t SM_PROF = SM_BAR + 320;
constexpr int SMEM_BYTES = SM_PROF + 512;
constexpr uint32_t SPIN_LIMIT = 1u << 16;
constexpr uint32_t POLL_MASK = 7;
constexpr int EARLY = 2;
constexpr int WN = 5;
constexpr int PEEL = 5, STAG = 3;

struct SyncBlock {
    unsigned done;       unsigned pad0[31];
    unsigned ln;         unsigned pad1[31];
    unsigned router;     unsigned pad4[31];
    unsigned ffn_ticket; unsigned pad2[31];
    unsigned ffn_done;   unsigned pad3[31];
    unsigned kv[NH * 8];
    unsigned kvfree[16 * 8];
    unsigned ctx[32 * NH];
};

__device__ __align__(1024) uint8_t g_xn[8 * 16 * 4 * 8192];
__device__ __align__(4096) uint8_t g_kv[16 * 16 * 65536];
__device__ __align__(4096) uint8_t g_ctx[16 * 64 * 16384];
__device__ __align__(16) uint4 g_routed[2 * 128];
__device__ int g_sel[2];
__device__ __align__(16) float g_r[SEQ];
__device__ __align__(16) float g_ypart[4 * 2 * DM];
__device__ SyncBlock g_sync;

__device__ __forceinline__ uint32_t smem_u32(const void* p) { return (uint32_t)__cvta_generic_to_shared(p); }

__device__ __forceinline__ void mbar_init(uint32_t bar, uint32_t count) {
    asm volatile("mbarrier.init.shared::cta.b64 [%0], %1;" ::"r"(bar), "r"(count) : "memory");
}
#define MBAR_WAIT_ASM(HINT, LIMIT)                                                                  \
    asm volatile("{\n.reg .pred p;\n.reg .u32 n;\nmov.u32 n, 0;\n"                                  \
                 "WAIT_LOOP:\n"                                                                     \
                 "mbarrier.try_wait.parity.shared::cta.b64 p, [%0], %1" HINT ";\n"                  \
                 "@p bra WAIT_DONE;\n"                                                              \
                 "add.u32 n, n, 1;\n"                                                               \
                 "setp.lt.u32 p, n, " LIMIT ";\n"                                                   \
                 "@p bra WAIT_LOOP;\n"                                                              \
                 "WAIT_DONE:\n}\n" ::"r"(bar), "r"(parity) : "memory")
__device__ __forceinline__ void mbar_wait(uint32_t bar, uint32_t parity) { MBAR_WAIT_ASM("", "131072"); }
__device__ __forceinline__ void mbar_sleep(uint32_t bar, uint32_t parity) { MBAR_WAIT_ASM(", 2000", "8192"); }
__device__ __forceinline__ bool mbar_try(uint32_t bar, uint32_t parity) {
    uint32_t ok;
    asm volatile("{\n.reg .pred p;\nmbarrier.try_wait.parity.shared::cta.b64 p, [%1], %2;\nselp.u32 %0, 1, 0, p;\n}\n"
                 : "=r"(ok) : "r"(bar), "r"(parity) : "memory");
    return ok;
}
__device__ __forceinline__ bool mbar_test(uint32_t bar, uint32_t parity) {
    uint32_t ok;
    asm volatile("{\n.reg .pred p;\nmbarrier.test_wait.parity.shared::cta.b64 p, [%1], %2;\nselp.u32 %0, 1, 0, p;\n}\n"
                 : "=r"(ok) : "r"(bar), "r"(parity) : "memory");
    return ok;
}
__device__ __forceinline__ bool elect_one() {
    uint32_t ok;
    asm volatile("{\n.reg .pred p;\nelect.sync _|p, 0xffffffff;\nselp.u32 %0, 1, 0, p;\n}\n" : "=r"(ok));
    return ok;
}
__device__ __forceinline__ void mbar_arrive(uint32_t bar) {
    asm volatile("mbarrier.arrive.shared::cta.b64 _, [%0];" ::"r"(bar) : "memory");
}
__device__ __forceinline__ void mbar_expect_tx(uint32_t bar, uint32_t bytes) {
    asm volatile("mbarrier.arrive.expect_tx.shared::cta.b64 _, [%0], %1;" ::"r"(bar), "r"(bytes) : "memory");
}
__device__ __forceinline__ void mbar_arrive_cluster(uint32_t cluster_addr) {
    asm volatile("mbarrier.arrive.shared::cluster.b64 _, [%0];" ::"r"(cluster_addr) : "memory");
}
__device__ __forceinline__ uint32_t mapa(uint32_t addr, uint32_t rank) {
    uint32_t r;
    asm("mapa.shared::cluster.u32 %0, %1, %2;" : "=r"(r) : "r"(addr), "r"(rank));
    return r;
}
__device__ __forceinline__ void tma_3d(uint32_t dst, const CUtensorMap* m, int c0, int c1, int c2, uint32_t bar) {
    asm volatile("cp.async.bulk.tensor.3d.shared::cluster.global.mbarrier::complete_tx::bytes [%0], [%1, {%3, %4, %5}], [%2];"
                 ::"r"(dst), "l"(m), "r"(bar), "r"(c0), "r"(c1), "r"(c2) : "memory");
}
__device__ __forceinline__ void tma_3d_hint(uint32_t dst, const CUtensorMap* m, int c0, int c1, int c2, uint32_t bar, uint64_t pol) {
    asm volatile("cp.async.bulk.tensor.3d.shared::cluster.global.mbarrier::complete_tx::bytes.L2::cache_hint [%0], [%1, {%3, %4, %5}], [%2], %6;"
                 ::"r"(dst), "l"(m), "r"(bar), "r"(c0), "r"(c1), "r"(c2), "l"(pol) : "memory");
}
__device__ __forceinline__ void tma_3d_mc(uint32_t dst, const CUtensorMap* m, int c0, int c1, int c2, uint32_t bar) {
    asm volatile("cp.async.bulk.tensor.3d.shared::cluster.global.mbarrier::complete_tx::bytes.multicast::cluster [%0], [%1, {%3, %4, %5}], [%2], %6;"
                 ::"r"(dst), "l"(m), "r"(bar), "r"(c0), "r"(c1), "r"(c2), "h"((uint16_t)3) : "memory");
}
__device__ __forceinline__ void bulk_load(uint32_t dst, const void* src, uint32_t bytes, uint32_t bar) {
    asm volatile("cp.async.bulk.shared::cluster.global.mbarrier::complete_tx::bytes [%0], [%1], %2, [%3];"
                 ::"r"(dst), "l"(src), "r"(bytes), "r"(bar) : "memory");
}
__device__ __forceinline__ void cp_async16(uint32_t dst, const void* src) {
    asm volatile("cp.async.cg.shared.global [%0], [%1], 16;" ::"r"(dst), "l"(src) : "memory");
}
__device__ __forceinline__ void bulk_load_mc(uint32_t dst, const void* src, uint32_t bytes, uint32_t bar) {
    asm volatile("cp.async.bulk.shared::cluster.global.mbarrier::complete_tx::bytes.multicast::cluster [%0], [%1], %2, [%3], %4;"
                 ::"r"(dst), "l"(src), "r"(bytes), "r"(bar), "h"((uint16_t)3) : "memory");
}
__device__ __forceinline__ void fence_async_smem() { asm volatile("fence.proxy.async.shared::cta;" ::: "memory"); }
__device__ __forceinline__ void prefetch_map(const CUtensorMap* m) {
    asm volatile("prefetch.tensormap [%0];" ::"l"(m) : "memory");
}
__device__ __forceinline__ void red_release(unsigned* p) {
    asm volatile("red.release.gpu.global.add.u32 [%0], 1;" ::"l"(p) : "memory");
}
__device__ __forceinline__ unsigned ld_relaxed(const unsigned* p) {
    unsigned v;
    asm volatile("ld.relaxed.gpu.global.u32 %0, [%1];" : "=r"(v) : "l"(p) : "memory");
    return v;
}
__device__ __forceinline__ void wait_counter(const unsigned* p, unsigned target) {
    for (uint32_t n = 0; (int)(ld_relaxed(p) - target) < 0 && n < SPIN_LIMIT; n++) __nanosleep(100);
    asm volatile("fence.acquire.gpu;" ::: "memory");
    asm volatile("fence.proxy.async.global;" ::: "memory");
}
__device__ __forceinline__ void bar_sync(int id, int n) { asm volatile("bar.sync %0, %1;" ::"r"(id), "r"(n) : "memory"); }
__device__ __forceinline__ void bar_arrive(int id, int n) { asm volatile("bar.arrive %0, %1;" ::"r"(id), "r"(n) : "memory"); }
__device__ __forceinline__ void cluster_sync() {
    asm volatile("barrier.cluster.arrive.relaxed.aligned;\nbarrier.cluster.wait.aligned;" ::: "memory");
}
__device__ __forceinline__ void wg_fence() { asm volatile("wgmma.fence.sync.aligned;" ::: "memory"); }
__device__ __forceinline__ void wg_commit() { asm volatile("wgmma.commit_group.sync.aligned;" ::: "memory"); }
template <int N> __device__ __forceinline__ void wg_wait() { asm volatile("wgmma.wait_group.sync.aligned %0;" ::"n"(N) : "memory"); }
template <int N> __device__ __forceinline__ void reg_fence(float (&a)[N]) {
#pragma unroll
    for (int i = 0; i < N; i++) asm volatile("" : "+f"(a[i])::"memory");
}
template <int N> __device__ __forceinline__ void reg_fence(uint32_t (&a)[N]) {
#pragma unroll
    for (int i = 0; i < N; i++) asm volatile("" : "+r"(a[i])::"memory");
}
__device__ __forceinline__ uint32_t pack_bf16(float lo, float hi) {
    uint32_t r;
    asm("cvt.rn.bf16x2.f32 %0, %1, %2;" : "=r"(r) : "f"(hi), "f"(lo));
    return r;
}
__device__ __forceinline__ float bf_lo(uint32_t v) { return __uint_as_float(v << 16); }
__device__ __forceinline__ float bf_hi(uint32_t v) { return __uint_as_float(v & 0xffff0000u); }
__device__ __forceinline__ float bf_round(float v) { return __bfloat162float(__float2bfloat16_rn(v)); }
__device__ __forceinline__ float ex2(float v) {
    float r;
    asm("ex2.approx.ftz.f32 %0, %1;" : "=f"(r) : "f"(v));
    return r;
}
__device__ __forceinline__ float sqrt_approx(float v) {
    float r;
    asm("sqrt.approx.ftz.f32 %0, %1;" : "=f"(r) : "f"(v));
    return r;
}
__device__ __forceinline__ float rcp_approx(float v) {
    float r;
    asm("rcp.approx.ftz.f32 %0, %1;" : "=f"(r) : "f"(v));
    return r;
}
__device__ __forceinline__ float silu_f(float v) { return v * rcp_approx(1.0f + ex2(v * -1.4426950408889634f)); }
__device__ __forceinline__ void stmatrix_x4(uint32_t addr, uint32_t r0, uint32_t r1, uint32_t r2, uint32_t r3) {
    asm volatile("stmatrix.sync.aligned.m8n8.x4.shared.b16 [%0], {%1, %2, %3, %4};"
                 ::"r"(addr), "r"(r0), "r"(r1), "r"(r2), "r"(r3) : "memory");
}
__device__ __forceinline__ void sts128(uint32_t addr, uint32_t r0, uint32_t r1, uint32_t r2, uint32_t r3) {
    asm volatile("st.shared.v4.b32 [%0], {%1, %2, %3, %4};" ::"r"(addr), "r"(r0), "r"(r1), "r"(r2), "r"(r3) : "memory");
}
__device__ __forceinline__ void lds128(uint32_t addr, uint32_t& r0, uint32_t& r1, uint32_t& r2, uint32_t& r3) {
    asm volatile("ld.shared.v4.b32 {%0, %1, %2, %3}, [%4];" : "=r"(r0), "=r"(r1), "=r"(r2), "=r"(r3) : "r"(addr) : "memory");
}
__device__ __forceinline__ uint32_t bf2_mul(uint32_t a, uint32_t b) {
    uint32_t r;
    asm("mul.rn.bf16x2 %0, %1, %2;" : "=r"(r) : "r"(a), "r"(b));
    return r;
}
__device__ __forceinline__ uint32_t bf2_add(uint32_t a, uint32_t b) {
    uint32_t r;
    asm("add.rn.bf16x2 %0, %1, %2;" : "=r"(r) : "r"(a), "r"(b));
    return r;
}
constexpr uint64_t POL_FIRST = 0x12F0000000000000ull, POL_NORMAL = 0x16F0000000000000ull;
__device__ __forceinline__ uint4 ldg_hint(const void* p, uint64_t pol) {
    uint4 v;
    asm volatile("ld.global.cg.L2::cache_hint.v4.u32 {%0, %1, %2, %3}, [%4], %5;" : "=r"(v.x), "=r"(v.y), "=r"(v.z), "=r"(v.w) : "l"(p), "l"(pol));
    return v;
}
__device__ __forceinline__ void stg_hint(void* p, uint32_t r0, uint32_t r1, uint32_t r2, uint32_t r3, uint64_t pol) {
    asm volatile("st.global.cg.L2::cache_hint.v4.u32 [%0], {%1, %2, %3, %4}, %5;" ::"l"(p), "r"(r0), "r"(r1), "r"(r2), "r"(r3), "l"(pol) : "memory");
}

__device__ __forceinline__ uint64_t make_desc(uint32_t addr, uint32_t lbo_bytes) {
    return (uint64_t)((addr & 0x3FFFF) >> 4) | ((uint64_t)(lbo_bytes >> 4) << 16) | ((uint64_t)(1024 >> 4) << 32) | (1ull << 62);
}

__device__ __forceinline__ void wgmma_n256_ss(float (&d)[128], uint64_t da, uint64_t db, int acc) {
    asm volatile(
        "{\n.reg .pred p;\nsetp.ne.b32 p, %130, 0;\n"
        "wgmma.mma_async.sync.aligned.m64n256k16.f32.bf16.bf16 {"
        "%0, %1, %2, %3, %4, %5, %6, %7, %8, %9, %10, %11, %12, %13, %14, %15, "
        "%16, %17, %18, %19, %20, %21, %22, %23, %24, %25, %26, %27, %28, %29, %30, %31, "
        "%32, %33, %34, %35, %36, %37, %38, %39, %40, %41, %42, %43, %44, %45, %46, %47, "
        "%48, %49, %50, %51, %52, %53, %54, %55, %56, %57, %58, %59, %60, %61, %62, %63, "
        "%64, %65, %66, %67, %68, %69, %70, %71, %72, %73, %74, %75, %76, %77, %78, %79, "
        "%80, %81, %82, %83, %84, %85, %86, %87, %88, %89, %90, %91, %92, %93, %94, %95, "
        "%96, %97, %98, %99, %100, %101, %102, %103, %104, %105, %106, %107, %108, %109, %110, %111, "
        "%112, %113, %114, %115, %116, %117, %118, %119, %120, %121, %122, %123, %124, %125, %126, %127"
        "}, %128, %129, p, 1, 1, 1, 0;\n}\n"
        :
        "+f"(d[0]), "+f"(d[1]), "+f"(d[2]), "+f"(d[3]), "+f"(d[4]), "+f"(d[5]), "+f"(d[6]), "+f"(d[7]),
        "+f"(d[8]), "+f"(d[9]), "+f"(d[10]), "+f"(d[11]), "+f"(d[12]), "+f"(d[13]), "+f"(d[14]), "+f"(d[15]),
        "+f"(d[16]), "+f"(d[17]), "+f"(d[18]), "+f"(d[19]), "+f"(d[20]), "+f"(d[21]), "+f"(d[22]), "+f"(d[23]),
        "+f"(d[24]), "+f"(d[25]), "+f"(d[26]), "+f"(d[27]), "+f"(d[28]), "+f"(d[29]), "+f"(d[30]), "+f"(d[31]),
        "+f"(d[32]), "+f"(d[33]), "+f"(d[34]), "+f"(d[35]), "+f"(d[36]), "+f"(d[37]), "+f"(d[38]), "+f"(d[39]),
        "+f"(d[40]), "+f"(d[41]), "+f"(d[42]), "+f"(d[43]), "+f"(d[44]), "+f"(d[45]), "+f"(d[46]), "+f"(d[47]),
        "+f"(d[48]), "+f"(d[49]), "+f"(d[50]), "+f"(d[51]), "+f"(d[52]), "+f"(d[53]), "+f"(d[54]), "+f"(d[55]),
        "+f"(d[56]), "+f"(d[57]), "+f"(d[58]), "+f"(d[59]), "+f"(d[60]), "+f"(d[61]), "+f"(d[62]), "+f"(d[63]),
        "+f"(d[64]), "+f"(d[65]), "+f"(d[66]), "+f"(d[67]), "+f"(d[68]), "+f"(d[69]), "+f"(d[70]), "+f"(d[71]),
        "+f"(d[72]), "+f"(d[73]), "+f"(d[74]), "+f"(d[75]), "+f"(d[76]), "+f"(d[77]), "+f"(d[78]), "+f"(d[79]),
        "+f"(d[80]), "+f"(d[81]), "+f"(d[82]), "+f"(d[83]), "+f"(d[84]), "+f"(d[85]), "+f"(d[86]), "+f"(d[87]),
        "+f"(d[88]), "+f"(d[89]), "+f"(d[90]), "+f"(d[91]), "+f"(d[92]), "+f"(d[93]), "+f"(d[94]), "+f"(d[95]),
        "+f"(d[96]), "+f"(d[97]), "+f"(d[98]), "+f"(d[99]), "+f"(d[100]), "+f"(d[101]), "+f"(d[102]), "+f"(d[103]),
        "+f"(d[104]), "+f"(d[105]), "+f"(d[106]), "+f"(d[107]), "+f"(d[108]), "+f"(d[109]), "+f"(d[110]), "+f"(d[111]),
        "+f"(d[112]), "+f"(d[113]), "+f"(d[114]), "+f"(d[115]), "+f"(d[116]), "+f"(d[117]), "+f"(d[118]), "+f"(d[119]),
        "+f"(d[120]), "+f"(d[121]), "+f"(d[122]), "+f"(d[123]), "+f"(d[124]), "+f"(d[125]), "+f"(d[126]), "+f"(d[127])
        : "l"(da), "l"(db), "r"(acc));
}

__device__ __forceinline__ void wgmma_n64_rs_tb(float* d, uint32_t a0, uint32_t a1, uint32_t a2, uint32_t a3, uint32_t db, int acc) {
    asm volatile(
        "{\n.reg .pred p;\n.reg .b64 db;\nsetp.ne.b32 p, %37, 0;\nmov.b64 db, {%36, 0x40000040};\n"
        "wgmma.mma_async.sync.aligned.m64n64k16.f32.bf16.bf16 {"
        "%0, %1, %2, %3, %4, %5, %6, %7, %8, %9, %10, %11, %12, %13, %14, %15, "
        "%16, %17, %18, %19, %20, %21, %22, %23, %24, %25, %26, %27, %28, %29, %30, %31"
        "}, {%32, %33, %34, %35}, db, p, 1, 1, 1;\n}\n"
        :
        "+f"(d[0]), "+f"(d[1]), "+f"(d[2]), "+f"(d[3]), "+f"(d[4]), "+f"(d[5]), "+f"(d[6]), "+f"(d[7]),
        "+f"(d[8]), "+f"(d[9]), "+f"(d[10]), "+f"(d[11]), "+f"(d[12]), "+f"(d[13]), "+f"(d[14]), "+f"(d[15]),
        "+f"(d[16]), "+f"(d[17]), "+f"(d[18]), "+f"(d[19]), "+f"(d[20]), "+f"(d[21]), "+f"(d[22]), "+f"(d[23]),
        "+f"(d[24]), "+f"(d[25]), "+f"(d[26]), "+f"(d[27]), "+f"(d[28]), "+f"(d[29]), "+f"(d[30]), "+f"(d[31])
        : "r"(a0), "r"(a1), "r"(a2), "r"(a3), "r"(db), "r"(acc));
}

template <int TB>
__device__ __forceinline__ void wgmma_n128_rs(float (&d)[64], uint32_t a0, uint32_t a1, uint32_t a2, uint32_t a3, uint32_t db, int acc) {
    asm volatile(
        "{\n.reg .pred p;\n.reg .b64 db;\nsetp.ne.b32 p, %69, 0;\nmov.b64 db, {%68, 0x40000040};\n"
        "wgmma.mma_async.sync.aligned.m64n128k16.f32.bf16.bf16 {"
        "%0, %1, %2, %3, %4, %5, %6, %7, %8, %9, %10, %11, %12, %13, %14, %15, "
        "%16, %17, %18, %19, %20, %21, %22, %23, %24, %25, %26, %27, %28, %29, %30, %31, "
        "%32, %33, %34, %35, %36, %37, %38, %39, %40, %41, %42, %43, %44, %45, %46, %47, "
        "%48, %49, %50, %51, %52, %53, %54, %55, %56, %57, %58, %59, %60, %61, %62, %63"
        "}, {%64, %65, %66, %67}, db, p, 1, 1, %70;\n}\n"
        :
        "+f"(d[0]), "+f"(d[1]), "+f"(d[2]), "+f"(d[3]), "+f"(d[4]), "+f"(d[5]), "+f"(d[6]), "+f"(d[7]),
        "+f"(d[8]), "+f"(d[9]), "+f"(d[10]), "+f"(d[11]), "+f"(d[12]), "+f"(d[13]), "+f"(d[14]), "+f"(d[15]),
        "+f"(d[16]), "+f"(d[17]), "+f"(d[18]), "+f"(d[19]), "+f"(d[20]), "+f"(d[21]), "+f"(d[22]), "+f"(d[23]),
        "+f"(d[24]), "+f"(d[25]), "+f"(d[26]), "+f"(d[27]), "+f"(d[28]), "+f"(d[29]), "+f"(d[30]), "+f"(d[31]),
        "+f"(d[32]), "+f"(d[33]), "+f"(d[34]), "+f"(d[35]), "+f"(d[36]), "+f"(d[37]), "+f"(d[38]), "+f"(d[39]),
        "+f"(d[40]), "+f"(d[41]), "+f"(d[42]), "+f"(d[43]), "+f"(d[44]), "+f"(d[45]), "+f"(d[46]), "+f"(d[47]),
        "+f"(d[48]), "+f"(d[49]), "+f"(d[50]), "+f"(d[51]), "+f"(d[52]), "+f"(d[53]), "+f"(d[54]), "+f"(d[55]),
        "+f"(d[56]), "+f"(d[57]), "+f"(d[58]), "+f"(d[59]), "+f"(d[60]), "+f"(d[61]), "+f"(d[62]), "+f"(d[63])
        : "r"(a0), "r"(a1), "r"(a2), "r"(a3), "r"(db), "r"(acc), "n"(TB));
}

__device__ __forceinline__ void wgmma_n128_ss(float* d, uint64_t da, uint64_t db, int acc) {
    asm volatile(
        "{\n.reg .pred p;\nsetp.ne.b32 p, %66, 0;\n"
        "wgmma.mma_async.sync.aligned.m64n128k16.f32.bf16.bf16 {"
        "%0, %1, %2, %3, %4, %5, %6, %7, %8, %9, %10, %11, %12, %13, %14, %15, "
        "%16, %17, %18, %19, %20, %21, %22, %23, %24, %25, %26, %27, %28, %29, %30, %31, "
        "%32, %33, %34, %35, %36, %37, %38, %39, %40, %41, %42, %43, %44, %45, %46, %47, "
        "%48, %49, %50, %51, %52, %53, %54, %55, %56, %57, %58, %59, %60, %61, %62, %63"
        "}, %64, %65, p, 1, 1, 0, 1;\n}\n"
        :
        "+f"(d[0]), "+f"(d[1]), "+f"(d[2]), "+f"(d[3]), "+f"(d[4]), "+f"(d[5]), "+f"(d[6]), "+f"(d[7]),
        "+f"(d[8]), "+f"(d[9]), "+f"(d[10]), "+f"(d[11]), "+f"(d[12]), "+f"(d[13]), "+f"(d[14]), "+f"(d[15]),
        "+f"(d[16]), "+f"(d[17]), "+f"(d[18]), "+f"(d[19]), "+f"(d[20]), "+f"(d[21]), "+f"(d[22]), "+f"(d[23]),
        "+f"(d[24]), "+f"(d[25]), "+f"(d[26]), "+f"(d[27]), "+f"(d[28]), "+f"(d[29]), "+f"(d[30]), "+f"(d[31]),
        "+f"(d[32]), "+f"(d[33]), "+f"(d[34]), "+f"(d[35]), "+f"(d[36]), "+f"(d[37]), "+f"(d[38]), "+f"(d[39]),
        "+f"(d[40]), "+f"(d[41]), "+f"(d[42]), "+f"(d[43]), "+f"(d[44]), "+f"(d[45]), "+f"(d[46]), "+f"(d[47]),
        "+f"(d[48]), "+f"(d[49]), "+f"(d[50]), "+f"(d[51]), "+f"(d[52]), "+f"(d[53]), "+f"(d[54]), "+f"(d[55]),
        "+f"(d[56]), "+f"(d[57]), "+f"(d[58]), "+f"(d[59]), "+f"(d[60]), "+f"(d[61]), "+f"(d[62]), "+f"(d[63])
        : "l"(da), "l"(db), "r"(acc));
}

__device__ __forceinline__ void wgmma_n8_ta(float* d, uint64_t da, uint64_t db) {
    asm volatile("wgmma.mma_async.sync.aligned.m64n8k16.f32.bf16.bf16 {%0, %1, %2, %3}, %4, %5, 1, 1, 1, 1, 0;\n"
                 : "+f"(d[0]), "+f"(d[1]), "+f"(d[2]), "+f"(d[3]) : "l"(da), "l"(db));
}

#define PROF(slot, role)
#undef PROF_GT
#define PROF_GT(slot)

struct Params {
    const __nv_bfloat16* x;
    const __nv_bfloat16* w_r;
    const uint8_t *c_kv, *w_uk, *w_uv;
    uint8_t* out;
};
__device__ __forceinline__ void lsu_prefetch(const void* p) { asm volatile("prefetch.global.L2 [%0];" ::"l"(p) : "memory"); }

template <typename T>
__device__ __forceinline__ T* ptr_off(T* base, uint32_t off) {
    uint32_t lo, hi;
    asm("mov.b64 {%0, %1}, %2;" : "=r"(lo), "=r"(hi) : "l"(base));
    asm("add.cc.u32 %0, %0, %2;\naddc.u32 %1, %1, 0;" : "+r"(lo), "+r"(hi) : "r"(off));
    T* r;
    asm("mov.b64 %0, {%1, %2};" : "=l"(r) : "r"(lo), "r"(hi));
    return r;
}
__device__ __forceinline__ int kv_head(int pair) { return pair & 7; }
__device__ __forceinline__ int kv_tokens(int pair) { return ((pair >> 3) & 1) * 4 + (pair >> 4); }
__device__ __forceinline__ int out_rows(int pair) { return pair & 7; }
__device__ __forceinline__ int out_cols(int pair) { return (pair >> 4) * 4 + ((pair >> 3) & 1) * 2; }
__device__ __forceinline__ int attn_rowblock(int pair, int seg) {
    int j = pair & 3, hl = pair >> 2;
    return (((hl & 1) | (j == 0)) ^ seg) ? j : 7 - j;
}
__device__ __forceinline__ int outproj_head(int i, int ib) {
    if (i < 16) return i;
    return 16 + 2 * (i & 7) + ((ib < 4) ^ ((i >> 3) & 1));
}

__device__ __forceinline__ void pin_value(uint32_t& v) { asm volatile("" : "+r"(v)); }
__device__ __forceinline__ void pin_value(int& v) { asm volatile("" : "+r"(v)); }
__device__ __forceinline__ void pin_value(const uint8_t*& v) { asm volatile("" : "+l"(v)); }

__device__ __forceinline__ void producer(const Params& P, uint32_t sb, int pair, int c,
                                         const CUtensorMap* m_ckv, const CUtensorMap* m_wu,
                                         const CUtensorMap* m_wq, const CUtensorMap* m_wo) {
    const int hl = pair >> 2;
    const int ibA = attn_rowblock(pair, 0), nA = 2 * ibA + 2;
    const int ib = out_rows(pair), mi = 2 * ib + c, nb = out_cols(pair);
    const bool leader = elect_one();
    uint32_t g = 4, tail = 0;
    if (leader) prefetch_map(m_wq);
    auto wait_released = [&](uint32_t need) {
#pragma unroll 1
        for (; tail <= need; tail++) mbar_wait(sb + BAR_EMPTY + (tail & 7) * 8, (tail >> 3) & 1);
    };
    auto wait_released_here = [&](uint32_t need) {
#pragma unroll 1
        for (; tail < need; tail++) mbar_wait(sb + BAR_EMPTY + (tail & 7) * 8, (tail >> 3) & 1);
        if (tail == need) mbar_wait(sb + BAR_EMPTYL + (need & 7) * 8, (need >> 3) & 1);
    };
    auto wait_released_peer = [&](uint32_t need) {
        if (tail == need) {
            uint32_t eb = sb + BAR_EMPTY + (need & 7) * 8, ep = (need >> 3) & 1;
            tail++;
            mbar_wait(eb, ep);
        }
    };
    auto full_bar = [&]() { return sb + BAR_FULL + (g & 7) * 8; };
    auto pin = [](auto&... v) { (pin_value(v), ...); };
#pragma unroll 1
    for (int rnd = 0; rnd < 2; rnd++) {
#pragma unroll 1
        for (int i = rnd ? 0 : 4; i < 16; i++) {
            int kb = i & 7, h2 = (kv_head(pair) + (i & 8) + rnd * 16) * 2, krow = kb * 64;
            uint32_t pg = sb + (i & 3) * (3 * PAGE), pb = pg + (1 + c) * PAGE, bar = full_bar();
            pin(kb, h2, krow, pg, pb, bar);
            const uint32_t need = g - 4 - (i < 2);
            wait_released_here(need);
            if (leader) {
                mbar_expect_tx(bar, 3 * PAGE);
                tma_3d(pg, m_wu, 0, krow, h2, bar);
            }
            wait_released_peer(need);
            if (leader) {
                tma_3d_mc(pb, m_ckv, 0, kv_tokens(pair) * 256 + c * 128, kb, bar);
                if (rnd == 1 && i == 3) asm volatile("red.relaxed.gpu.global.add.u32 [%0], 1;" ::"l"(ptr_off(g_sync.kvfree, hl * 32)) : "memory");
            }
            g++;
        }
        mbar_sleep(sb + BAR_DEP, 0);
        const uint8_t* xa = ptr_off(g_xn, ibA * (16 * 32768) + c * PAGE);
        const uint8_t* xb = ptr_off(g_xn, (7 - ibA) * (16 * 32768) + (1 - c) * PAGE);
#pragma unroll 1
        for (int kb = 0; kb < DM / 64; kb++) {
            uint32_t pg = sb + (kb & 3) * (3 * PAGE), pw = pg + 2 * PAGE + c * 8192, bar = full_bar(), p2 = pg + PAGE;
            int krow = kb * 64;
            pin(pg, pw, p2, bar, krow);
            wait_released_here(g - 4);
            if (leader) {
                mbar_expect_tx(bar, 3 * PAGE);
                bulk_load(pg, xa, PAGE, bar);
            }
            wait_released_peer(g - 4);
            if (leader) {
                tma_3d_mc(pw, m_wq, 0, krow, (rnd * 16 + hl) * 2 + c, bar);
                bulk_load(p2, xb, PAGE, bar);
            }
            g++;
            xa += 32768;
            xb += 32768;
        }
        mbar_sleep(sb + BAR_DEP + 8 + rnd * 16, 0);
        if (rnd == 1 && leader) prefetch_map(m_wo);
        uint32_t pg = sb + c * PAGE;
#pragma unroll 1
        for (int j = 0; j < 36; j++) {
            const bool isk = j == 0 || ((j & 1) && j != 35);
            const int t = isk ? (j + 1) >> 1 : (j - 1) >> 1;
            const uint8_t* src = ptr_off(g_kv, (hl * 16 + (t >= nA ? t - nA : t)) * 65536 + (isk ? 0 : 32768) + c * PAGE);
            uint32_t bar = full_bar(), need = g - 6 + (j < 2) + (j < 5);
            pin(src, bar, need);
            wait_released(need);
            if (leader) {
                mbar_expect_tx(bar, 2 * PAGE);
                bulk_load_mc(pg, src, PAGE, bar);
            }
            g++;
            if (rnd == 0 && j >= 22 && j < 34) {
                const int cta = pair * 2 + c, i = j - 22;
                const uint32_t l = (threadIdx.x & 31) * 128;
                if (i < 8) lsu_prefetch(ptr_off(i & 1 ? P.w_uv : P.w_uk, cta * 32768 + (i >> 1) * 8192 + 4096 + l));
                else lsu_prefetch(ptr_off(P.c_kv, cta * 16384 + (i - 8) * 4096 + l));
            }
            pg = pg >= sb + SM_REGION - 2 * PAGE ? pg - (SM_REGION - 2 * PAGE) : pg + 2 * PAGE;
        }
    }
    uint32_t pg = sb;
#pragma unroll 1
    for (int i = 0; i < 64; i++) {
        if ((i & 15) == 0 && i != 16) mbar_sleep(sb + BAR_DEP + 32 + (i >> 1) - (i ? 8 : 0), 0);
        const int kb = outproj_head(i >> 1, ib) * 2 + (i & 1);
        const uint8_t* src = ptr_off(g_ctx, (mi * 64 + kb) * PAGE);
        uint32_t bar = full_bar(), pw = pg + PAGE + c * 8192;
        int krow = kb * 64;
        pin(src, bar, pw, krow);
        wait_released_here(g - 6);
        if (leader) {
            mbar_expect_tx(bar, 2 * PAGE);
            bulk_load(pg, src, PAGE, bar);
        }
        wait_released_peer(g - 6);
        if (leader) tma_3d_mc(pw, m_wo, 0, krow, nb + c, bar);
        g++;
        pg = pg == sb + SM_REGION - 2 * PAGE ? sb : pg + 2 * PAGE;
    }
}

__device__ __forceinline__ uint32_t xn_block(int row64, int kb) {
    return (((row64 >> 2) * 16 + kb) * 4 + ((row64 & 1) * 2 + (((row64 >> 1) & 1) ^ 1))) * 8192;
}
__device__ __forceinline__ uint32_t image_offset(int row, int ch) {
    return xn_block(row >> 6, ch >> 3) + (row & 63) * 128 + (((ch & 7) ^ (row & 7)) << 4);
}
__device__ __forceinline__ uint32_t bf2_sub(uint32_t a, uint32_t b) {
    uint32_t r;
    asm("sub.rn.bf16x2 %0, %1, %2;" : "=r"(r) : "r"(a), "r"(b));
    return r;
}
__device__ __forceinline__ uint32_t bf2_fma(uint32_t a, uint32_t b, uint32_t c) {
    uint32_t r;
    asm("fma.rn.bf16x2 %0, %1, %2, %3;" : "=r"(r) : "r"(a), "r"(b), "r"(c));
    return r;
}
template <int N0, int N>
__device__ __forceinline__ void ln_sums(const uint32_t (&u)[N], float& sum, float& sq) {
    float s0 = 0.f, s1 = 0.f, q0 = 0.f, q1 = 0.f;
#pragma unroll
    for (int k = N0; k < N0 + 16; k++) {
        const float a = bf_lo(u[k]), b = bf_hi(u[k]);
        s0 += a; s1 += b;
        q0 = fmaf(a, a, q0); q1 = fmaf(b, b, q1);
    }
    sum = s0 + s1;
    sq = q0 + q1;
}
__device__ __forceinline__ void ln_finish(float sum, float sq, uint32_t& mean2, uint32_t& rhi2, uint32_t& rlo2) {
    const float ms = sum * (1.0f / DM);
    const float var = fmaxf(fmaf(-ms, ms, sq * (1.0f / DM)), 0.f);
    const float rden = rcp_approx(bf_round(sqrt_approx(bf_round(bf_round(var) + 1e-5f))));
    const float rhi = bf_round(rden);
    mean2 = pack_bf16(ms, ms);
    rhi2 = pack_bf16(rhi, rhi);
    rlo2 = pack_bf16(rden - rhi, rden - rhi);
}
template <int N0, int N>
__device__ __forceinline__ void ln_apply(uint32_t (&u)[N], uint32_t mean2, uint32_t rhi2, uint32_t rlo2, uint8_t* dst) {
#pragma unroll
    for (int i = 0; i < 4; i++) {
        uint32_t o[4];
#pragma unroll
        for (int k = 0; k < 4; k++) {
            const uint32_t d = bf2_sub(u[N0 + 4 * i + k], mean2);
            o[k] = bf2_fma(d, rhi2, bf2_mul(d, rlo2));
        }
#pragma unroll
        for (int k = 0; k < 4; k++) u[N0 + 4 * i + k] = o[k];
        __stcg(reinterpret_cast<uint4*>(dst + i * 131072), make_uint4(o[0], o[1], o[2], o[3]));
    }
}
__device__ __forceinline__ int query_rowblock(int pair, int c, int w, int seg) {
    const int qA = (w ? 0 : 2) + c;
    return 4 * attn_rowblock(pair, seg) + (seg ? 3 - qA : qA);
}

__device__ __noinline__ void fetch_helper(const uint8_t* w_u, uint32_t sb, int w, int lane, int pair, int c) {
    const uint32_t page = sb + SM_REGION + w * PAGE + lane * 16;
    mbar_sleep(sb + BAR_FULL + 5 * 8, 0);
#pragma unroll 1
    for (int i = 0; i < 2; i++) {
        lsu_prefetch(ptr_off(w_u, ((pair * 2 + c) * 4 + i * 2 + (lane >> 4)) * 8192 + 2048 + (lane & 15) * 128));
        __nanosleep(300);
    }
    const unsigned e1 = __ldcg(&g_sync.done) / NCTA + 1;
#pragma unroll 1
    for (int e = 1; e <= 7; e += 2) mbar_sleep(sb + BAR_DONE + 8, (e >> 1) & 1);
    const int rb = out_rows(pair) * 4 + c * 2 + w, kb0 = out_cols(pair);
    const uint8_t* src = ptr_off(g_xn, xn_block(rb, kb0) + lane * 16);
#pragma unroll 1
    for (int i = 0; i < 32; i += 4) {
#pragma unroll
        for (int k = 0; k < 4; k++) cp_async16(page + (i + k) * 512, src + (i + k) * 512 + (i >> 4) * (32768 - 8192));
        __nanosleep(200);
    }
    wait_counter(&g_sync.ffn_done, e1);
    const int r = __ldcg(ptr_off(g_sel, (lane >> 4) * 4)) - rb * 64, ch = lane & 15;
    const uint4 t = __ldcg(ptr_off(g_routed, ((lane >> 4) * 128 + kb0 * 8 + ch) * 16));
    asm volatile("cp.async.wait_all;" ::: "memory");
    __syncwarp();
    if (r >= 0 && r < 64)
        sts128(sb + SM_REGION + w * PAGE + (ch >> 3) * 8192 + r * 128 + (((ch & 7) ^ (r & 7)) << 4), t.x, t.y, t.z, t.w);
    __syncwarp();
    if (lane == 0) mbar_arrive(sb + BAR_G + w * 8);
    PROF(20, 2);
}

__device__ __noinline__ void sync_helper(uint32_t sb, int lane, int pair, int c) {
    const unsigned e1 = __ldcg(&g_sync.done) / NCTA + 1;
    const int ib = out_rows(pair);
    int e = 0, b = 0;
#pragma unroll 1
    for (uint32_t n = 0; (e < 9 || b < 7) && n < SPIN_LIMIT; n++) {
        if (e < 9 && __all_sync(~0u, mbar_test(sb + BAR_DONE + (e & 1) * 8, (e >> 1) & 1))) {
            const int rnd = e > 4, ev = (e - 1) & 3;
            unsigned* flag = e == 0 ? &g_sync.ln
                           : ev < 2 ? ptr_off(g_sync.kv, (rnd * 16 + kv_head(pair) + 8 * ev) * 32)
                                    : ptr_off(g_sync.ctx, (query_rowblock(pair, c, lane & 1, ev & 1) * NH + rnd * 16 + (pair >> 2)) * 4);
            asm volatile("fence.proxy.async.global;\nfence.release.gpu;" ::: "memory");
            if (lane < ((e == 0 || ev < 2) ? 1 : 2)) asm volatile("red.relaxed.gpu.global.add.u32 [%0], 1;" ::"l"(flag) : "memory");
            PROF(10 + e, 2);
            e++;
        }
        if (b < 7 && e > 0 && (b < 4 || (n & POLL_MASK) == 0)) {
            const int i = b == 4 ? lane >> 1 : 8 * b - 24 + ((lane >> 1) & 7);
            const unsigned* cnt = b == 0 ? &g_sync.ln
                                : b == 2 ? ptr_off(g_sync.kvfree, (kv_head(pair) + 8 * (lane & 1)) * 32)
                                : b < 4 ? ptr_off(g_sync.kv, ((b >> 1) * 16 + (pair >> 2)) * 32)
                                        : ptr_off(g_sync.ctx, ((4 * ib + 2 * c + (lane & 1)) * NH + outproj_head(i & 31, ib)) * 4);
            if (__all_sync(~0u, (int)(ld_relaxed(cnt) - e1 * (b == 0 ? NMAIN : b == 2 ? 8 : b < 4 ? 16 : 1)) >= 0)) {
                asm volatile("fence.acquire.gpu;\nfence.proxy.async.global;" ::: "memory");
                __syncwarp();
                if (lane == 0) mbar_arrive(sb + BAR_DEP + b * 8);
                PROF(1 + b, 2);
                b++;
            }
        }
        __nanosleep(150);
    }
}

__device__ __forceinline__ unsigned long long block_max_key(unsigned long long k, unsigned long long* red, int tid) {
#pragma unroll
    for (int o = 16; o; o >>= 1) {
        unsigned long long t = __shfl_xor_sync(~0u, k, o);
        k = t > k ? t : k;
    }
    bar_sync(1, 256);
    if ((tid & 31) == 0) red[tid >> 5] = k;
    bar_sync(1, 256);
    k = red[0];
#pragma unroll
    for (int i = 1; i < 8; i++) k = red[i] > k ? red[i] : k;
    return k;
}

constexpr int FS = FF / 4;
constexpr int FSTAGE = 32768, FNST = 6;
constexpr int FN1 = 2 * (DM / 16), FN2 = FS / 16;

__device__ __forceinline__ void ffn_producer(uint32_t sb, int s, const CUtensorMap* m_gate, const CUtensorMap* m_up,
                                             const CUtensorMap* m_down) {
    wait_counter(&g_sync.ln, (__ldcg(&g_sync.done) / NCTA + 1) * NMAIN);
    int slot = 0, ph = 1;
#pragma unroll 1
    for (int st = 0; st < FN1 + FN2; st++) {
        mbar_sleep(sb + BAR_EMPTY + slot * 8, ph);
        const uint32_t bar = sb + BAR_FULL + slot * 8;
        const bool up = st < FN1;
        mbar_expect_tx(bar, up ? FS * 32 : DM * 32);
        tma_3d_hint(sb + slot * FSTAGE, up ? ((st & 1) ? m_up : m_gate) : m_down, 0,
                    up ? (st >> 1) * 16 : s * FS + (st - FN1) * 16, up ? s * (FS / 64) : 0, bar, POL_FIRST);
        if (++slot == FNST) { slot = 0; ph ^= 1; }
    }
}

__device__ __forceinline__ void ffn_cta(uint8_t* smem, uint32_t sb, int s, unsigned epoch, const __nv_bfloat16* w_r) {
    const int tid = threadIdx.x, lane = tid & 31;
    const int warp = __shfl_sync(~0u, tid >> 5, 0), w = warp >> 2;
    constexpr uint32_t XB = FNST * FSTAGE, HB = XB + 16384, AUX = HB + 14336;
    unsigned long long* red = reinterpret_cast<unsigned long long*>(smem + AUX);
    unsigned* flag = reinterpret_cast<unsigned*>(smem + AUX + 128);
    const unsigned e1 = epoch + 1;
    for (int i = tid; i < (16384 + 14336) / 16; i += 256) reinterpret_cast<uint4*>(smem + XB)[i] = make_uint4(0, 0, 0, 0);
    {
        float wf[32];
#pragma unroll
        for (int i = 0; i < 4; i++) {
            const uint4 t = __ldg(reinterpret_cast<const uint4*>(w_r) + lane + 32 * i);
            const uint32_t tu[4] = {t.x, t.y, t.z, t.w};
#pragma unroll
            for (int k = 0; k < 4; k++) { wf[8 * i + 2 * k] = bf_lo(tu[k]); wf[8 * i + 2 * k + 1] = bf_hi(tu[k]); }
        }
        if (tid == 0) wait_counter(&g_sync.ln, e1 * NMAIN);
        bar_sync(1, 256);
#pragma unroll 1
        for (int r0 = s * (SEQ / 4) + warp * (SEQ / 32); r0 < s * (SEQ / 4) + (warp + 1) * (SEQ / 32); r0 += 4) {
            uint4 t[4][4];
#pragma unroll
            for (int r = 0; r < 4; r++)
#pragma unroll
                for (int i = 0; i < 4; i++) t[r][i] = __ldcg(reinterpret_cast<const uint4*>(g_xn + image_offset(r0 + r, lane) + i * 131072));
            float acc[4];
#pragma unroll
            for (int r = 0; r < 4; r++) {
                float a = 0.f, b = 0.f;
#pragma unroll
                for (int i = 0; i < 4; i++) {
                    const uint32_t tu[4] = {t[r][i].x, t[r][i].y, t[r][i].z, t[r][i].w};
#pragma unroll
                    for (int k = 0; k < 4; k++) {
                        a = fmaf(bf_lo(tu[k]), wf[8 * i + 2 * k], a);
                        b = fmaf(bf_hi(tu[k]), wf[8 * i + 2 * k + 1], b);
                    }
                }
                acc[r] = a + b;
            }
#pragma unroll
            for (int o = 16; o; o >>= 1)
#pragma unroll
                for (int r = 0; r < 4; r++) acc[r] += __shfl_xor_sync(~0u, acc[r], o);
            if (lane < 4) __stcg(&g_r[r0 + lane], bf_round(lane == 0 ? acc[0] : lane == 1 ? acc[1] : lane == 2 ? acc[2] : acc[3]));
        }
        __threadfence();
        bar_sync(1, 256);
        if (tid == 0) {
            red_release(&g_sync.router);
            wait_counter(&g_sync.router, e1 * 4);
        }
        bar_sync(1, 256);
    }
    unsigned long long keys[8];
    unsigned long long best = 0;
#pragma unroll
    for (int i = 0; i < 8; i++) {
        int idx = tid + 256 * i;
        uint32_t b = __float_as_uint(__ldcg(&g_r[idx]) + 0.0f);
        b = (b & 0x80000000u) ? ~b : (b | 0x80000000u);
        keys[i] = ((unsigned long long)b << 32) | (unsigned)(SEQ - 1 - idx);
        best = keys[i] > best ? keys[i] : best;
    }
    const unsigned long long k0 = block_max_key(best, red, tid);
    best = 0;
#pragma unroll
    for (int i = 0; i < 8; i++) best = (keys[i] != k0 && keys[i] > best) ? keys[i] : best;
    const unsigned long long k1 = block_max_key(best, red, tid);
    const int row = SEQ - 1 - (int)((w ? k1 : k0) & 0xffffffffu);
    const int ch = tid & 127;
    const uint4 xrow = __ldcg(reinterpret_cast<const uint4*>(g_xn + image_offset(row, ch)));
    *reinterpret_cast<uint4*>(smem + XB + (ch >> 3) * 1024 + w * 128 + (((ch & 7) ^ w) << 4)) = xrow;
    fence_async_smem();
    bar_sync(1, 256);
    PROF(20, tid >> 7);
    int slot = 0, ph = 0, prev = 0;
    auto next_stage = [&](bool has_prev) {
        wg_commit();
        wg_wait<1>();
        if (has_prev && lane < 2) mbar_arrive(sb + BAR_EMPTY + prev * 8);
        prev = slot;
        if (++slot == FNST) { slot = 0; ph ^= 1; }
    };
    {
        float ag[28], au[28];
#pragma unroll
        for (int i = 0; i < 28; i++) ag[i] = au[i] = 0.f;
#pragma unroll 1
        for (int ks = 0; ks < DM / 16; ks++) {
            const uint64_t db = make_desc(sb + XB + (ks >> 2) * 1024 + (ks & 3) * 32, 16);
            mbar_wait(sb + BAR_FULL + slot * 8, ph);
            uint64_t da = make_desc(sb + slot * FSTAGE + w * (7 * 2048), 16);
            wg_fence();
#pragma unroll
            for (int b = 0; b < 7; b++) wgmma_n8_ta(ag + 4 * b, da + b * 128, db);
            next_stage(ks > 0);
            mbar_wait(sb + BAR_FULL + slot * 8, ph);
            da = make_desc(sb + slot * FSTAGE + w * (7 * 2048), 16);
            wg_fence();
#pragma unroll
            for (int b = 0; b < 7; b++) wgmma_n8_ta(au + 4 * b, da + b * 128, db);
            next_stage(true);
        }
        wg_wait<0>();
        reg_fence(ag);
        reg_fence(au);
        if ((lane & 3) == 0) {
#pragma unroll
            for (int i = 0; i < 28; i++) {
                const int f = (warp & 3) * 16 + (lane >> 2) + (i & 2) * 4, tok = i & 1;
                const float h = bf_round(silu_f(bf_round(ag[i]))) * bf_round(au[i]);
                *reinterpret_cast<__nv_bfloat16*>(smem + HB + (w * 7 + (i >> 2)) * 1024 + tok * 128 + (((f >> 3) ^ tok) << 4) + (f & 7) * 2) =
                    __float2bfloat16_rn(h);
            }
        }
    }
    fence_async_smem();
    bar_sync(1, 256);
    PROF(21, tid >> 7);
    {
        float ay[32];
#pragma unroll
        for (int i = 0; i < 32; i++) ay[i] = 0.f;
#pragma unroll 1
        for (int ks = 0; ks < FN2; ks++) {
            const uint64_t db = make_desc(sb + HB + (ks >> 2) * 1024 + (ks & 3) * 32, 16);
            mbar_wait(sb + BAR_FULL + slot * 8, ph);
            const uint64_t da = make_desc(sb + slot * FSTAGE + w * (8 * 2048), 16);
            wg_fence();
#pragma unroll
            for (int b = 0; b < 8; b++) wgmma_n8_ta(ay + 4 * b, da + b * 128, db);
            next_stage(true);
        }
        wg_wait<0>();
        reg_fence(ay);
        if ((lane & 3) == 0) {
#pragma unroll
            for (int i = 0; i < 32; i++)
                g_ypart[(s * 2 + (i & 1)) * DM + (w * 8 + (i >> 2)) * 64 + (warp & 3) * 16 + (lane >> 2) + (i & 2) * 4] = ay[i];
        }
    }
    PROF(23, tid >> 7);
    __threadfence();
    bar_sync(1, 256);
    if (tid == 0) {
        *flag = atomicAdd(&g_sync.ffn_ticket, 1u) == epoch * 4 + 3;
        __threadfence();
    }
    bar_sync(1, 256);
    if (*flag) {
        const float sg = bf_round(__fdividef(1.0f, 1.0f + __expf(-__ldcg(&g_r[row]))));
        const uint32_t xu[4] = {xrow.x, xrow.y, xrow.z, xrow.w};
        uint32_t o[4];
#pragma unroll
        for (int k = 0; k < 4; k++) {
            float y0 = 0.f, y1 = 0.f;
#pragma unroll
            for (int q = 0; q < 4; q++) {
                const float2 y = __ldcg(reinterpret_cast<const float2*>(&g_ypart[(q * 2 + w) * DM + ch * 8 + 2 * k]));
                y0 += y.x; y1 += y.y;
            }
            o[k] = pack_bf16(bf_lo(xu[k]) + bf_round(bf_round(y0) * sg), bf_hi(xu[k]) + bf_round(bf_round(y1) * sg));
        }
        g_routed[w * 128 + ch] = make_uint4(o[0], o[1], o[2], o[3]);
        if (ch == 0) g_sel[w] = row;
        bar_sync(1, 256);
        if (tid == 0) red_release(&g_sync.ffn_done);
    }
}

__device__ __forceinline__ uint32_t slab_addr(uint32_t stg, int lane, int s) {
    const int row = ((lane >> 3) & 1) * 8 + (lane & 7);
    const int chunk = 2 * (s & 3) + (lane >> 4);
    return stg + row * 128 + (s >> 2) * 8192 + ((chunk ^ (lane & 7)) << 4);
}

constexpr float SM_SCALE = 0.08838834764831845f * 1.4426950408889634f;
constexpr float SUM_HI = 1048576.f, SUM_LO = 1.0f / 1048576.f;

template <int I0, int I1, int J0>
__device__ __forceinline__ void mask_range(float (&S)[64], float limf) {
#pragma unroll
    for (int i = I0; i < I1; i++) {
        const int j = i >> 2;
        float t;
        asm("add.sat.f32 %0, %1, %2;" : "=f"(t) : "f"((float)(32 * (j >> 2) + 2 * (j & 3) + (i & 1) - (i & 2) * 4)), "f"(-limf));
        S[4 * J0 + i] = fmaf(t, -1e30f, S[4 * J0 + i]);
    }
}
template <int J0>
__device__ __forceinline__ void mask_half(float (&S)[64], float limf, int v) {
    asm volatile("" : "+f"(limf));
    if (v < 2) {
        mask_range<0, 16, J0>(S, limf);
#pragma unroll
        for (int i = 16; i < 32; i++) S[4 * J0 + i] = -1e30f;
    } else {
        mask_range<16, 32, J0>(S, limf);
    }
}
__device__ __forceinline__ void issue_qk(float (&S)[64], const uint32_t (&Q)[32], uint32_t d0) {
#pragma unroll
    for (int s = 0; s < 8; s++)
        wgmma_n128_rs<1>(S, Q[4 * s], Q[4 * s + 1], Q[4 * s + 2], Q[4 * s + 3], d0 + s * 128, s > 0);
}
__device__ __forceinline__ void issue_qk_half(float (&T)[32], const uint32_t (&Q)[32], uint32_t d0) {
#pragma unroll
    for (int s = 0; s < 8; s++) wgmma_n64_rs_tb(T, Q[4 * s], Q[4 * s + 1], Q[4 * s + 2], Q[4 * s + 3], d0 + s * 128, s > 0);
}
template <int H>
__device__ __forceinline__ void issue_pv(float (&O)[64], const uint32_t (&Pm)[32], uint32_t d0, int acc) {
#pragma unroll
    for (int s = 4 * H; s < 4 * H + 4; s++)
        wgmma_n128_rs<0>(O, Pm[4 * s], Pm[4 * s + 1], Pm[4 * s + 2], Pm[4 * s + 3], d0 + H * (PAGE >> 4) + (s & 3) * 2, s > 0 ? 1 : acc);
}
template <int J0, int J1>
__device__ __forceinline__ void exp_groups(const float (&S)[64], uint32_t (&Pm)[32], float (&sum)[2]) {
#pragma unroll
    for (int i = 2 * J0; i < 2 * J1; i++) asm volatile("" : "+r"(Pm[i])::"memory");
#pragma unroll
    for (int j = J0; j < J1; j++) {
        const float e0 = ex2(S[4 * j]), e1 = ex2(S[4 * j + 1]), e2 = ex2(S[4 * j + 2]), e3 = ex2(S[4 * j + 3]);
        sum[0] = (j ? sum[0] + e0 : e0) + e1;
        sum[1] = (j ? sum[1] + e2 : e2) + e3;
        Pm[2 * j] = pack_bf16(e0, e1);
        Pm[2 * j + 1] = pack_bf16(e2, e3);
    }
}
__device__ __forceinline__ void shift_rows(float (&S)[64], float d0, float d1) {
#pragma unroll
    for (int j = 0; j < 16; j++) {
        S[4 * j] -= d0; S[4 * j + 1] -= d0; S[4 * j + 2] -= d1; S[4 * j + 3] -= d1;
    }
}
__device__ constexpr int chunk_src(int i) { return 4 * (4 * (i >> 3) + (i & 3)) + 2 * ((i >> 2) & 1); }
enum : uint32_t { CTL_FIRST = 1, CTL_SWITCH = 2, CTL_LAST = 4, CTL_HALF = 128, CTL_MASKHI = 256, CTL_WOUT = 512, CTL_PVHALF = 1024, CTL_PVACC = 16384,
                  CTL_SHIFT = 32768 };
__device__ __forceinline__ float quad_sum(float v) {
    v += __shfl_xor_sync(~0u, v, 1);
    return v + __shfl_xor_sync(~0u, v, 2);
}

__device__ __forceinline__ void store_part(uint8_t* base, uint32_t row_bits, int p, const uint32_t (&pk)[64], uint64_t pol) {
    asm volatile("{\n.reg .b64 d0, d1;\nxor.b64 d0, %0, %1;\nxor.b64 d1, d0, 64;\n"
                 "TS: .branchtargets P0, P1, P2, P3, P4, P5, P6, P7;\n"
                 "brx.idx.uni %2, TS;\n"
                 "P0:\n st.global.cg.L2::cache_hint.v4.u32 [d0 + 0], {%3, %4, %5, %6}, %67;\n st.global.cg.L2::cache_hint.v4.u32 [d1 + 0], {%11, %12, %13, %14}, %67;\n bra.uni DONE;\n"
                 "P1:\n st.global.cg.L2::cache_hint.v4.u32 [d0 + 0], {%7, %8, %9, %10}, %67;\n st.global.cg.L2::cache_hint.v4.u32 [d1 + 0], {%15, %16, %17, %18}, %67;\n bra.uni DONE;\n"
                 "P2:\n st.global.cg.L2::cache_hint.v4.u32 [d0 + 16384], {%19, %20, %21, %22}, %67;\n st.global.cg.L2::cache_hint.v4.u32 [d1 + 16384], {%27, %28, %29, %30}, %67;\n bra.uni DONE;\n"
                 "P3:\n st.global.cg.L2::cache_hint.v4.u32 [d0 + 16384], {%23, %24, %25, %26}, %67;\n st.global.cg.L2::cache_hint.v4.u32 [d1 + 16384], {%31, %32, %33, %34}, %67;\n bra.uni DONE;\n"
                 "P4:\n st.global.cg.L2::cache_hint.v4.u32 [d0 + 65536], {%35, %36, %37, %38}, %67;\n st.global.cg.L2::cache_hint.v4.u32 [d1 + 65536], {%43, %44, %45, %46}, %67;\n bra.uni DONE;\n"
                 "P5:\n st.global.cg.L2::cache_hint.v4.u32 [d0 + 65536], {%39, %40, %41, %42}, %67;\n st.global.cg.L2::cache_hint.v4.u32 [d1 + 65536], {%47, %48, %49, %50}, %67;\n bra.uni DONE;\n"
                 "P6:\n st.global.cg.L2::cache_hint.v4.u32 [d0 + 81920], {%51, %52, %53, %54}, %67;\n st.global.cg.L2::cache_hint.v4.u32 [d1 + 81920], {%59, %60, %61, %62}, %67;\n bra.uni DONE;\n"
                 "P7:\n st.global.cg.L2::cache_hint.v4.u32 [d0 + 81920], {%55, %56, %57, %58}, %67;\n st.global.cg.L2::cache_hint.v4.u32 [d1 + 81920], {%63, %64, %65, %66}, %67;\n bra.uni DONE;\n"
                 "DONE:\n}\n"
                 ::"l"(base), "l"((uint64_t)((p & 1) ? row_bits : 0)), "r"(p), "r"(pk[0]), "r"(pk[1]), "r"(pk[2]), "r"(pk[3]), "r"(pk[4]), "r"(pk[5]), "r"(pk[6]), "r"(pk[7]), "r"(pk[8]), "r"(pk[9]), "r"(pk[10]), "r"(pk[11]), "r"(pk[12]), "r"(pk[13]), "r"(pk[14]), "r"(pk[15]), "r"(pk[16]), "r"(pk[17]), "r"(pk[18]), "r"(pk[19]), "r"(pk[20]), "r"(pk[21]), "r"(pk[22]), "r"(pk[23]), "r"(pk[24]), "r"(pk[25]), "r"(pk[26]), "r"(pk[27]), "r"(pk[28]), "r"(pk[29]), "r"(pk[30]), "r"(pk[31]), "r"(pk[32]), "r"(pk[33]), "r"(pk[34]), "r"(pk[35]), "r"(pk[36]), "r"(pk[37]), "r"(pk[38]), "r"(pk[39]), "r"(pk[40]), "r"(pk[41]), "r"(pk[42]), "r"(pk[43]), "r"(pk[44]), "r"(pk[45]), "r"(pk[46]), "r"(pk[47]), "r"(pk[48]), "r"(pk[49]), "r"(pk[50]), "r"(pk[51]), "r"(pk[52]), "r"(pk[53]), "r"(pk[54]), "r"(pk[55]), "r"(pk[56]), "r"(pk[57]), "r"(pk[58]), "r"(pk[59]), "r"(pk[60]), "r"(pk[61]), "r"(pk[62]), "r"(pk[63]), "l"(pol)
                 : "memory");
}

__device__ __forceinline__ void store_part4(uint8_t* d0, int p, const uint32_t (&pk)[64]) {
    asm volatile("{\n.reg .b64 d1;\nxor.b64 d1, %0, 64;\n"
                 "TS: .branchtargets P0, P1, P2, P3;\n"
                 "brx.idx.uni %1, TS;\n"
                 "P0:\n st.global.cg.v4.u32 [%0 + 0], {%2, %3, %4, %5};\n st.global.cg.v4.u32 [d1 + 0], {%10, %11, %12, %13};\n bra.uni DONE;\n"
                 "P1:\n st.global.cg.v4.u32 [%0 + 1024], {%6, %7, %8, %9};\n st.global.cg.v4.u32 [d1 + 1024], {%14, %15, %16, %17};\n bra.uni DONE;\n"
                 "P2:\n st.global.cg.v4.u32 [%0 + 16384], {%18, %19, %20, %21};\n st.global.cg.v4.u32 [d1 + 16384], {%26, %27, %28, %29};\n bra.uni DONE;\n"
                 "P3:\n st.global.cg.v4.u32 [%0 + 17408], {%22, %23, %24, %25};\n st.global.cg.v4.u32 [d1 + 17408], {%30, %31, %32, %33};\n bra.uni DONE;\n"
                 "DONE:\n}\n"
                 ::"l"(d0), "r"(p), "r"(pk[0]), "r"(pk[1]), "r"(pk[2]), "r"(pk[3]), "r"(pk[4]), "r"(pk[5]), "r"(pk[6]), "r"(pk[7]), "r"(pk[8]), "r"(pk[9]), "r"(pk[10]), "r"(pk[11]), "r"(pk[12]), "r"(pk[13]), "r"(pk[14]), "r"(pk[15]), "r"(pk[16]), "r"(pk[17]), "r"(pk[18]), "r"(pk[19]), "r"(pk[20]), "r"(pk[21]), "r"(pk[22]), "r"(pk[23]), "r"(pk[24]), "r"(pk[25]), "r"(pk[26]), "r"(pk[27]), "r"(pk[28]), "r"(pk[29]), "r"(pk[30]), "r"(pk[31])
                 : "memory");
}

__device__ __forceinline__ void consumer(uint32_t sb, int pair, int c, uint8_t* out, const uint8_t* x) {
    const int tid = threadIdx.x;
    const int warp = __shfl_sync(~0u, tid >> 5, 0);
    const int w = warp >> 2, v = warp & 3;
    const int lane = __shfl_sync(~0u, tid & 31, tid & 31);

    const uint32_t empty_rel = lane == 2 ? mapa(sb + BAR_EMPTYL, c) : mapa(sb + BAR_EMPTY, lane & 1);
    auto release = [&](uint32_t grp) {
        if (lane < 3) mbar_arrive_cluster(empty_rel + (grp & 7) * 8);
    };
    auto wait_full = [&](uint32_t grp) { mbar_wait(sb + BAR_FULL + (grp & 7) * 8, (grp >> 3) & 1); };

    uint32_t g = 0;
    const uint32_t stg = sb + SM_REGION + w * PAGE + v * 2048;
    const uint32_t chunk0 = (lane >> 2) * 128 + (((lane & 3) ^ (lane >> 2)) << 4);
    auto mark_done = [&](int odd) {
        __syncwarp();
        if (lane == 0) mbar_arrive(sb + BAR_DONE + odd * 8);
    };
    auto ctx_dst = [&](int rnd, int seg) {
        const int rb = query_rowblock(pair, c, w, seg);
        return ptr_off(g_ctx, ((rb >> 1) * 64 + (rnd * 16 + (pair >> 2)) * 2) * PAGE + (rb & 1) * 8192 + v * 2048);
    };

    uint32_t ctl_tab;
    {
        const int t = lane, firstB = 2 * attn_rowblock(pair, 0) + 2 - w;
        auto is_half = [&](int u) { return (u == firstB - 1 || u == 16) && c == (u >= firstB); };
        auto block = [&](int u) { return u + (w == 1 && u >= firstB); };
        auto place = [](int j) { return ((j & 15) << 3) | ((j - (j * 43 >> 8) * 6) << 11); };
        const int jv = min(2 * block(t - 1) + 2, 35), jk = t == 17 ? jv : max(2 * block(t) - 1, 0);
        const bool diag = t == firstB - 1 || t == 16;
        ctl_tab = ((t == 0 || t == firstB) ? CTL_FIRST : 0) | (t == firstB ? CTL_SWITCH : 0) | (t == 17 ? CTL_LAST : 0) |
                  (diag ? (is_half(t) ? CTL_HALF : CTL_MASKHI) : 0) | (t == firstB + 1 ? CTL_WOUT : 0) |
                  (is_half(t - 1) ? CTL_PVHALF : 0) | ((t == 1 || t == firstB + 1) ? 0 : CTL_PVACC) |
                  place(jk) | ((place(jv) | (t ? 3 : 0)) << 16);
    }

    uint32_t pk[64];
#pragma unroll
    for (int i = 0; i < 64; i++) asm volatile("" : "=r"(pk[i]));
    uint8_t* pend = nullptr;
    uint32_t prow = 0x400;
    auto write_part = [&](int p, uint64_t pol = POL_NORMAL) { store_part(pend, prow, p, pk, pol); };
    if (w == 1) bar_arrive(2, 256);

    for (int item = 0; item < 6; item++) {
        if ((0x1B >> item) & 1) {
            constexpr int nk = DC / 64;
            float acc[128];
            auto issue_kblock = [&](int first_acc) {
                wait_full(g);
                const uint32_t pg = sb + (g & 3) * (3 * PAGE);
                const uint64_t da = make_desc(pg + w * 8192, 16), db = make_desc(pg + PAGE, 16);
                wg_fence();
                wgmma_n256_ss(acc, da, db, first_acc);
                wgmma_n256_ss(acc, da + 128, db + 2, 1);
                wgmma_n256_ss(acc, da + 256, db + 4, 1);
                wgmma_n256_ss(acc, da + 384, db + 6, 1);
                wg_commit();
                g++;
            };
            if (item == 0) PROF(17, w);
            issue_kblock(0);
            if (item == 0) PROF(1, w);
            if (item == 0 && w == 0) PROF_GT(1);
            const int nparts = item == 0 ? 0 : (item == 3 ? 4 : 8);
            const int ln_row = (pair * 2 + c) * 16 + warp * 2;
            if (item == 0) {
                const uint8_t* src = ptr_off(x, ln_row * (DM * 2) + lane * 16);
#pragma unroll
                for (int i = 0; i < 8; i++) {
                    const uint4 t = __ldcg(reinterpret_cast<const uint4*>(src + i * 512));
                    pk[4 * i] = t.x; pk[4 * i + 1] = t.y; pk[4 * i + 2] = t.z; pk[4 * i + 3] = t.w;
                }
            }
#pragma unroll 1
            for (int kb = 1; kb < nk; kb++) {
                if (kb == nk - 1 && w == 1) bar_sync(4, 256);
                issue_kblock(1);
                if (kb == nk - 1 && w == 0) bar_arrive(4, 256);
                wg_wait<1>();
                release(g - 2);
                if (kb <= nparts) {
                    if (item == 4 && kb == 1) mbar_wait(sb + BAR_DEP + 16, 0);
                    write_part(kb - 1, item == 3 ? POL_FIRST : POL_NORMAL);
                    if (kb == nk - 1) write_part(nk - 1);
                    if (kb == nparts || kb == nk - 1) mark_done(item != 3);
                }
                if (g < 8) {
                    float s[2], q[2];
                    if (g == 4) {
                        ln_sums<0>(pk, s[0], q[0]);
                        pk[32] = __float_as_uint(s[0]); pk[33] = __float_as_uint(q[0]);
                    }
                    if (g == 5) {
                        ln_sums<16>(pk, s[1], q[1]);
                        pk[34] = __float_as_uint(s[1]); pk[35] = __float_as_uint(q[1]);
                    }
                    if (g == 6) {
#pragma unroll
                        for (int r = 0; r < 2; r++) { s[r] = __uint_as_float(pk[32 + 2 * r]); q[r] = __uint_as_float(pk[33 + 2 * r]); }
                        const bool hi = lane & 16, od = lane & 8;
                        float a = hi ? s[1] : s[0], b = hi ? q[1] : q[0];
                        a += __shfl_xor_sync(~0u, hi ? s[0] : s[1], 16);
                        b += __shfl_xor_sync(~0u, hi ? q[0] : q[1], 16);
                        float t = od ? b : a;
                        t += __shfl_xor_sync(~0u, od ? a : b, 8);
#pragma unroll
                        for (int o = 4; o; o >>= 1) t += __shfl_xor_sync(~0u, t, o);
#pragma unroll
                        for (int r = 0; r < 2; r++) {
                            s[r] = __shfl_sync(~0u, t, 16 * r);
                            q[r] = __shfl_sync(~0u, t, 16 * r + 8);
                        }
                        ln_finish(s[0], q[0], pk[36], pk[37], pk[38]);
                        ln_finish(s[1], q[1], pk[39], pk[40], pk[41]);
                    }
                    if (g == 6) ln_apply<0>(pk, pk[36], pk[37], pk[38], ptr_off(g_xn, image_offset(ln_row, lane)));
                    if (g == 7) {
                        ln_apply<16>(pk, pk[39], pk[40], pk[41], ptr_off(g_xn, image_offset(ln_row + 1, lane)));
                        mark_done(0);
                    }
                }
            }
            wg_wait<0>();
            reg_fence(acc);
            release(g - 1);
            PROF(2 + 2 * item, w);
            if (w == 0) PROF_GT(2 + 2 * item);
#pragma unroll
            for (int i = 0; i < 64; i++) pk[i] = pack_bf16(acc[chunk_src(i)], acc[chunk_src(i) + 1]);
            const uint32_t vrow = (v >> 1) * 32 + (lane >> 3) * 8 + (v & 1) * 4 + ((lane >> 2) & 1);
            pend = ptr_off(g_kv, ((kv_head(pair) + (item == 1 || item == 4 ? 8 : 0)) * 16 + kv_tokens(pair) * 2) * 65536 + w * 8192 +
                                     (c ? 32768 + vrow * 128 + (((lane & 3) ^ (vrow & 7)) << 4) : v * 2048 + chunk0));
            prow = c ? 0x120 : 0x400;
            PROF(3 + 2 * item, w);
            continue;
        }

        float O[64], S[64];
        auto issue_q = [&](int first_acc) {
            wait_full(g);
            const uint32_t pg = sb + (g & 3) * (3 * PAGE);
            const uint64_t da = make_desc(pg + w * 8192, 16), db = make_desc(pg + 2 * PAGE, 8192);
            const uint64_t dab = make_desc(pg + PAGE + (1 - w) * 8192, 16);
            wg_fence();
#pragma unroll
            for (int q = 0; q < 4; q++) wgmma_n128_ss(S, da + 2 * q, db + 128 * q, q ? 1 : first_acc);
            wg_commit();
#pragma unroll
            for (int q = 0; q < 4; q++) wgmma_n128_ss(O, dab + 2 * q, db + 128 * q, q ? 1 : first_acc);
            wg_commit();
            g++;
        };
        issue_q(0);
#pragma unroll 1
        for (int kb = 1; kb < DM / 64; kb++) {
            if (kb == DM / 64 - 2 && w == 1) bar_sync(4, 256);
            issue_q(1);
            if (kb == DM / 64 - 1 && w == 0) bar_arrive(4, 256);
            wg_wait<2>();
            release(g - 2);
            if (kb <= 8) {
                write_part(kb - 1);
                if (kb == 8) mark_done(0);
            }
        }
        uint32_t Q[32], Pm[32];
#pragma unroll
        for (int i = 0; i < 32; i++) Pm[i] = pk[32 + i];
        float lim = (float)(v * 16 + (lane >> 2) - 8 * (lane & 3));
        float mc[2] = {0.f, 0.f}, l[2] = {0.f, 0.f}, scale[2] = {0.f, 0.f}, sum[2];
        uint32_t ctl = __shfl_sync(~0u, ctl_tab, 0), nxt = __shfl_sync(~0u, ctl_tab, 1);
        int t = 1;
        asm volatile("" : "+f"(lim), "+f"(mc[0]), "+f"(mc[1]), "+f"(l[0]), "+f"(l[1]), "+r"(ctl), "+r"(nxt), "+r"(t));
        wg_wait<1>();
        reg_fence(S);
#pragma unroll
        for (int i = 0; i < 32; i++) Q[i] = pack_bf16(S[2 * i] * SM_SCALE, S[2 * i + 1] * SM_SCALE);
        reg_fence(Q);
        wait_full(g);
        wg_wait<0>();
        reg_fence(O);
        release(g - 1);
        PROF(2 + 2 * item, w);
        if (w == 0) PROF_GT(2 + 2 * item);

        const uint32_t qaddr = stg + lane * 16;
        auto put_queries = [&](const float (&A)[64]) {
#pragma unroll
            for (int i = 0; i < 8; i++)
                sts128(qaddr + (i >> 2) * 8192 + (i & 3) * 512, pack_bf16(A[8 * i] * SM_SCALE, A[8 * i + 1] * SM_SCALE), pack_bf16(A[8 * i + 2] * SM_SCALE, A[8 * i + 3] * SM_SCALE),
                       pack_bf16(A[8 * i + 4] * SM_SCALE, A[8 * i + 5] * SM_SCALE), pack_bf16(A[8 * i + 6] * SM_SCALE, A[8 * i + 7] * SM_SCALE));
        };
        auto get_queries = [&]() {
#pragma unroll
            for (int i = 0; i < 8; i++) lds128(qaddr + (i >> 2) * 8192 + (i & 3) * 512, Q[4 * i], Q[4 * i + 1], Q[4 * i + 2], Q[4 * i + 3]);
        };
        const uint32_t kdesc0 = (uint32_t)make_desc(sb, PAGE), vdesc0 = (uint32_t)make_desc(sb, 16);
        auto wait_block = [&](uint32_t word) { mbar_wait(sb + BAR_FULL + (word & 56), (word >> 6) & 1); };
        auto write_out = [&](auto early) {
            uint8_t* dst = ctx_dst(item == 5, 0);
            uint8_t* d[2] = {ptr_off(dst, chunk0), ptr_off(dst, chunk0 ^ 64)};
#pragma unroll
            for (int i = early.value ? 0 : WN; i < (early.value ? WN : 8); i++) {
                const float sc = scale[i & 1];
                uint32_t q[4];
#pragma unroll
                for (int k = 0; k < 4; k++) q[k] = pack_bf16(O[chunk_src(4 * i + k)] * sc, O[chunk_src(4 * i + k) + 1] * sc);
                if (early.value && i > 0) {
#pragma unroll
                    for (int k = 0; k < 4; k++) O[4 * (i - 1) + k] = __uint_as_float(q[k]);
                }
                stg_hint(d[(i >> 1) & 1] + (i >> 2) * PAGE + (i & 1) * 1024, q[0], q[1], q[2], q[3], item == 2 ? POL_FIRST : POL_NORMAL);
            }
            if (!early.value) mark_done(1);
        };
        put_queries(O);
        bar_sync(2 + w, 256);
        if (!(ctl & CTL_HALF)) {
            wg_fence();
            issue_qk(S, Q, kdesc0);
            wg_commit();
            wg_fence();
            wg_commit();
            wg_commit();
            bar_arrive(3 - w, 256);
            wg_wait<2>();
            reg_fence(S);
        } else {
            float T[32];
            wg_fence();
            issue_qk_half(T, Q, kdesc0);
            wg_commit();
            wg_fence();
            wg_commit();
            wg_commit();
            bar_arrive(3 - w, 256);
            wg_wait<2>();
            reg_fence(T);
#pragma unroll
            for (int i = 0; i < 32; i++) S[i] = T[i];
        }
        for (;;) {
            const bool kready = mbar_try(sb + BAR_FULL + (nxt & 56), (nxt >> 6) & 1);
            if (ctl & (CTL_HALF | CTL_MASKHI | CTL_SHIFT)) {
                if (ctl & CTL_HALF) mask_half<0>(S, lim, v);
                if (ctl & CTL_MASKHI) mask_half<8>(S, lim, v);
                if (ctl & CTL_SHIFT) shift_rows(S, mc[0], mc[1]);
            }
            float early[4 * EARLY];
#pragma unroll
            for (int j = 0; j < EARLY; j++) {
#pragma unroll
                for (int i = 4 * j; i < 4 * j + 4; i++) early[i] = ex2(S[i]);
                sum[0] = (j ? sum[0] + early[4 * j] : early[4 * j]) + early[4 * j + 1];
                sum[1] = (j ? sum[1] + early[4 * j + 2] : early[4 * j + 2]) + early[4 * j + 3];
            }
            const uint32_t tie = __float_as_uint(sum[0]) & __float_as_uint(sum[1]) & (ctl & 0x80000000u);
            if (lane < 3) mbar_arrive_cluster(empty_rel + tie + (ctl & 56));
            wg_wait<1>();
#pragma unroll
            for (int j = 0; j < EARLY; j++) {
                asm volatile("" : "+r"(Pm[2 * j]), "+r"(Pm[2 * j + 1])::"memory");
                Pm[2 * j] = pack_bf16(early[4 * j], early[4 * j + 1]);
                Pm[2 * j + 1] = pack_bf16(early[4 * j + 2], early[4 * j + 3]);
            }
            exp_groups<EARLY, 8>(S, Pm, sum);
            const bool half = ctl & CTL_HALF;
            if (!half) {
                wg_wait<0>();
                reg_fence(O);
                if (lane < ((ctl >> 16) & 3)) mbar_arrive_cluster(empty_rel + ((ctl >> 16) & 56));
                exp_groups<8, 16>(S, Pm, sum);
            } else {
                asm volatile("wgmma.wait_group.sync.aligned 0;\n" ::: "memory");
                reg_fence(O);
                if (lane < ((ctl >> 16) & 3)) asm volatile("mbarrier.arrive.shared::cluster.b64 _, [%0];\n" ::"r"(empty_rel + ((ctl >> 16) & 56)) : "memory");
            }
            const bool over = !(sum[0] + sum[1] <= SUM_HI);
            if (__any_sync(~0u, over || !kready) || (((ctl & CTL_FIRST) | (nxt & (CTL_SWITCH | CTL_LAST | CTL_HALF))) != 0)) {
                bool bad = __any_sync(~0u, over);
                if (!kready) wait_block(nxt);
                const bool first = ctl & CTL_FIRST;
                if (first) {
                    uint32_t b0 = __ballot_sync(~0u, sum[0] >= SUM_LO), b1 = __ballot_sync(~0u, sum[1] >= SUM_LO);
                    b0 |= b0 >> 1; b1 |= b1 >> 1;
                    b0 |= b0 >> 2; b1 |= b1 >> 2;
                    bad |= (b0 & b1 & 0x11111111u) != 0x11111111u;
                }
                if (bad) {
                    float d0 = fmaxf(S[0], S[1]), d1 = fmaxf(S[2], S[3]);
#pragma unroll
                    for (int j = 1; j < 8; j++) {
                        d0 = fmaxf(d0, fmaxf(S[4 * j], S[4 * j + 1]));
                        d1 = fmaxf(d1, fmaxf(S[4 * j + 2], S[4 * j + 3]));
                    }
                    if (!half) {
#pragma unroll
                        for (int j = 8; j < 16; j++) {
                            d0 = fmaxf(d0, fmaxf(S[4 * j], S[4 * j + 1]));
                            d1 = fmaxf(d1, fmaxf(S[4 * j + 2], S[4 * j + 3]));
                        }
                    }
                    d0 = fmaxf(d0, __shfl_xor_sync(~0u, d0, 1));
                    d1 = fmaxf(d1, __shfl_xor_sync(~0u, d1, 1));
                    d0 = fmaxf(d0, __shfl_xor_sync(~0u, d0, 2));
                    d1 = fmaxf(d1, __shfl_xor_sync(~0u, d1, 2));
                    if (!first) {
                        d0 = fmaxf(d0, 0.f);
                        d1 = fmaxf(d1, 0.f);
                        const float a0 = ex2(-d0), a1 = ex2(-d1);
#pragma unroll
                        for (int j = 0; j < 16; j++) {
                            O[4 * j] *= a0; O[4 * j + 1] *= a0; O[4 * j + 2] *= a1; O[4 * j + 3] *= a1;
                        }
                        l[0] *= a0; l[1] *= a1;
                    }
                    mc[0] += d0; mc[1] += d1;
                    ctl_tab |= CTL_SHIFT;
                    nxt |= CTL_SHIFT;
                    shift_rows(S, d0, d1);
                    exp_groups<0, 8>(S, Pm, sum);
                    if (!half) exp_groups<8, 16>(S, Pm, sum);
                }
                if (ctl & CTL_SWITCH) write_out(std::true_type());
                if (nxt & CTL_LAST) break;
                if (nxt & CTL_SWITCH) {
                    get_queries();
                    nxt &= ~CTL_SHIFT;
                    ctl_tab &= ~CTL_SHIFT;
                }
                if (nxt & CTL_HALF) {
                    ctl = nxt;
                    float T[32];
                    bar_sync(2 + w, 256);
                    wg_fence();
                    issue_qk_half(T, Q, kdesc0 + (ctl & 0x3800));
                    wg_commit();
                    l[0] += sum[0]; l[1] += sum[1];
                    nxt = __shfl_sync(~0u, ctl_tab, ++t);
                    wait_block(ctl >> 16);
                    const uint32_t vdesc = vdesc0 + ((ctl >> 16) & 0x3800);
                    wg_fence();
                    issue_pv<0>(O, Pm, vdesc, ctl & CTL_PVACC);
                    wg_commit();
                    issue_pv<1>(O, Pm, vdesc, 1);
                    wg_commit();
                    bar_arrive(3 - w, 256);
                    wg_wait<2>();
                    reg_fence(T);
#pragma unroll
                    for (int i = 0; i < 32; i++) S[i] = T[i];
                    continue;
                }
            }
            ctl = nxt;
            bar_sync(2 + w, 256);
            wg_fence();
            issue_qk(S, Q, kdesc0 + (ctl & 0x3800));
            wg_commit();
            l[0] += sum[0]; l[1] += sum[1];
            nxt = __shfl_sync(~0u, ctl_tab, ++t);
            if (ctl & (CTL_SWITCH | CTL_WOUT)) {
                if (ctl & CTL_SWITCH) {
                    scale[0] = rcp_approx(quad_sum(l[0]));
                    scale[1] = rcp_approx(quad_sum(l[1]));
                    l[0] = l[1] = mc[0] = mc[1] = 0.f;
                    if (w == 1) { release((ctl >> 3) - 2); release((ctl >> 3) + 1); }
                } else {
                    write_out(std::false_type());
                }
            }
            wait_block(ctl >> 16);
            const uint32_t vdesc = vdesc0 + ((ctl >> 16) & 0x3800);
            if (!(ctl & CTL_PVHALF)) {
                wg_fence();
                issue_pv<0>(O, Pm, vdesc, ctl & CTL_PVACC);
                wg_commit();
                issue_pv<1>(O, Pm, vdesc, 1);
                wg_commit();
            } else {
                wg_fence();
                issue_pv<0>(O, Pm, vdesc, ctl & CTL_PVACC);
                wg_commit();
                wg_commit();
            }
            bar_arrive(3 - w, 256);
            wg_wait<2>();
            reg_fence(S);
        }
        g += 36;
        const uint32_t vdesc = vdesc0 + (nxt & 0x3800);
        if (nxt & CTL_PVHALF) {
            wg_fence();
            issue_pv<0>(O, Pm, vdesc, nxt & CTL_PVACC);
            wg_commit();
        } else {
            wg_fence();
            issue_pv<0>(O, Pm, vdesc, nxt & CTL_PVACC);
            issue_pv<1>(O, Pm, vdesc, 1);
            wg_commit();
        }
        l[0] += sum[0]; l[1] += sum[1];
        ctl_tab = (ctl_tab & ~(0x00780078u | CTL_SHIFT)) | ((ctl_tab + 0x00200020u) & 0x00780078u);
        const float i0 = rcp_approx(quad_sum(l[0])), i1 = rcp_approx(quad_sum(l[1]));
        const uint32_t tie = __float_as_uint(i0) & __float_as_uint(i1) & (nxt & 0x80000000u);
        if (lane + tie < (w ? 0 : 3)) mbar_arrive_cluster(empty_rel + ((g - 3) & 7) * 8);
        auto finish_attention = [&](uint32_t next) {
            reg_fence(O);
            if (w == 0) release(next - 2);
            release(next - 1);
#pragma unroll
            for (int i = 0; i < 32; i++) {
                const float sc = (i & 4) ? i1 : i0;
                pk[i] = pack_bf16(O[chunk_src(i)] * sc, O[chunk_src(i) + 1] * sc);
            }
            pend = ptr_off(ctx_dst(item == 5, 1), chunk0);
            PROF(3 + 2 * item, w);
            if (w == 0) PROF_GT(3 + 2 * item);
        };
        if (item != 5) {
            wg_wait<0>();
            finish_attention(g);
            prow = 0x400;
#pragma unroll
            for (int i = 32; i < 64; i++) pk[i] = Pm[i - 32];
            continue;
        }

        float acc[64];
        uint32_t slot = 0;
        auto issue_out = [&](int first_acc) {
            wait_full(g);
            const uint64_t da = make_desc(sb + slot + w * 8192, 16), db = make_desc(sb + slot + PAGE, 8192);
            wg_fence();
#pragma unroll
            for (int q = 0; q < 4; q++) wgmma_n128_ss(acc, da + 2 * q, db + 128 * q, q ? 1 : first_acc);
            wg_commit();
            g++;
            slot = slot == SM_REGION - 2 * PAGE ? 0 : slot + 2 * PAGE;
        };
        issue_out(0);
        wg_wait<1>();
        finish_attention(g - 1);
#pragma unroll 1
        for (int kb = 1; kb < 64 - PEEL; kb++) {
            issue_out(1);
            wg_wait<1>();
            release(g - 2);
            if (kb <= 8 && !(kb & 1)) {
                store_part4(pend, (kb >> 1) - 1, pk);
                if (kb == 8) mark_done(0);
            }
            if (kb >= 32 - PEEL && ((kb + PEEL) & 3) == 2 * w) {
                uint32_t u0, u1, u2, u3;
                const uint32_t a = stg + ((kb + PEEL) & 16) * 512 + ((kb + PEEL) & 12) * 128 + lane * 16;
                mbar_wait(sb + BAR_G + w * 8, 0);
                lds128(a, u0, u1, u2, u3);
                sts128(a, pack_bf16(silu_f(bf_lo(u0)), silu_f(bf_hi(u0))), pack_bf16(silu_f(bf_lo(u1)), silu_f(bf_hi(u1))),
                       pack_bf16(silu_f(bf_lo(u2)), silu_f(bf_hi(u2))), pack_bf16(silu_f(bf_lo(u3)), silu_f(bf_hi(u3))));
            }
        }
        const uint32_t goff = (out_rows(pair) * 256 + c * 128 + w * 64 + v * 16 + (lane >> 3)) * (DM * 2) +
                              out_cols(pair) * 128 + (((lane & 7) ^ (lane >> 3)) << 4);
        uint32_t xr[32], gr[32];
        {
            const uint8_t* src[2] = {ptr_off(x, goff), ptr_off(x, goff ^ 64)};
#pragma unroll
            for (int i = 0; i < 8; i++) {
                const uint4 t = ldg_hint(src[i & 1] + (i & 3) * (4 * DM * 2) + (i >> 2) * 128, POL_FIRST);
                xr[4 * i] = t.x; xr[4 * i + 1] = t.y; xr[4 * i + 2] = t.z; xr[4 * i + 3] = t.w;
            }
        }
#pragma unroll 1
        for (int i = 0; i < PEEL; i++) {
            if (i == PEEL - STAG && w == 1) bar_sync(4, 256);
            issue_out(1);
            if (i == PEEL - 1 && w == 0) bar_arrive(4, 256);
            wg_wait<1>();
        }
        asm volatile("barrier.cluster.arrive.relaxed.aligned;" ::: "memory");
#pragma unroll
        for (int i = 0; i < 8; i++) lds128(stg + (i >> 2) * 8192 + (i & 3) * 512 + lane * 16, gr[4 * i], gr[4 * i + 1], gr[4 * i + 2], gr[4 * i + 3]);
        uint8_t* dst[2] = {ptr_off(out, goff), ptr_off(out, goff ^ 64)};
        __syncwarp();
        wg_wait<0>();
        reg_fence(acc);
        PROF(14, w);
        if (w == 0) PROF_GT(14);
#pragma unroll
        for (int s = 0; s < 8; s++)
            stmatrix_x4(slab_addr(stg, lane, s), pack_bf16(acc[8 * s], acc[8 * s + 1]), pack_bf16(acc[8 * s + 2], acc[8 * s + 3]),
                        pack_bf16(acc[8 * s + 4], acc[8 * s + 5]), pack_bf16(acc[8 * s + 6], acc[8 * s + 7]));
        __syncwarp();
        uint32_t o[32];
#pragma unroll
        for (int i = 0; i < 8; i++) lds128(stg + (i >> 2) * 8192 + (i & 3) * 512 + lane * 16, o[4 * i], o[4 * i + 1], o[4 * i + 2], o[4 * i + 3]);
#pragma unroll
        for (int i = 0; i < 8; i++) {
#pragma unroll
            for (int k = 0; k < 4; k++) xr[4 * i + k] = bf2_add(xr[4 * i + k], bf2_mul(o[4 * i + k], gr[4 * i + k]));
            __stcg(reinterpret_cast<uint4*>(dst[i & 1] + (i & 3) * (4 * DM * 2) + (i >> 2) * 128), make_uint4(xr[4 * i], xr[4 * i + 1], xr[4 * i + 2], xr[4 * i + 3]));
        }
        PROF(28, w);
        return;
    }
}

__global__ void __cluster_dims__(2, 1, 1) __launch_bounds__(384, 1)
fused_kernel(const __grid_constant__ CUtensorMap m_ckv, const __grid_constant__ CUtensorMap m_wuk,
             const __grid_constant__ CUtensorMap m_wuv, const __grid_constant__ CUtensorMap m_wq,
             const __grid_constant__ CUtensorMap m_wo, const __grid_constant__ CUtensorMap m_gate,
             const __grid_constant__ CUtensorMap m_up, const __grid_constant__ CUtensorMap m_down, const Params P) {
    extern __shared__ __align__(1024) uint8_t smem[];
    const uint32_t sb = __shfl_sync(~0u, smem_u32(smem), 0);
    const int tid = threadIdx.x;
    const int cl = blockIdx.x >> 1, c = blockIdx.x & 1;
    const int pair = cl >= 64 ? cl : cl < 4 ? cl * 16 + 15 : cl < 36 ? ((cl - 4) >> 3) * 16 + ((cl - 4) & 7)
                                                                    : ((cl - 36) / 7) * 16 + 8 + (cl - 36) % 7;
    const bool starter = tid == 256 && pair < NMAIN / 2;
    const CUtensorMap* m_wu = c ? &m_wuv : &m_wuk;
    if (tid == 256) {
        mbar_init(sb + BAR_FULL, 1);
        if (starter) {
            asm volatile("fence.mbarrier_init.release.cluster;" ::: "memory");
            mbar_expect_tx(sb + BAR_FULL, 3 * PAGE);
            tma_3d(sb, m_wu, 0, 0, kv_head(pair) * 2, sb + BAR_FULL);
            tma_3d(sb + PAGE, &m_ckv, 0, kv_tokens(pair) * 256, 0, sb + BAR_FULL);
            tma_3d(sb + 2 * PAGE, &m_ckv, 0, kv_tokens(pair) * 256 + 128, 0, sb + BAR_FULL);
        }
#pragma unroll
        for (int i = 1; i < NBAR; i++) mbar_init(sb + SM_BAR + i * 8, (i >> 3) == 1 ? 16 : i >= 25 ? 8 : 1);
        asm volatile("fence.mbarrier_init.release.cluster;" ::: "memory");
    }
    if (starter) {
#pragma unroll 1
        for (int kb = 1; kb < 4; kb++) mbar_expect_tx(sb + BAR_FULL + kb * 8, 3 * PAGE);
        tma_3d(sb + 3 * PAGE, m_wu, 0, 64, kv_head(pair) * 2, sb + BAR_FULL + 8);
    }
    PROF(18, (tid >> 7) & 1);
    __syncthreads();
    cluster_sync();
    PROF(22, (tid >> 7) & 1);
    PROF(19, (tid >> 7) & 1);
    const int warp = __shfl_sync(~0u, tid >> 5, 0), lane = tid & 31;
    auto dump_prof = [&]() {
    };
    if (pair >= NMAIN / 2) {
        if (warp < 8) ffn_cta(smem, sb, blockIdx.x - NMAIN, __ldcg(&g_sync.done) / NCTA, P.w_r);
        else if (tid == 256) ffn_producer(sb, blockIdx.x - NMAIN, &m_gate, &m_up, &m_down);
        __syncwarp();
        PROF(29, tid >> 7);
        cluster_sync();
        if (tid == 0) atomicAdd(&g_sync.done, 1u);
        if (warp < 8) dump_prof();
    } else if (warp < 8) {
        asm volatile("setmaxnreg.inc.sync.aligned.u32 232;");
        consumer(sb, pair, c, P.out, (const uint8_t*)P.x);
        PROF(29, tid >> 7);
        asm volatile("barrier.cluster.wait.aligned;" ::: "memory");
        dump_prof();
    } else {
        asm volatile("setmaxnreg.dec.sync.aligned.u32 40;");
        if (starter) {
#pragma unroll 1
            for (int kb = 1; kb < 4; kb++) {
                if (kb > 1) tma_3d(sb + kb * (3 * PAGE), m_wu, 0, kb * 64, kv_head(pair) * 2, sb + BAR_FULL + kb * 8);
                tma_3d_mc(sb + kb * (3 * PAGE) + (1 + c) * PAGE, &m_ckv, 0, kv_tokens(pair) * 256 + c * 128, kb, sb + BAR_FULL + kb * 8);
            }
        }
        if (warp == 10) {
            sync_helper(sb, lane, pair, c);
        } else if (warp & 1) {
            fetch_helper((warp & 2) ? P.w_uv : P.w_uk, sb, (warp >> 1) & 1, lane, pair, c);
        } else {
            producer(P, sb, pair, c, &m_ckv, m_wu, &m_wq, &m_wo);
        }
        bar_sync(6, 128);
        if (tid == 256) atomicAdd(&g_sync.done, 1u);
        cluster_sync();
    }
}

typedef CUresult (*EncodeFn)(CUtensorMap*, CUtensorMapDataType, cuuint32_t, void*, const cuuint64_t*, const cuuint64_t*,
                             const cuuint32_t*, const cuuint32_t*, CUtensorMapInterleave, CUtensorMapSwizzle,
                             CUtensorMapL2promotion, CUtensorMapFloatOOBfill);

void make_map_w(EncodeFn fn, CUtensorMap* m, const void* ptr, int rows, int cols, int blocks, int box_rows = 32) {
    cuuint64_t dims[3] = {64, (cuuint64_t)rows, (cuuint64_t)cols / 64};
    cuuint64_t strides[2] = {(cuuint64_t)cols * 2, 128};
    cuuint32_t box[3] = {64, (cuuint32_t)box_rows, (cuuint32_t)blocks};
    cuuint32_t es[3] = {1, 1, 1};
    fn(m, CU_TENSOR_MAP_DATA_TYPE_BFLOAT16, 3, const_cast<void*>(ptr), dims, strides, box, es, CU_TENSOR_MAP_INTERLEAVE_NONE,
       CU_TENSOR_MAP_SWIZZLE_128B, CU_TENSOR_MAP_L2_PROMOTION_L2_256B, CU_TENSOR_MAP_FLOAT_OOB_FILL_NONE);
}

}

extern "C" void kernel_launch(void* const* d_in, const int* in_sizes, int n_in, void* d_out, int out_size) {
    static EncodeFn fn = nullptr;
    if (!fn) {
        void* f = nullptr;
        cudaDriverEntryPointQueryResult qr;
        cudaGetDriverEntryPoint("cuTensorMapEncodeTiled", &f, cudaEnableDefault, &qr);
        fn = (EncodeFn)f;
        cudaFuncSetAttribute(fused_kernel, cudaFuncAttributeMaxDynamicSharedMemorySize, SMEM_BYTES);
    }
    CUtensorMap m_ckv, m_wuk, m_wuv, m_wq, m_wo, m_gate, m_up, m_down;
    make_map_w(fn, &m_gate, d_in[8], DM, FF, FS / 64, 16);
    make_map_w(fn, &m_up, d_in[9], DM, FF, FS / 64, 16);
    make_map_w(fn, &m_down, d_in[10], FF, DM, DM / 64, 16);
    make_map_w(fn, &m_ckv, d_in[1], SEQ, DC, 1, 128);
    make_map_w(fn, &m_wq, d_in[2], DM, NH * 128, 1, 64);
    make_map_w(fn, &m_wuk, d_in[3], DC, NH * 128, 2, 64);
    make_map_w(fn, &m_wuv, d_in[4], DC, NH * 128, 2, 64);
    make_map_w(fn, &m_wo, d_in[5], NH * 128, DM, 1, 64);
    Params P;
    P.x = (const __nv_bfloat16*)d_in[0];
    P.w_r = (const __nv_bfloat16*)d_in[7];
    P.c_kv = (const uint8_t*)d_in[1];
    P.w_uk = (const uint8_t*)d_in[3];
    P.w_uv = (const uint8_t*)d_in[4];
    P.out = (uint8_t*)d_out;
    fused_kernel<<<NCTA, 384, SMEM_BYTES>>>(m_ckv, m_wuk, m_wuv, m_wq, m_wo, m_gate, m_up, m_down, P);
}
```

```cpp
#include <cuda_runtime.h>
#include <cuda_bf16.h>
#include <cuda.h>
#include <stdint.h>
#include <type_traits>

namespace {

constexpr int SEQ = 2048, DM = 1024, NH = 32, DC = 512, FF = 3584;
constexpr int PAGE = 16384;
constexpr int NRING = 12;
constexpr int NCTA = 132, NMAIN = 128;
constexpr uint32_t SM_REGION = NRING * PAGE;
constexpr uint32_t SM_BAR = (NRING + 2) * PAGE;
constexpr uint32_t BAR_FULL = SM_BAR, BAR_EMPTY = SM_BAR + 64;
constexpr uint32_t BAR_DEP = SM_BAR + 128;
constexpr uint32_t BAR_G = SM_BAR + 184;
constexpr uint32_t BAR_DONE = SM_BAR + 200;
constexpr uint32_t BAR_EMPTYL = SM_BAR + 216;
constexpr int NBAR = 35;
constexpr uint32_t SM_PROF = SM_BAR + 320;
constexpr int SMEM_BYTES = SM_PROF + 512;
constexpr uint32_t SPIN_LIMIT = 1u << 16;
constexpr uint32_t POLL_MASK = 7;
constexpr int EARLY = 2;
constexpr int WN = 5;
constexpr int PEEL = 5, STAG = 3;

struct SyncBlock {
    unsigned done;       unsigned pad0[31];
    unsigned ln;         unsigned pad1[31];
    unsigned router;     unsigned pad4[31];
    unsigned ffn_ticket; unsigned pad2[31];
    unsigned ffn_done;   unsigned pad3[31];
    unsigned kv[NH * 8];
    unsigned kvfree[16 * 8];
    unsigned ctx[32 * NH];
};

__device__ __align__(1024) uint8_t g_xn[8 * 16 * 4 * 8192];
__device__ __align__(4096) uint8_t g_kv[16 * 16 * 65536];
__device__ __align__(4096) uint8_t g_ctx[16 * 64 * 16384];
__device__ __align__(16) uint4 g_routed[2 * 128];
__device__ int g_sel[2];
__device__ __align__(16) float g_r[SEQ];
__device__ __align__(16) float g_ypart[4 * 2 * DM];
__device__ SyncBlock g_sync;

__device__ __forceinline__ uint32_t smem_u32(const void* p) { return (uint32_t)__cvta_generic_to_shared(p); }

__device__ __forceinline__ void mbar_init(uint32_t bar, uint32_t count) {
    asm volatile("mbarrier.init.shared::cta.b64 [%0], %1;" ::"r"(bar), "r"(count) : "memory");
}
#define MBAR_WAIT_ASM(HINT, LIMIT)                                                                  \
    asm volatile("{\n.reg .pred p;\n.reg .u32 n;\nmov.u32 n, 0;\n"                                  \
                 "WAIT_LOOP:\n"                                                                     \
                 "mbarrier.try_wait.parity.shared::cta.b64 p, [%0], %1" HINT ";\n"                  \
                 "@p bra WAIT_DONE;\n"                                                              \
                 "add.u32 n, n, 1;\n"                                                               \
                 "setp.lt.u32 p, n, " LIMIT ";\n"                                                   \
                 "@p bra WAIT_LOOP;\n"                                                              \
                 "WAIT_DONE:\n}\n" ::"r"(bar), "r"(parity) : "memory")
__device__ __forceinline__ void mbar_wait(uint32_t bar, uint32_t parity) { MBAR_WAIT_ASM("", "131072"); }
__device__ __forceinline__ void mbar_sleep(uint32_t bar, uint32_t parity) { MBAR_WAIT_ASM(", 2000", "8192"); }
__device__ __forceinline__ bool mbar_try(uint32_t bar, uint32_t parity) {
    uint32_t ok;
    asm volatile("{\n.reg .pred p;\nmbarrier.try_wait.parity.shared::cta.b64 p, [%1], %2;\nselp.u32 %0, 1, 0, p;\n}\n"
                 : "=r"(ok) : "r"(bar), "r"(parity) : "memory");
    return ok;
}
__device__ __forceinline__ bool mbar_test(uint32_t bar, uint32_t parity) {
    uint32_t ok;
    asm volatile("{\n.reg .pred p;\nmbarrier.test_wait.parity.shared::cta.b64 p, [%1], %2;\nselp.u32 %0, 1, 0, p;\n}\n"
                 : "=r"(ok) : "r"(bar), "r"(parity) : "memory");
    return ok;
}
__device__ __forceinline__ bool elect_one() {
    uint32_t ok;
    asm volatile("{\n.reg .pred p;\nelect.sync _|p, 0xffffffff;\nselp.u32 %0, 1, 0, p;\n}\n" : "=r"(ok));
    return ok;
}
__device__ __forceinline__ void mbar_arrive(uint32_t bar) {
    asm volatile("mbarrier.arrive.shared::cta.b64 _, [%0];" ::"r"(bar) : "memory");
}
__device__ __forceinline__ void mbar_expect_tx(uint32_t bar, uint32_t bytes) {
    asm volatile("mbarrier.arrive.expect_tx.shared::cta.b64 _, [%0], %1;" ::"r"(bar), "r"(bytes) : "memory");
}
__device__ __forceinline__ void mbar_arrive_cluster(uint32_t cluster_addr) {
    asm volatile("mbarrier.arrive.shared::cluster.b64 _, [%0];" ::"r"(cluster_addr) : "memory");
}
__device__ __forceinline__ uint32_t mapa(uint32_t addr, uint32_t rank) {
    uint32_t r;
    asm("mapa.shared::cluster.u32 %0, %1, %2;" : "=r"(r) : "r"(addr), "r"(rank));
    return r;
}
__device__ __forceinline__ void tma_3d(uint32_t dst, const CUtensorMap* m, int c0, int c1, int c2, uint32_t bar) {
    asm volatile("cp.async.bulk.tensor.3d.shared::cluster.global.mbarrier::complete_tx::bytes [%0], [%1, {%3, %4, %5}], [%2];"
                 ::"r"(dst), "l"(m), "r"(bar), "r"(c0), "r"(c1), "r"(c2) : "memory");
}
__device__ __forceinline__ void tma_3d_hint(uint32_t dst, const CUtensorMap* m, int c0, int c1, int c2, uint32_t bar, uint64_t pol) {
    asm volatile("cp.async.bulk.tensor.3d.shared::cluster.global.mbarrier::complete_tx::bytes.L2::cache_hint [%0], [%1, {%3, %4, %5}], [%2], %6;"
                 ::"r"(dst), "l"(m), "r"(bar), "r"(c0), "r"(c1), "r"(c2), "l"(pol) : "memory");
}
__device__ __forceinline__ void tma_3d_mc(uint32_t dst, const CUtensorMap* m, int c0, int c1, int c2, uint32_t bar) {
    asm volatile("cp.async.bulk.tensor.3d.shared::cluster.global.mbarrier::complete_tx::bytes.multicast::cluster [%0], [%1, {%3, %4, %5}], [%2], %6;"
                 ::"r"(dst), "l"(m), "r"(bar), "r"(c0), "r"(c1), "r"(c2), "h"((uint16_t)3) : "memory");
}
__device__ __forceinline__ void bulk_load(uint32_t dst, const void* src, uint32_t bytes, uint32_t bar) {
    asm volatile("cp.async.bulk.shared::cluster.global.mbarrier::complete_tx::bytes [%0], [%1], %2, [%3];"
                 ::"r"(dst), "l"(src), "r"(bytes), "r"(bar) : "memory");
}
__device__ __forceinline__ void cp_async16(uint32_t dst, const void* src) {
    asm volatile("cp.async.cg.shared.global [%0], [%1], 16;" ::"r"(dst), "l"(src) : "memory");
}
__device__ __forceinline__ void bulk_load_mc(uint32_t dst, const void* src, uint32_t bytes, uint32_t bar) {
    asm volatile("cp.async.bulk.shared::cluster.global.mbarrier::complete_tx::bytes.multicast::cluster [%0], [%1], %2, [%3], %4;"
                 ::"r"(dst), "l"(src), "r"(bytes), "r"(bar), "h"((uint16_t)3) : "memory");
}
__device__ __forceinline__ void fence_async_smem() { asm volatile("fence.proxy.async.shared::cta;" ::: "memory"); }
__device__ __forceinline__ void prefetch_map(const CUtensorMap* m) {
    asm volatile("prefetch.tensormap [%0];" ::"l"(m) : "memory");
}
__device__ __forceinline__ void red_release(unsigned* p) {
    asm volatile("red.release.gpu.global.add.u32 [%0], 1;" ::"l"(p) : "memory");
}
__device__ __forceinline__ unsigned ld_relaxed(const unsigned* p) {
    unsigned v;
    asm volatile("ld.relaxed.gpu.global.u32 %0, [%1];" : "=r"(v) : "l"(p) : "memory");
    return v;
}
__device__ __forceinline__ void wait_counter(const unsigned* p, unsigned target) {
    for (uint32_t n = 0; (int)(ld_relaxed(p) - target) < 0 && n < SPIN_LIMIT; n++) __nanosleep(100);
    asm volatile("fence.acquire.gpu;" ::: "memory");
    asm volatile("fence.proxy.async.global;" ::: "memory");
}
__device__ __forceinline__ void bar_sync(int id, int n) { asm volatile("bar.sync %0, %1;" ::"r"(id), "r"(n) : "memory"); }
__device__ __forceinline__ void bar_arrive(int id, int n) { asm volatile("bar.arrive %0, %1;" ::"r"(id), "r"(n) : "memory"); }
__device__ __forceinline__ void cluster_sync() {
    asm volatile("barrier.cluster.arrive.relaxed.aligned;\nbarrier.cluster.wait.aligned;" ::: "memory");
}
__device__ __forceinline__ void wg_fence() { asm volatile("wgmma.fence.sync.aligned;" ::: "memory"); }
__device__ __forceinline__ void wg_commit() { asm volatile("wgmma.commit_group.sync.aligned;" ::: "memory"); }
template <int N> __device__ __forceinline__ void wg_wait() { asm volatile("wgmma.wait_group.sync.aligned %0;" ::"n"(N) : "memory"); }
template <int N> __device__ __forceinline__ void reg_fence(float (&a)[N]) {
#pragma unroll
    for (int i = 0; i < N; i++) asm volatile("" : "+f"(a[i])::"memory");
}
template <int N> __device__ __forceinline__ void reg_fence(uint32_t (&a)[N]) {
#pragma unroll
    for (int i = 0; i < N; i++) asm volatile("" : "+r"(a[i])::"memory");
}
__device__ __forceinline__ uint32_t pack_bf16(float lo, float hi) {
    uint32_t r;
    asm("cvt.rn.bf16x2.f32 %0, %1, %2;" : "=r"(r) : "f"(hi), "f"(lo));
    return r;
}
__device__ __forceinline__ float bf_lo(uint32_t v) { return __uint_as_float(v << 16); }
__device__ __forceinline__ float bf_hi(uint32_t v) { return __uint_as_float(v & 0xffff0000u); }
__device__ __forceinline__ float bf_round(float v) { return __bfloat162float(__float2bfloat16_rn(v)); }
__device__ __forceinline__ float ex2(float v) {
    float r;
    asm("ex2.approx.ftz.f32 %0, %1;" : "=f"(r) : "f"(v));
    return r;
}
__device__ __forceinline__ float sqrt_approx(float v) {
    float r;
    asm("sqrt.approx.ftz.f32 %0, %1;" : "=f"(r) : "f"(v));
    return r;
}
__device__ __forceinline__ float rcp_approx(float v) {
    float r;
    asm("rcp.approx.ftz.f32 %0, %1;" : "=f"(r) : "f"(v));
    return r;
}
__device__ __forceinline__ float silu_f(float v) { return v * rcp_approx(1.0f + ex2(v * -1.4426950408889634f)); }
__device__ __forceinline__ void stmatrix_x4(uint32_t addr, uint32_t r0, uint32_t r1, uint32_t r2, uint32_t r3) {
    asm volatile("stmatrix.sync.aligned.m8n8.x4.shared.b16 [%0], {%1, %2, %3, %4};"
                 ::"r"(addr), "r"(r0), "r"(r1), "r"(r2), "r"(r3) : "memory");
}
__device__ __forceinline__ void sts128(uint32_t addr, uint32_t r0, uint32_t r1, uint32_t r2, uint32_t r3) {
    asm volatile("st.shared.v4.b32 [%0], {%1, %2, %3, %4};" ::"r"(addr), "r"(r0), "r"(r1), "r"(r2), "r"(r3) : "memory");
}
__device__ __forceinline__ void lds128(uint32_t addr, uint32_t& r0, uint32_t& r1, uint32_t& r2, uint32_t& r3) {
    asm volatile("ld.shared.v4.b32 {%0, %1, %2, %3}, [%4];" : "=r"(r0), "=r"(r1), "=r"(r2), "=r"(r3) : "r"(addr) : "memory");
}
__device__ __forceinline__ uint32_t bf2_mul(uint32_t a, uint32_t b) {
    uint32_t r;
    asm("mul.rn.bf16x2 %0, %1, %2;" : "=r"(r) : "r"(a), "r"(b));
    return r;
}
__device__ __forceinline__ uint32_t bf2_add(uint32_t a, uint32_t b) {
    uint32_t r;
    asm("add.rn.bf16x2 %0, %1, %2;" : "=r"(r) : "r"(a), "r"(b));
    return r;
}
constexpr uint64_t POL_FIRST = 0x12F0000000000000ull, POL_NORMAL = 0x16F0000000000000ull;
__device__ __forceinline__ uint4 ldg_hint(const void* p, uint64_t pol) {
    uint4 v;
    asm volatile("ld.global.cg.L2::cache_hint.v4.u32 {%0, %1, %2, %3}, [%4], %5;" : "=r"(v.x), "=r"(v.y), "=r"(v.z), "=r"(v.w) : "l"(p), "l"(pol));
    return v;
}
__device__ __forceinline__ void stg_hint(void* p, uint32_t r0, uint32_t r1, uint32_t r2, uint32_t r3, uint64_t pol) {
    asm volatile("st.global.cg.L2::cache_hint.v4.u32 [%0], {%1, %2, %3, %4}, %5;" ::"l"(p), "r"(r0), "r"(r1), "r"(r2), "r"(r3), "l"(pol) : "memory");
}

__device__ __forceinline__ uint64_t make_desc(uint32_t addr, uint32_t lbo_bytes) {
    return (uint64_t)((addr & 0x3FFFF) >> 4) | ((uint64_t)(lbo_bytes >> 4) << 16) | ((uint64_t)(1024 >> 4) << 32) | (1ull << 62);
}

__device__ __forceinline__ void wgmma_n256_ss(float (&d)[128], uint64_t da, uint64_t db, int acc) {
    asm volatile(
        "{\n.reg .pred p;\nsetp.ne.b32 p, %130, 0;\n"
        "wgmma.mma_async.sync.aligned.m64n256k16.f32.bf16.bf16 {"
        "%0, %1, %2, %3, %4, %5, %6, %7, %8, %9, %10, %11, %12, %13, %14, %15, "
        "%16, %17, %18, %19, %20, %21, %22, %23, %24, %25, %26, %27, %28, %29, %30, %31, "
        "%32, %33, %34, %35, %36, %37, %38, %39, %40, %41, %42, %43, %44, %45, %46, %47, "
        "%48, %49, %50, %51, %52, %53, %54, %55, %56, %57, %58, %59, %60, %61, %62, %63, "
        "%64, %65, %66, %67, %68, %69, %70, %71, %72, %73, %74, %75, %76, %77, %78, %79, "
        "%80, %81, %82, %83, %84, %85, %86, %87, %88, %89, %90, %91, %92, %93, %94, %95, "
        "%96, %97, %98, %99, %100, %101, %102, %103, %104, %105, %106, %107, %108, %109, %110, %111, "
        "%112, %113, %114, %115, %116, %117, %118, %119, %120, %121, %122, %123, %124, %125, %126, %127"
        "}, %128, %129, p, 1, 1, 1, 0;\n}\n"
        :
        "+f"(d[0]), "+f"(d[1]), "+f"(d[2]), "+f"(d[3]), "+f"(d[4]), "+f"(d[5]), "+f"(d[6]), "+f"(d[7]),
        "+f"(d[8]), "+f"(d[9]), "+f"(d[10]), "+f"(d[11]), "+f"(d[12]), "+f"(d[13]), "+f"(d[14]), "+f"(d[15]),
        "+f"(d[16]), "+f"(d[17]), "+f"(d[18]), "+f"(d[19]), "+f"(d[20]), "+f"(d[21]), "+f"(d[22]), "+f"(d[23]),
        "+f"(d[24]), "+f"(d[25]), "+f"(d[26]), "+f"(d[27]), "+f"(d[28]), "+f"(d[29]), "+f"(d[30]), "+f"(d[31]),
        "+f"(d[32]), "+f"(d[33]), "+f"(d[34]), "+f"(d[35]), "+f"(d[36]), "+f"(d[37]), "+f"(d[38]), "+f"(d[39]),
        "+f"(d[40]), "+f"(d[41]), "+f"(d[42]), "+f"(d[43]), "+f"(d[44]), "+f"(d[45]), "+f"(d[46]), "+f"(d[47]),
        "+f"(d[48]), "+f"(d[49]), "+f"(d[50]), "+f"(d[51]), "+f"(d[52]), "+f"(d[53]), "+f"(d[54]), "+f"(d[55]),
        "+f"(d[56]), "+f"(d[57]), "+f"(d[58]), "+f"(d[59]), "+f"(d[60]), "+f"(d[61]), "+f"(d[62]), "+f"(d[63]),
        "+f"(d[64]), "+f"(d[65]), "+f"(d[66]), "+f"(d[67]), "+f"(d[68]), "+f"(d[69]), "+f"(d[70]), "+f"(d[71]),
        "+f"(d[72]), "+f"(d[73]), "+f"(d[74]), "+f"(d[75]), "+f"(d[76]), "+f"(d[77]), "+f"(d[78]), "+f"(d[79]),
        "+f"(d[80]), "+f"(d[81]), "+f"(d[82]), "+f"(d[83]), "+f"(d[84]), "+f"(d[85]), "+f"(d[86]), "+f"(d[87]),
        "+f"(d[88]), "+f"(d[89]), "+f"(d[90]), "+f"(d[91]), "+f"(d[92]), "+f"(d[93]), "+f"(d[94]), "+f"(d[95]),
        "+f"(d[96]), "+f"(d[97]), "+f"(d[98]), "+f"(d[99]), "+f"(d[100]), "+f"(d[101]), "+f"(d[102]), "+f"(d[103]),
        "+f"(d[104]), "+f"(d[105]), "+f"(d[106]), "+f"(d[107]), "+f"(d[108]), "+f"(d[109]), "+f"(d[110]), "+f"(d[111]),
        "+f"(d[112]), "+f"(d[113]), "+f"(d[114]), "+f"(d[115]), "+f"(d[116]), "+f"(d[117]), "+f"(d[118]), "+f"(d[119]),
        "+f"(d[120]), "+f"(d[121]), "+f"(d[122]), "+f"(d[123]), "+f"(d[124]), "+f"(d[125]), "+f"(d[126]), "+f"(d[127])
        : "l"(da), "l"(db), "r"(acc));
}

__device__ __forceinline__ void wgmma_n64_rs_tb(float* d, uint32_t a0, uint32_t a1, uint32_t a2, uint32_t a3, uint32_t db, int acc) {
    asm volatile(
        "{\n.reg .pred p;\n.reg .b64 db;\nsetp.ne.b32 p, %37, 0;\nmov.b64 db, {%36, 0x40000040};\n"
        "wgmma.mma_async.sync.aligned.m64n64k16.f32.bf16.bf16 {"
        "%0, %1, %2, %3, %4, %5, %6, %7, %8, %9, %10, %11, %12, %13, %14, %15, "
        "%16, %17, %18, %19, %20, %21, %22, %23, %24, %25, %26, %27, %28, %29, %30, %31"
        "}, {%32, %33, %34, %35}, db, p, 1, 1, 1;\n}\n"
        :
        "+f"(d[0]), "+f"(d[1]), "+f"(d[2]), "+f"(d[3]), "+f"(d[4]), "+f"(d[5]), "+f"(d[6]), "+f"(d[7]),
        "+f"(d[8]), "+f"(d[9]), "+f"(d[10]), "+f"(d[11]), "+f"(d[12]), "+f"(d[13]), "+f"(d[14]), "+f"(d[15]),
        "+f"(d[16]), "+f"(d[17]), "+f"(d[18]), "+f"(d[19]), "+f"(d[20]), "+f"(d[21]), "+f"(d[22]), "+f"(d[23]),
        "+f"(d[24]), "+f"(d[25]), "+f"(d[26]), "+f"(d[27]), "+f"(d[28]), "+f"(d[29]), "+f"(d[30]), "+f"(d[31])
        : "r"(a0), "r"(a1), "r"(a2), "r"(a3), "r"(db), "r"(acc));
}

template <int TB>
__device__ __forceinline__ void wgmma_n128_rs(float (&d)[64], uint32_t a0, uint32_t a1, uint32_t a2, uint32_t a3, uint32_t db, int acc) {
    asm volatile(
        "{\n.reg .pred p;\n.reg .b64 db;\nsetp.ne.b32 p, %69, 0;\nmov.b64 db, {%68, 0x40000040};\n"
        "wgmma.mma_async.sync.aligned.m64n128k16.f32.bf16.bf16 {"
        "%0, %1, %2, %3, %4, %5, %6, %7, %8, %9, %10, %11, %12, %13, %14, %15, "
        "%16, %17, %18, %19, %20, %21, %22, %23, %24, %25, %26, %27, %28, %29, %30, %31, "
        "%32, %33, %34, %35, %36, %37, %38, %39, %40, %41, %42, %43, %44, %45, %46, %47, "
        "%48, %49, %50, %51, %52, %53, %54, %55, %56, %57, %58, %59, %60, %61, %62, %63"
        "}, {%64, %65, %66, %67}, db, p, 1, 1, %70;\n}\n"
        :
        "+f"(d[0]), "+f"(d[1]), "+f"(d[2]), "+f"(d[3]), "+f"(d[4]), "+f"(d[5]), "+f"(d[6]), "+f"(d[7]),
        "+f"(d[8]), "+f"(d[9]), "+f"(d[10]), "+f"(d[11]), "+f"(d[12]), "+f"(d[13]), "+f"(d[14]), "+f"(d[15]),
        "+f"(d[16]), "+f"(d[17]), "+f"(d[18]), "+f"(d[19]), "+f"(d[20]), "+f"(d[21]), "+f"(d[22]), "+f"(d[23]),
        "+f"(d[24]), "+f"(d[25]), "+f"(d[26]), "+f"(d[27]), "+f"(d[28]), "+f"(d[29]), "+f"(d[30]), "+f"(d[31]),
        "+f"(d[32]), "+f"(d[33]), "+f"(d[34]), "+f"(d[35]), "+f"(d[36]), "+f"(d[37]), "+f"(d[38]), "+f"(d[39]),
        "+f"(d[40]), "+f"(d[41]), "+f"(d[42]), "+f"(d[43]), "+f"(d[44]), "+f"(d[45]), "+f"(d[46]), "+f"(d[47]),
        "+f"(d[48]), "+f"(d[49]), "+f"(d[50]), "+f"(d[51]), "+f"(d[52]), "+f"(d[53]), "+f"(d[54]), "+f"(d[55]),
        "+f"(d[56]), "+f"(d[57]), "+f"(d[58]), "+f"(d[59]), "+f"(d[60]), "+f"(d[61]), "+f"(d[62]), "+f"(d[63])
        : "r"(a0), "r"(a1), "r"(a2), "r"(a3), "r"(db), "r"(acc), "n"(TB));
}

__device__ __forceinline__ void wgmma_n128_ss(float* d, uint64_t da, uint64_t db, int acc) {
    asm volatile(
        "{\n.reg .pred p;\nsetp.ne.b32 p, %66, 0;\n"
        "wgmma.mma_async.sync.aligned.m64n128k16.f32.bf16.bf16 {"
        "%0, %1, %2, %3, %4, %5, %6, %7, %8, %9, %10, %11, %12, %13, %14, %15, "
        "%16, %17, %18, %19, %20, %21, %22, %23, %24, %25, %26, %27, %28, %29, %30, %31, "
        "%32, %33, %34, %35, %36, %37, %38, %39, %40, %41, %42, %43, %44, %45, %46, %47, "
        "%48, %49, %50, %51, %52, %53, %54, %55, %56, %57, %58, %59, %60, %61, %62, %63"
        "}, %64, %65, p, 1, 1, 0, 1;\n}\n"
        :
        "+f"(d[0]), "+f"(d[1]), "+f"(d[2]), "+f"(d[3]), "+f"(d[4]), "+f"(d[5]), "+f"(d[6]), "+f"(d[7]),
        "+f"(d[8]), "+f"(d[9]), "+f"(d[10]), "+f"(d[11]), "+f"(d[12]), "+f"(d[13]), "+f"(d[14]), "+f"(d[15]),
        "+f"(d[16]), "+f"(d[17]), "+f"(d[18]), "+f"(d[19]), "+f"(d[20]), "+f"(d[21]), "+f"(d[22]), "+f"(d[23]),
        "+f"(d[24]), "+f"(d[25]), "+f"(d[26]), "+f"(d[27]), "+f"(d[28]), "+f"(d[29]), "+f"(d[30]), "+f"(d[31]),
        "+f"(d[32]), "+f"(d[33]), "+f"(d[34]), "+f"(d[35]), "+f"(d[36]), "+f"(d[37]), "+f"(d[38]), "+f"(d[39]),
        "+f"(d[40]), "+f"(d[41]), "+f"(d[42]), "+f"(d[43]), "+f"(d[44]), "+f"(d[45]), "+f"(d[46]), "+f"(d[47]),
        "+f"(d[48]), "+f"(d[49]), "+f"(d[50]), "+f"(d[51]), "+f"(d[52]), "+f"(d[53]), "+f"(d[54]), "+f"(d[55]),
        "+f"(d[56]), "+f"(d[57]), "+f"(d[58]), "+f"(d[59]), "+f"(d[60]), "+f"(d[61]), "+f"(d[62]), "+f"(d[63])
        : "l"(da), "l"(db), "r"(acc));
}

__device__ __forceinline__ void wgmma_n8_ta(float* d, uint64_t da, uint64_t db) {
    asm volatile("wgmma.mma_async.sync.aligned.m64n8k16.f32.bf16.bf16 {%0, %1, %2, %3}, %4, %5, 1, 1, 1, 1, 0;\n"
                 : "+f"(d[0]), "+f"(d[1]), "+f"(d[2]), "+f"(d[3]) : "l"(da), "l"(db));
}

#define PROF(slot, role)
#undef PROF_GT
#define PROF_GT(slot)

struct Params {
    const __nv_bfloat16* x;
    const __nv_bfloat16* w_r;
    const uint8_t *c_kv, *w_uk, *w_uv;
    uint8_t* out;
};
__device__ __forceinline__ void lsu_prefetch(const void* p) { asm volatile("prefetch.global.L2 [%0];" ::"l"(p) : "memory"); }

template <typename T>
__device__ __forceinline__ T* ptr_off(T* base, uint32_t off) {
    uint32_t lo, hi;
    asm("mov.b64 {%0, %1}, %2;" : "=r"(lo), "=r"(hi) : "l"(base));
    asm("add.cc.u32 %0, %0, %2;\naddc.u32 %1, %1, 0;" : "+r"(lo), "+r"(hi) : "r"(off));
    T* r;
    asm("mov.b64 %0, {%1, %2};" : "=l"(r) : "r"(lo), "r"(hi));
    return r;
}
__device__ __forceinline__ int kv_head(int pair) { return pair & 7; }
__device__ __forceinline__ int kv_tokens(int pair) { return ((pair >> 3) & 1) * 4 + (pair >> 4); }
__device__ __forceinline__ int out_rows(int pair) { return pair & 7; }
__device__ __forceinline__ int out_cols(int pair) { return (pair >> 4) * 4 + ((pair >> 3) & 1) * 2; }
__device__ __forceinline__ int attn_rowblock(int pair, int seg) {
    int j = pair & 3, hl = pair >> 2;
    return (((hl & 1) | (j == 0)) ^ seg) ? j : 7 - j;
}
__device__ __forceinline__ int outproj_head(int i, int ib) {
    if (i < 16) return i;
    return 16 + 2 * (i & 7) + ((ib < 4) ^ ((i >> 3) & 1));
}

__device__ __forceinline__ void pin_value(uint32_t& v) { asm volatile("" : "+r"(v)); }
__device__ __forceinline__ void pin_value(int& v) { asm volatile("" : "+r"(v)); }
__device__ __forceinline__ void pin_value(const uint8_t*& v) { asm volatile("" : "+l"(v)); }

__device__ __forceinline__ void producer(const Params& P, uint32_t sb, int pair, int c,
                                         const CUtensorMap* m_ckv, const CUtensorMap* m_wu,
                                         const CUtensorMap* m_wq, const CUtensorMap* m_wo) {
    const int hl = pair >> 2;
    const int ibA = attn_rowblock(pair, 0), nA = 2 * ibA + 2;
    const int ib = out_rows(pair), mi = 2 * ib + c, nb = out_cols(pair);
    const bool leader = elect_one();
    uint32_t g = 4, tail = 0;
    if (leader) prefetch_map(m_wq);
    auto wait_released = [&](uint32_t need) {
#pragma unroll 1
        for (; tail <= need; tail++) mbar_wait(sb + BAR_EMPTY + (tail & 7) * 8, (tail >> 3) & 1);
    };
    auto wait_released_here = [&](uint32_t need) {
#pragma unroll 1
        for (; tail < need; tail++) mbar_wait(sb + BAR_EMPTY + (tail & 7) * 8, (tail >> 3) & 1);
        if (tail == need) mbar_wait(sb + BAR_EMPTYL + (need & 7) * 8, (need >> 3) & 1);
    };
    auto wait_released_peer = [&](uint32_t need) {
        if (tail == need) {
            uint32_t eb = sb + BAR_EMPTY + (need & 7) * 8, ep = (need >> 3) & 1;
            tail++;
            mbar_wait(eb, ep);
        }
    };
    auto full_bar = [&]() { return sb + BAR_FULL + (g & 7) * 8; };
    auto pin = [](auto&... v) { (pin_value(v), ...); };
#pragma unroll 1
    for (int rnd = 0; rnd < 2; rnd++) {
#pragma unroll 1
        for (int i = rnd ? 0 : 4; i < 16; i++) {
            int kb = i & 7, h2 = (kv_head(pair) + (i & 8) + rnd * 16) * 2, krow = kb * 64;
            uint32_t pg = sb + (i & 3) * (3 * PAGE), pb = pg + (1 + c) * PAGE, bar = full_bar();
            pin(kb, h2, krow, pg, pb, bar);
            const uint32_t need = g - 4 - (i < 2);
            wait_released_here(need);
            if (leader) {
                mbar_expect_tx(bar, 3 * PAGE);
                tma_3d(pg, m_wu, 0, krow, h2, bar);
            }
            wait_released_peer(need);
            if (leader) {
                tma_3d_mc(pb, m_ckv, 0, kv_tokens(pair) * 256 + c * 128, kb, bar);
                if (rnd == 1 && i == 3) asm volatile("red.relaxed.gpu.global.add.u32 [%0], 1;" ::"l"(ptr_off(g_sync.kvfree, hl * 32)) : "memory");
            }
            g++;
        }
        mbar_sleep(sb + BAR_DEP, 0);
        const uint8_t* xa = ptr_off(g_xn, ibA * (16 * 32768) + c * PAGE);
        const uint8_t* xb = ptr_off(g_xn, (7 - ibA) * (16 * 32768) + (1 - c) * PAGE);
#pragma unroll 1
        for (int kb = 0; kb < DM / 64; kb++) {
            uint32_t pg = sb + (kb & 3) * (3 * PAGE), pw = pg + 2 * PAGE + c * 8192, bar = full_bar(), p2 = pg + PAGE;
            int krow = kb * 64;
            pin(pg, pw, p2, bar, krow);
            wait_released_here(g - 4);
            if (leader) {
                mbar_expect_tx(bar, 3 * PAGE);
                bulk_load(pg, xa, PAGE, bar);
            }
            wait_released_peer(g - 4);
            if (leader) {
                tma_3d_mc(pw, m_wq, 0, krow, (rnd * 16 + hl) * 2 + c, bar);
                bulk_load(p2, xb, PAGE, bar);
            }
            g++;
            xa += 32768;
            xb += 32768;
        }
        mbar_sleep(sb + BAR_DEP + 8 + rnd * 16, 0);
        if (rnd == 1 && leader) prefetch_map(m_wo);
        uint32_t pg = sb + c * PAGE;
#pragma unroll 1
        for (int j = 0; j < 36; j++) {
            const bool isk = j == 0 || ((j & 1) && j != 35);
            const int t = isk ? (j + 1) >> 1 : (j - 1) >> 1;
            const uint8_t* src = ptr_off(g_kv, (hl * 16 + (t >= nA ? t - nA : t)) * 65536 + (isk ? 0 : 32768) + c * PAGE);
            uint32_t bar = full_bar(), need = g - 6 + (j < 2) + (j < 5);
            pin(src, bar, need);
            wait_released(need);
            if (leader) {
                mbar_expect_tx(bar, 2 * PAGE);
                bulk_load_mc(pg, src, PAGE, bar);
            }
            g++;
            if (rnd == 0 && j >= 22 && j < 34) {
                const int cta = pair * 2 + c, i = j - 22;
                const uint32_t l = (threadIdx.x & 31) * 128;
                if (i < 8) lsu_prefetch(ptr_off(i & 1 ? P.w_uv : P.w_uk, cta * 32768 + (i >> 1) * 8192 + 4096 + l));
                else lsu_prefetch(ptr_off(P.c_kv, cta * 16384 + (i - 8) * 4096 + l));
            }
            pg = pg >= sb + SM_REGION - 2 * PAGE ? pg - (SM_REGION - 2 * PAGE) : pg + 2 * PAGE;
        }
    }
    uint32_t pg = sb;
#pragma unroll 1
    for (int i = 0; i < 64; i++) {
        if ((i & 15) == 0 && i != 16) mbar_sleep(sb + BAR_DEP + 32 + (i >> 1) - (i ? 8 : 0), 0);
        const int kb = outproj_head(i >> 1, ib) * 2 + (i & 1);
        const uint8_t* src = ptr_off(g_ctx, (mi * 64 + kb) * PAGE);
        uint32_t bar = full_bar(), pw = pg + PAGE + c * 8192;
        int krow = kb * 64;
        pin(src, bar, pw, krow);
        wait_released_here(g - 6);
        if (leader) {
            mbar_expect_tx(bar, 2 * PAGE);
            bulk_load(pg, src, PAGE, bar);
        }
        wait_released_peer(g - 6);
        if (leader) tma_3d_mc(pw, m_wo, 0, krow, nb + c, bar);
        g++;
        pg = pg == sb + SM_REGION - 2 * PAGE ? sb : pg + 2 * PAGE;
    }
}

__device__ __forceinline__ uint32_t xn_block(int row64, int kb) {
    return (((row64 >> 2) * 16 + kb) * 4 + ((row64 & 1) * 2 + (((row64 >> 1) & 1) ^ 1))) * 8192;
}
__device__ __forceinline__ uint32_t image_offset(int row, int ch) {
    return xn_block(row >> 6, ch >> 3) + (row & 63) * 128 + (((ch & 7) ^ (row & 7)) << 4);
}
__device__ __forceinline__ uint32_t bf2_sub(uint32_t a, uint32_t b) {
    uint32_t r;
    asm("sub.rn.bf16x2 %0, %1, %2;" : "=r"(r) : "r"(a), "r"(b));
    return r;
}
__device__ __forceinline__ uint32_t bf2_fma(uint32_t a, uint32_t b, uint32_t c) {
    uint32_t r;
    asm("fma.rn.bf16x2 %0, %1, %2, %3;" : "=r"(r) : "r"(a), "r"(b), "r"(c));
    return r;
}
template <int N0, int N>
__device__ __forceinline__ void ln_sums(const uint32_t (&u)[N], float& sum, float& sq) {
    float s0 = 0.f, s1 = 0.f, q0 = 0.f, q1 = 0.f;
#pragma unroll
    for (int k = N0; k < N0 + 16; k++) {
        const float a = bf_lo(u[k]), b = bf_hi(u[k]);
        s0 += a; s1 += b;
        q0 = fmaf(a, a, q0); q1 = fmaf(b, b, q1);
    }
    sum = s0 + s1;
    sq = q0 + q1;
}
__device__ __forceinline__ void ln_finish(float sum, float sq, uint32_t& mean2, uint32_t& rhi2, uint32_t& rlo2) {
    const float ms = sum * (1.0f / DM);
    const float var = fmaxf(fmaf(-ms, ms, sq * (1.0f / DM)), 0.f);
    const float rden = rcp_approx(bf_round(sqrt_approx(bf_round(bf_round(var) + 1e-5f))));
    const float rhi = bf_round(rden);
    mean2 = pack_bf16(ms, ms);
    rhi2 = pack_bf16(rhi, rhi);
    rlo2 = pack_bf16(rden - rhi, rden - rhi);
}
template <int N0, int N>
__device__ __forceinline__ void ln_apply(uint32_t (&u)[N], uint32_t mean2, uint32_t rhi2, uint32_t rlo2, uint8_t* dst) {
#pragma unroll
    for (int i = 0; i < 4; i++) {
        uint32_t o[4];
#pragma unroll
        for (int k = 0; k < 4; k++) {
            const uint32_t d = bf2_sub(u[N0 + 4 * i + k], mean2);
            o[k] = bf2_fma(d, rhi2, bf2_mul(d, rlo2));
        }
#pragma unroll
        for (int k = 0; k < 4; k++) u[N0 + 4 * i + k] = o[k];
        __stcg(reinterpret_cast<uint4*>(dst + i * 131072), make_uint4(o[0], o[1], o[2], o[3]));
    }
}
__device__ __forceinline__ int query_rowblock(int pair, int c, int w, int seg) {
    const int qA = (w ? 0 : 2) + c;
    return 4 * attn_rowblock(pair, seg) + (seg ? 3 - qA : qA);
}

__device__ __noinline__ void fetch_helper(const uint8_t* w_u, uint32_t sb, int w, int lane, int pair, int c) {
    const uint32_t page = sb + SM_REGION + w * PAGE + lane * 16;
    mbar_sleep(sb + BAR_FULL + 5 * 8, 0);
#pragma unroll 1
    for (int i = 0; i < 2; i++) {
        lsu_prefetch(ptr_off(w_u, ((pair * 2 + c) * 4 + i * 2 + (lane >> 4)) * 8192 + 2048 + (lane & 15) * 128));
        __nanosleep(300);
    }
    const unsigned e1 = __ldcg(&g_sync.done) / NCTA + 1;
#pragma unroll 1
    for (int e = 1; e <= 7; e += 2) mbar_sleep(sb + BAR_DONE + 8, (e >> 1) & 1);
    const int rb = out_rows(pair) * 4 + c * 2 + w, kb0 = out_cols(pair);
    const uint8_t* src = ptr_off(g_xn, xn_block(rb, kb0) + lane * 16);
#pragma unroll 1
    for (int i = 0; i < 32; i += 4) {
#pragma unroll
        for (int k = 0; k < 4; k++) cp_async16(page + (i + k) * 512, src + (i + k) * 512 + (i >> 4) * (32768 - 8192));
        __nanosleep(200);
    }
    wait_counter(&g_sync.ffn_done, e1);
    const int r = __ldcg(ptr_off(g_sel, (lane >> 4) * 4)) - rb * 64, ch = lane & 15;
    const uint4 t = __ldcg(ptr_off(g_routed, ((lane >> 4) * 128 + kb0 * 8 + ch) * 16));
    asm volatile("cp.async.wait_all;" ::: "memory");
    __syncwarp();
    if (r >= 0 && r < 64)
        sts128(sb + SM_REGION + w * PAGE + (ch >> 3) * 8192 + r * 128 + (((ch & 7) ^ (r & 7)) << 4), t.x, t.y, t.z, t.w);
    __syncwarp();
    if (lane == 0) mbar_arrive(sb + BAR_G + w * 8);
    PROF(20, 2);
}

__device__ __noinline__ void sync_helper(uint32_t sb, int lane, int pair, int c) {
    const unsigned e1 = __ldcg(&g_sync.done) / NCTA + 1;
    const int ib = out_rows(pair);
    int e = 0, b = 0;
#pragma unroll 1
    for (uint32_t n = 0; (e < 9 || b < 7) && n < SPIN_LIMIT; n++) {
        if (e < 9 && __all_sync(~0u, mbar_test(sb + BAR_DONE + (e & 1) * 8, (e >> 1) & 1))) {
            const int rnd = e > 4, ev = (e - 1) & 3;
            unsigned* flag = e == 0 ? &g_sync.ln
                           : ev < 2 ? ptr_off(g_sync.kv, (rnd * 16 + kv_head(pair) + 8 * ev) * 32)
                                    : ptr_off(g_sync.ctx, (query_rowblock(pair, c, lane & 1, ev & 1) * NH + rnd * 16 + (pair >> 2)) * 4);
            asm volatile("fence.proxy.async.global;\nfence.release.gpu;" ::: "memory");
            if (lane < ((e == 0 || ev < 2) ? 1 : 2)) asm volatile("red.relaxed.gpu.global.add.u32 [%0], 1;" ::"l"(flag) : "memory");
            PROF(10 + e, 2);
            e++;
        }
        if (b < 7 && e > 0 && (b < 4 || (n & POLL_MASK) == 0)) {
            const int i = b == 4 ? lane >> 1 : 8 * b - 24 + ((lane >> 1) & 7);
            const unsigned* cnt = b == 0 ? &g_sync.ln
                                : b == 2 ? ptr_off(g_sync.kvfree, (kv_head(pair) + 8 * (lane & 1)) * 32)
                                : b < 4 ? ptr_off(g_sync.kv, ((b >> 1) * 16 + (pair >> 2)) * 32)
                                        : ptr_off(g_sync.ctx, ((4 * ib + 2 * c + (lane & 1)) * NH + outproj_head(i & 31, ib)) * 4);
            if (__all_sync(~0u, (int)(ld_relaxed(cnt) - e1 * (b == 0 ? NMAIN : b == 2 ? 8 : b < 4 ? 16 : 1)) >= 0)) {
                asm volatile("fence.acquire.gpu;\nfence.proxy.async.global;" ::: "memory");
                __syncwarp();
                if (lane == 0) mbar_arrive(sb + BAR_DEP + b * 8);
                PROF(1 + b, 2);
                b++;
            }
        }
        __nanosleep(150);
    }
}

__device__ __forceinline__ unsigned long long block_max_key(unsigned long long k, unsigned long long* red, int tid) {
#pragma unroll
    for (int o = 16; o; o >>= 1) {
        unsigned long long t = __shfl_xor_sync(~0u, k, o);
        k = t > k ? t : k;
    }
    bar_sync(1, 256);
    if ((tid & 31) == 0) red[tid >> 5] = k;
    bar_sync(1, 256);
    k = red[0];
#pragma unroll
    for (int i = 1; i < 8; i++) k = red[i] > k ? red[i] : k;
    return k;
}

constexpr int FS = FF / 4;
constexpr int FSTAGE = 32768, FNST = 6;
constexpr int FN1 = 2 * (DM / 16), FN2 = FS / 16;

__device__ __forceinline__ void ffn_producer(uint32_t sb, int s, const CUtensorMap* m_gate, const CUtensorMap* m_up,
                                             const CUtensorMap* m_down) {
    wait_counter(&g_sync.ln, (__ldcg(&g_sync.done) / NCTA + 1) * NMAIN);
    int slot = 0, ph = 1;
#pragma unroll 1
    for (int st = 0; st < FN1 + FN2; st++) {
        mbar_sleep(sb + BAR_EMPTY + slot * 8, ph);
        const uint32_t bar = sb + BAR_FULL + slot * 8;
        const bool up = st < FN1;
        mbar_expect_tx(bar, up ? FS * 32 : DM * 32);
        tma_3d_hint(sb + slot * FSTAGE, up ? ((st & 1) ? m_up : m_gate) : m_down, 0,
                    up ? (st >> 1) * 16 : s * FS + (st - FN1) * 16, up ? s * (FS / 64) : 0, bar, POL_FIRST);
        if (++slot == FNST) { slot = 0; ph ^= 1; }
    }
}

__device__ __forceinline__ void ffn_cta(uint8_t* smem, uint32_t sb, int s, unsigned epoch, const __nv_bfloat16* w_r) {
    const int tid = threadIdx.x, lane = tid & 31;
    const int warp = __shfl_sync(~0u, tid >> 5, 0), w = warp >> 2;
    constexpr uint32_t XB = FNST * FSTAGE, HB = XB + 16384, AUX = HB + 14336;
    unsigned long long* red = reinterpret_cast<unsigned long long*>(smem + AUX);
    unsigned* flag = reinterpret_cast<unsigned*>(smem + AUX + 128);
    const unsigned e1 = epoch + 1;
    for (int i = tid; i < (16384 + 14336) / 16; i += 256) reinterpret_cast<uint4*>(smem + XB)[i] = make_uint4(0, 0, 0, 0);
    {
        float wf[32];
#pragma unroll
        for (int i = 0; i < 4; i++) {
            const uint4 t = __ldg(reinterpret_cast<const uint4*>(w_r) + lane + 32 * i);
            const uint32_t tu[4] = {t.x, t.y, t.z, t.w};
#pragma unroll
            for (int k = 0; k < 4; k++) { wf[8 * i + 2 * k] = bf_lo(tu[k]); wf[8 * i + 2 * k + 1] = bf_hi(tu[k]); }
        }
        if (tid == 0) wait_counter(&g_sync.ln, e1 * NMAIN);
        bar_sync(1, 256);
#pragma unroll 1
        for (int r0 = s * (SEQ / 4) + warp * (SEQ / 32); r0 < s * (SEQ / 4) + (warp + 1) * (SEQ / 32); r0 += 4) {
            uint4 t[4][4];
#pragma unroll
            for (int r = 0; r < 4; r++)
#pragma unroll
                for (int i = 0; i < 4; i++) t[r][i] = __ldcg(reinterpret_cast<const uint4*>(g_xn + image_offset(r0 + r, lane) + i * 131072));
            float acc[4];
#pragma unroll
            for (int r = 0; r < 4; r++) {
                float a = 0.f, b = 0.f;
#pragma unroll
                for (int i = 0; i < 4; i++) {
                    const uint32_t tu[4] = {t[r][i].x, t[r][i].y, t[r][i].z, t[r][i].w};
#pragma unroll
                    for (int k = 0; k < 4; k++) {
                        a = fmaf(bf_lo(tu[k]), wf[8 * i + 2 * k], a);
                        b = fmaf(bf_hi(tu[k]), wf[8 * i + 2 * k + 1], b);
                    }
                }
                acc[r] = a + b;
            }
#pragma unroll
            for (int o = 16; o; o >>= 1)
#pragma unroll
                for (int r = 0; r < 4; r++) acc[r] += __shfl_xor_sync(~0u, acc[r], o);
            if (lane < 4) __stcg(&g_r[r0 + lane], bf_round(lane == 0 ? acc[0] : lane == 1 ? acc[1] : lane == 2 ? acc[2] : acc[3]));
        }
        __threadfence();
        bar_sync(1, 256);
        if (tid == 0) {
            red_release(&g_sync.router);
            wait_counter(&g_sync.router, e1 * 4);
        }
        bar_sync(1, 256);
    }
    unsigned long long keys[8];
    unsigned long long best = 0;
#pragma unroll
    for (int i = 0; i < 8; i++) {
        int idx = tid + 256 * i;
        uint32_t b = __float_as_uint(__ldcg(&g_r[idx]) + 0.0f);
        b = (b & 0x80000000u) ? ~b : (b | 0x80000000u);
        keys[i] = ((unsigned long long)b << 32) | (unsigned)(SEQ - 1 - idx);
        best = keys[i] > best ? keys[i] : best;
    }
    const unsigned long long k0 = block_max_key(best, red, tid);
    best = 0;
#pragma unroll
    for (int i = 0; i < 8; i++) best = (keys[i] != k0 && keys[i] > best) ? keys[i] : best;
    const unsigned long long k1 = block_max_key(best, red, tid);
    const int row = SEQ - 1 - (int)((w ? k1 : k0) & 0xffffffffu);
    const int ch = tid & 127;
    const uint4 xrow = __ldcg(reinterpret_cast<const uint4*>(g_xn + image_offset(row, ch)));
    *reinterpret_cast<uint4*>(smem + XB + (ch >> 3) * 1024 + w * 128 + (((ch & 7) ^ w) << 4)) = xrow;
    fence_async_smem();
    bar_sync(1, 256);
    PROF(20, tid >> 7);
    int slot = 0, ph = 0, prev = 0;
    auto next_stage = [&](bool has_prev) {
        wg_commit();
        wg_wait<1>();
        if (has_prev && lane < 2) mbar_arrive(sb + BAR_EMPTY + prev * 8);
        prev = slot;
        if (++slot == FNST) { slot = 0; ph ^= 1; }
    };
    {
        float ag[28], au[28];
#pragma unroll
        for (int i = 0; i < 28; i++) ag[i] = au[i] = 0.f;
#pragma unroll 1
        for (int ks = 0; ks < DM / 16; ks++) {
            const uint64_t db = make_desc(sb + XB + (ks >> 2) * 1024 + (ks & 3) * 32, 16);
            mbar_wait(sb + BAR_FULL + slot * 8, ph);
            uint64_t da = make_desc(sb + slot * FSTAGE + w * (7 * 2048), 16);
            wg_fence();
#pragma unroll
            for (int b = 0; b < 7; b++) wgmma_n8_ta(ag + 4 * b, da + b * 128, db);
            next_stage(ks > 0);
            mbar_wait(sb + BAR_FULL + slot * 8, ph);
            da = make_desc(sb + slot * FSTAGE + w * (7 * 2048), 16);
            wg_fence();
#pragma unroll
            for (int b = 0; b < 7; b++) wgmma_n8_ta(au + 4 * b, da + b * 128, db);
            next_stage(true);
        }
        wg_wait<0>();
        reg_fence(ag);
        reg_fence(au);
        if ((lane & 3) == 0) {
#pragma unroll
            for (int i = 0; i < 28; i++) {
                const int f = (warp & 3) * 16 + (lane >> 2) + (i & 2) * 4, tok = i & 1;
                const float h = bf_round(silu_f(bf_round(ag[i]))) * bf_round(au[i]);
                *reinterpret_cast<__nv_bfloat16*>(smem + HB + (w * 7 + (i >> 2)) * 1024 + tok * 128 + (((f >> 3) ^ tok) << 4) + (f & 7) * 2) =
                    __float2bfloat16_rn(h);
            }
        }
    }
    fence_async_smem();
    bar_sync(1, 256);
    PROF(21, tid >> 7);
    {
        float ay[32];
#pragma unroll
        for (int i = 0; i < 32; i++) ay[i] = 0.f;
#pragma unroll 1
        for (int ks = 0; ks < FN2; ks++) {
            const uint64_t db = make_desc(sb + HB + (ks >> 2) * 1024 + (ks & 3) * 32, 16);
            mbar_wait(sb + BAR_FULL + slot * 8, ph);
            const uint64_t da = make_desc(sb + slot * FSTAGE + w * (8 * 2048), 16);
            wg_fence();
#pragma unroll
            for (int b = 0; b < 8; b++) wgmma_n8_ta(ay + 4 * b, da + b * 128, db);
            next_stage(true);
        }
        wg_wait<0>();
        reg_fence(ay);
        if ((lane & 3) == 0) {
#pragma unroll
            for (int i = 0; i < 32; i++)
                g_ypart[(s * 2 + (i & 1)) * DM + (w * 8 + (i >> 2)) * 64 + (warp & 3) * 16 + (lane >> 2) + (i & 2) * 4] = ay[i];
        }
    }
    PROF(23, tid >> 7);
    __threadfence();
    bar_sync(1, 256);
    if (tid == 0) {
        *flag = atomicAdd(&g_sync.ffn_ticket, 1u) == epoch * 4 + 3;
        __threadfence();
    }
    bar_sync(1, 256);
    if (*flag) {
        const float sg = bf_round(__fdividef(1.0f, 1.0f + __expf(-__ldcg(&g_r[row]))));
        const uint32_t xu[4] = {xrow.x, xrow.y, xrow.z, xrow.w};
        uint32_t o[4];
#pragma unroll
        for (int k = 0; k < 4; k++) {
            float y0 = 0.f, y1 = 0.f;
#pragma unroll
            for (int q = 0; q < 4; q++) {
                const float2 y = __ldcg(reinterpret_cast<const float2*>(&g_ypart[(q * 2 + w) * DM + ch * 8 + 2 * k]));
                y0 += y.x; y1 += y.y;
            }
            o[k] = pack_bf16(bf_lo(xu[k]) + bf_round(bf_round(y0) * sg), bf_hi(xu[k]) + bf_round(bf_round(y1) * sg));
        }
        g_routed[w * 128 + ch] = make_uint4(o[0], o[1], o[2], o[3]);
        if (ch == 0) g_sel[w] = row;
        bar_sync(1, 256);
        if (tid == 0) red_release(&g_sync.ffn_done);
    }
}

__device__ __forceinline__ uint32_t slab_addr(uint32_t stg, int lane, int s) {
    const int row = ((lane >> 3) & 1) * 8 + (lane & 7);
    const int chunk = 2 * (s & 3) + (lane >> 4);
    return stg + row * 128 + (s >> 2) * 8192 + ((chunk ^ (lane & 7)) << 4);
}

constexpr float SM_SCALE = 0.08838834764831845f * 1.4426950408889634f;
constexpr float SUM_HI = 1048576.f, SUM_LO = 1.0f / 1048576.f;

template <int I0, int I1, int J0>
__device__ __forceinline__ void mask_range(float (&S)[64], float limf) {
#pragma unroll
    for (int i = I0; i < I1; i++) {
        const int j = i >> 2;
        float t;
        asm("add.sat.f32 %0, %1, %2;" : "=f"(t) : "f"((float)(32 * (j >> 2) + 2 * (j & 3) + (i & 1) - (i & 2) * 4)), "f"(-limf));
        S[4 * J0 + i] = fmaf(t, -1e30f, S[4 * J0 + i]);
    }
}
template <int J0>
__device__ __forceinline__ void mask_half(float (&S)[64], float limf, int v) {
    asm volatile("" : "+f"(limf));
    if (v < 2) {
        mask_range<0, 16, J0>(S, limf);
#pragma unroll
        for (int i = 16; i < 32; i++) S[4 * J0 + i] = -1e30f;
    } else {
        mask_range<16, 32, J0>(S, limf);
    }
}
__device__ __forceinline__ void issue_qk(float (&S)[64], const uint32_t (&Q)[32], uint32_t d0) {
#pragma unroll
    for (int s = 0; s < 8; s++)
        wgmma_n128_rs<1>(S, Q[4 * s], Q[4 * s + 1], Q[4 * s + 2], Q[4 * s + 3], d0 + s * 128, s > 0);
}
__device__ __forceinline__ void issue_qk_half(float (&T)[32], const uint32_t (&Q)[32], uint32_t d0) {
#pragma unroll
    for (int s = 0; s < 8; s++) wgmma_n64_rs_tb(T, Q[4 * s], Q[4 * s + 1], Q[4 * s + 2], Q[4 * s + 3], d0 + s * 128, s > 0);
}
template <int H>
__device__ __forceinline__ void issue_pv(float (&O)[64], const uint32_t (&Pm)[32], uint32_t d0, int acc) {
#pragma unroll
    for (int s = 4 * H; s < 4 * H + 4; s++)
        wgmma_n128_rs<0>(O, Pm[4 * s], Pm[4 * s + 1], Pm[4 * s + 2], Pm[4 * s + 3], d0 + H * (PAGE >> 4) + (s & 3) * 2, s > 0 ? 1 : acc);
}
template <int J0, int J1>
__device__ __forceinline__ void exp_groups(const float (&S)[64], uint32_t (&Pm)[32], float (&sum)[2]) {
#pragma unroll
    for (int i = 2 * J0; i < 2 * J1; i++) asm volatile("" : "+r"(Pm[i])::"memory");
#pragma unroll
    for (int j = J0; j < J1; j++) {
        const float e0 = ex2(S[4 * j]), e1 = ex2(S[4 * j + 1]), e2 = ex2(S[4 * j + 2]), e3 = ex2(S[4 * j + 3]);
        sum[0] = (j ? sum[0] + e0 : e0) + e1;
        sum[1] = (j ? sum[1] + e2 : e2) + e3;
        Pm[2 * j] = pack_bf16(e0, e1);
        Pm[2 * j + 1] = pack_bf16(e2, e3);
    }
}
__device__ __forceinline__ void shift_rows(float (&S)[64], float d0, float d1) {
#pragma unroll
    for (int j = 0; j < 16; j++) {
        S[4 * j] -= d0; S[4 * j + 1] -= d0; S[4 * j + 2] -= d1; S[4 * j + 3] -= d1;
    }
}
__device__ constexpr int chunk_src(int i) { return 4 * (4 * (i >> 3) + (i & 3)) + 2 * ((i >> 2) & 1); }
enum : uint32_t { CTL_FIRST = 1, CTL_SWITCH = 2, CTL_LAST = 4, CTL_HALF = 128, CTL_MASKHI = 256, CTL_WOUT = 512, CTL_PVHALF = 1024, CTL_PVACC = 16384,
                  CTL_SHIFT = 32768 };
__device__ __forceinline__ float quad_sum(float v) {
    v += __shfl_xor_sync(~0u, v, 1);
    return v + __shfl_xor_sync(~0u, v, 2);
}

__device__ __forceinline__ void store_part(uint8_t* base, uint32_t row_bits, int p, const uint32_t (&pk)[64], uint64_t pol) {
    asm volatile("{\n.reg .b64 d0, d1;\nxor.b64 d0, %0, %1;\nxor.b64 d1, d0, 64;\n"
                 "TS: .branchtargets P0, P1, P2, P3, P4, P5, P6, P7;\n"
                 "brx.idx.uni %2, TS;\n"
                 "P0:\n st.global.cg.L2::cache_hint.v4.u32 [d0 + 0], {%3, %4, %5, %6}, %67;\n st.global.cg.L2::cache_hint.v4.u32 [d1 + 0], {%11, %12, %13, %14}, %67;\n bra.uni DONE;\n"
                 "P1:\n st.global.cg.L2::cache_hint.v4.u32 [d0 + 0], {%7, %8, %9, %10}, %67;\n st.global.cg.L2::cache_hint.v4.u32 [d1 + 0], {%15, %16, %17, %18}, %67;\n bra.uni DONE;\n"
                 "P2:\n st.global.cg.L2::cache_hint.v4.u32 [d0 + 16384], {%19, %20, %21, %22}, %67;\n st.global.cg.L2::cache_hint.v4.u32 [d1 + 16384], {%27, %28, %29, %30}, %67;\n bra.uni DONE;\n"
                 "P3:\n st.global.cg.L2::cache_hint.v4.u32 [d0 + 16384], {%23, %24, %25, %26}, %67;\n st.global.cg.L2::cache_hint.v4.u32 [d1 + 16384], {%31, %32, %33, %34}, %67;\n bra.uni DONE;\n"
                 "P4:\n st.global.cg.L2::cache_hint.v4.u32 [d0 + 65536], {%35, %36, %37, %38}, %67;\n st.global.cg.L2::cache_hint.v4.u32 [d1 + 65536], {%43, %44, %45, %46}, %67;\n bra.uni DONE;\n"
                 "P5:\n st.global.cg.L2::cache_hint.v4.u32 [d0 + 65536], {%39, %40, %41, %42}, %67;\n st.global.cg.L2::cache_hint.v4.u32 [d1 + 65536], {%47, %48, %49, %50}, %67;\n bra.uni DONE;\n"
                 "P6:\n st.global.cg.L2::cache_hint.v4.u32 [d0 + 81920], {%51, %52, %53, %54}, %67;\n st.global.cg.L2::cache_hint.v4.u32 [d1 + 81920], {%59, %60, %61, %62}, %67;\n bra.uni DONE;\n"
                 "P7:\n st.global.cg.L2::cache_hint.v4.u32 [d0 + 81920], {%55, %56, %57, %58}, %67;\n st.global.cg.L2::cache_hint.v4.u32 [d1 + 81920], {%63, %64, %65, %66}, %67;\n bra.uni DONE;\n"
                 "DONE:\n}\n"
                 ::"l"(base), "l"((uint64_t)((p & 1) ? row_bits : 0)), "r"(p), "r"(pk[0]), "r"(pk[1]), "r"(pk[2]), "r"(pk[3]), "r"(pk[4]), "r"(pk[5]), "r"(pk[6]), "r"(pk[7]), "r"(pk[8]), "r"(pk[9]), "r"(pk[10]), "r"(pk[11]), "r"(pk[12]), "r"(pk[13]), "r"(pk[14]), "r"(pk[15]), "r"(pk[16]), "r"(pk[17]), "r"(pk[18]), "r"(pk[19]), "r"(pk[20]), "r"(pk[21]), "r"(pk[22]), "r"(pk[23]), "r"(pk[24]), "r"(pk[25]), "r"(pk[26]), "r"(pk[27]), "r"(pk[28]), "r"(pk[29]), "r"(pk[30]), "r"(pk[31]), "r"(pk[32]), "r"(pk[33]), "r"(pk[34]), "r"(pk[35]), "r"(pk[36]), "r"(pk[37]), "r"(pk[38]), "r"(pk[39]), "r"(pk[40]), "r"(pk[41]), "r"(pk[42]), "r"(pk[43]), "r"(pk[44]), "r"(pk[45]), "r"(pk[46]), "r"(pk[47]), "r"(pk[48]), "r"(pk[49]), "r"(pk[50]), "r"(pk[51]), "r"(pk[52]), "r"(pk[53]), "r"(pk[54]), "r"(pk[55]), "r"(pk[56]), "r"(pk[57]), "r"(pk[58]), "r"(pk[59]), "r"(pk[60]), "r"(pk[61]), "r"(pk[62]), "r"(pk[63]), "l"(pol)
                 : "memory");
}

__device__ __forceinline__ void store_part4(uint8_t* d0, int p, const uint32_t (&pk)[64]) {
    asm volatile("{\n.reg .b64 d1;\nxor.b64 d1, %0, 64;\n"
                 "TS: .branchtargets P0, P1, P2, P3;\n"
                 "brx.idx.uni %1, TS;\n"
                 "P0:\n st.global.cg.v4.u32 [%0 + 0], {%2, %3, %4, %5};\n st.global.cg.v4.u32 [d1 + 0], {%10, %11, %12, %13};\n bra.uni DONE;\n"
                 "P1:\n st.global.cg.v4.u32 [%0 + 1024], {%6, %7, %8, %9};\n st.global.cg.v4.u32 [d1 + 1024], {%14, %15, %16, %17};\n bra.uni DONE;\n"
                 "P2:\n st.global.cg.v4.u32 [%0 + 16384], {%18, %19, %20, %21};\n st.global.cg.v4.u32 [d1 + 16384], {%26, %27, %28, %29};\n bra.uni DONE;\n"
                 "P3:\n st.global.cg.v4.u32 [%0 + 17408], {%22, %23, %24, %25};\n st.global.cg.v4.u32 [d1 + 17408], {%30, %31, %32, %33};\n bra.uni DONE;\n"
                 "DONE:\n}\n"
                 ::"l"(d0), "r"(p), "r"(pk[0]), "r"(pk[1]), "r"(pk[2]), "r"(pk[3]), "r"(pk[4]), "r"(pk[5]), "r"(pk[6]), "r"(pk[7]), "r"(pk[8]), "r"(pk[9]), "r"(pk[10]), "r"(pk[11]), "r"(pk[12]), "r"(pk[13]), "r"(pk[14]), "r"(pk[15]), "r"(pk[16]), "r"(pk[17]), "r"(pk[18]), "r"(pk[19]), "r"(pk[20]), "r"(pk[21]), "r"(pk[22]), "r"(pk[23]), "r"(pk[24]), "r"(pk[25]), "r"(pk[26]), "r"(pk[27]), "r"(pk[28]), "r"(pk[29]), "r"(pk[30]), "r"(pk[31])
                 : "memory");
}

__device__ __forceinline__ void consumer(uint32_t sb, int pair, int c, uint8_t* out, const uint8_t* x) {
    const int tid = threadIdx.x;
    const int warp = __shfl_sync(~0u, tid >> 5, 0);
    const int w = warp >> 2, v = warp & 3;
    const int lane = __shfl_sync(~0u, tid & 31, tid & 31);

    const uint32_t empty_rel = lane == 2 ? mapa(sb + BAR_EMPTYL, c) : mapa(sb + BAR_EMPTY, lane & 1);
    auto release = [&](uint32_t grp) {
        if (lane < 3) mbar_arrive_cluster(empty_rel + (grp & 7) * 8);
    };
    auto wait_full = [&](uint32_t grp) { mbar_wait(sb + BAR_FULL + (grp & 7) * 8, (grp >> 3) & 1); };

    uint32_t g = 0;
    const uint32_t stg = sb + SM_REGION + w * PAGE + v * 2048;
    const uint32_t chunk0 = (lane >> 2) * 128 + (((lane & 3) ^ (lane >> 2)) << 4);
    auto mark_done = [&](int odd) {
        __syncwarp();
        if (lane == 0) mbar_arrive(sb + BAR_DONE + odd * 8);
    };
    auto ctx_dst = [&](int rnd, int seg) {
        const int rb = query_rowblock(pair, c, w, seg);
        return ptr_off(g_ctx, ((rb >> 1) * 64 + (rnd * 16 + (pair >> 2)) * 2) * PAGE + (rb & 1) * 8192 + v * 2048);
    };

    uint32_t ctl_tab;
    {
        const int t = lane, firstB = 2 * attn_rowblock(pair, 0) + 2 - w;
        auto is_half = [&](int u) { return (u == firstB - 1 || u == 16) && c == (u >= firstB); };
        auto block = [&](int u) { return u + (w == 1 && u >= firstB); };
        auto place = [](int j) { return ((j & 15) << 3) | ((j - (j * 43 >> 8) * 6) << 11); };
        const int jv = min(2 * block(t - 1) + 2, 35), jk = t == 17 ? jv : max(2 * block(t) - 1, 0);
        const bool diag = t == firstB - 1 || t == 16;
        ctl_tab = ((t == 0 || t == firstB) ? CTL_FIRST : 0) | (t == firstB ? CTL_SWITCH : 0) | (t == 17 ? CTL_LAST : 0) |
                  (diag ? (is_half(t) ? CTL_HALF : CTL_MASKHI) : 0) | (t == firstB + 1 ? CTL_WOUT : 0) |
                  (is_half(t - 1) ? CTL_PVHALF : 0) | ((t == 1 || t == firstB + 1) ? 0 : CTL_PVACC) |
                  place(jk) | ((place(jv) | (t ? 3 : 0)) << 16);
    }

    uint32_t pk[64];
#pragma unroll
    for (int i = 0; i < 64; i++) asm volatile("" : "=r"(pk[i]));
    uint8_t* pend = nullptr;
    uint32_t prow = 0x400;
    auto write_part = [&](int p, uint64_t pol = POL_NORMAL) { store_part(pend, prow, p, pk, pol); };
    if (w == 1) bar_arrive(2, 256);

    for (int item = 0; item < 6; item++) {
        if ((0x1B >> item) & 1) {
            constexpr int nk = DC / 64;
            float acc[128];
            auto issue_kblock = [&](int first_acc) {
                wait_full(g);
                const uint32_t pg = sb + (g & 3) * (3 * PAGE);
                const uint64_t da = make_desc(pg + w * 8192, 16), db = make_desc(pg + PAGE, 16);
                wg_fence();
                wgmma_n256_ss(acc, da, db, first_acc);
                wgmma_n256_ss(acc, da + 128, db + 2, 1);
                wgmma_n256_ss(acc, da + 256, db + 4, 1);
                wgmma_n256_ss(acc, da + 384, db + 6, 1);
                wg_commit();
                g++;
            };
            if (item == 0) PROF(17, w);
            issue_kblock(0);
            if (item == 0) PROF(1, w);
            if (item == 0 && w == 0) PROF_GT(1);
            const int nparts = item == 0 ? 0 : (item == 3 ? 4 : 8);
            const int ln_row = (pair * 2 + c) * 16 + warp * 2;
            if (item == 0) {
                const uint8_t* src = ptr_off(x, ln_row * (DM * 2) + lane * 16);
#pragma unroll
                for (int i = 0; i < 8; i++) {
                    const uint4 t = __ldcg(reinterpret_cast<const uint4*>(src + i * 512));
                    pk[4 * i] = t.x; pk[4 * i + 1] = t.y; pk[4 * i + 2] = t.z; pk[4 * i + 3] = t.w;
                }
            }
#pragma unroll 1
            for (int kb = 1; kb < nk; kb++) {
                if (kb == nk - 1 && w == 1) bar_sync(4, 256);
                issue_kblock(1);
                if (kb == nk - 1 && w == 0) bar_arrive(4, 256);
                wg_wait<1>();
                release(g - 2);
                if (kb <= nparts) {
                    if (item == 4 && kb == 1) mbar_wait(sb + BAR_DEP + 16, 0);
                    write_part(kb - 1, item == 3 ? POL_FIRST : POL_NORMAL);
                    if (kb == nk - 1) write_part(nk - 1);
                    if (kb == nparts || kb == nk - 1) mark_done(item != 3);
                }
                if (g < 8) {
                    float s[2], q[2];
                    if (g == 4) {
                        ln_sums<0>(pk, s[0], q[0]);
                        pk[32] = __float_as_uint(s[0]); pk[33] = __float_as_uint(q[0]);
                    }
                    if (g == 5) {
                        ln_sums<16>(pk, s[1], q[1]);
                        pk[34] = __float_as_uint(s[1]); pk[35] = __float_as_uint(q[1]);
                    }
                    if (g == 6) {
#pragma unroll
                        for (int r = 0; r < 2; r++) { s[r] = __uint_as_float(pk[32 + 2 * r]); q[r] = __uint_as_float(pk[33 + 2 * r]); }
                        const bool hi = lane & 16, od = lane & 8;
                        float a = hi ? s[1] : s[0], b = hi ? q[1] : q[0];
                        a += __shfl_xor_sync(~0u, hi ? s[0] : s[1], 16);
                        b += __shfl_xor_sync(~0u, hi ? q[0] : q[1], 16);
                        float t = od ? b : a;
                        t += __shfl_xor_sync(~0u, od ? a : b, 8);
#pragma unroll
                        for (int o = 4; o; o >>= 1) t += __shfl_xor_sync(~0u, t, o);
#pragma unroll
                        for (int r = 0; r < 2; r++) {
                            s[r] = __shfl_sync(~0u, t, 16 * r);
                            q[r] = __shfl_sync(~0u, t, 16 * r + 8);
                        }
                        ln_finish(s[0], q[0], pk[36], pk[37], pk[38]);
                        ln_finish(s[1], q[1], pk[39], pk[40], pk[41]);
                    }
                    if (g == 6) ln_apply<0>(pk, pk[36], pk[37], pk[38], ptr_off(g_xn, image_offset(ln_row, lane)));
                    if (g == 7) {
                        ln_apply<16>(pk, pk[39], pk[40], pk[41], ptr_off(g_xn, image_offset(ln_row + 1, lane)));
                        mark_done(0);
                    }
                }
            }
            wg_wait<0>();
            reg_fence(acc);
            release(g - 1);
            PROF(2 + 2 * item, w);
            if (w == 0) PROF_GT(2 + 2 * item);
#pragma unroll
            for (int i = 0; i < 64; i++) pk[i] = pack_bf16(acc[chunk_src(i)], acc[chunk_src(i) + 1]);
            const uint32_t vrow = (v >> 1) * 32 + (lane >> 3) * 8 + (v & 1) * 4 + ((lane >> 2) & 1);
            pend = ptr_off(g_kv, ((kv_head(pair) + (item == 1 || item == 4 ? 8 : 0)) * 16 + kv_tokens(pair) * 2) * 65536 + w * 8192 +
                                     (c ? 32768 + vrow * 128 + (((lane & 3) ^ (vrow & 7)) << 4) : v * 2048 + chunk0));
            prow = c ? 0x120 : 0x400;
            PROF(3 + 2 * item, w);
            continue;
        }

        float O[64], S[64];
        auto issue_q = [&](int first_acc) {
            wait_full(g);
            const uint32_t pg = sb + (g & 3) * (3 * PAGE);
            const uint64_t da = make_desc(pg + w * 8192, 16), db = make_desc(pg + 2 * PAGE, 8192);
            const uint64_t dab = make_desc(pg + PAGE + (1 - w) * 8192, 16);
            wg_fence();
#pragma unroll
            for (int q = 0; q < 4; q++) wgmma_n128_ss(S, da + 2 * q, db + 128 * q, q ? 1 : first_acc);
            wg_commit();
#pragma unroll
            for (int q = 0; q < 4; q++) wgmma_n128_ss(O, dab + 2 * q, db + 128 * q, q ? 1 : first_acc);
            wg_commit();
            g++;
        };
        issue_q(0);
#pragma unroll 1
        for (int kb = 1; kb < DM / 64; kb++) {
            if (kb == DM / 64 - 2 && w == 1) bar_sync(4, 256);
            issue_q(1);
            if (kb == DM / 64 - 1 && w == 0) bar_arrive(4, 256);
            wg_wait<2>();
            release(g - 2);
            if (kb <= 8) {
                write_part(kb - 1);
                if (kb == 8) mark_done(0);
            }
        }
        uint32_t Q[32], Pm[32];
#pragma unroll
        for (int i = 0; i < 32; i++) Pm[i] = pk[32 + i];
        float lim = (float)(v * 16 + (lane >> 2) - 8 * (lane & 3));
        float mc[2] = {0.f, 0.f}, l[2] = {0.f, 0.f}, scale[2] = {0.f, 0.f}, sum[2];
        uint32_t ctl = __shfl_sync(~0u, ctl_tab, 0), nxt = __shfl_sync(~0u, ctl_tab, 1);
        int t = 1;
        asm volatile("" : "+f"(lim), "+f"(mc[0]), "+f"(mc[1]), "+f"(l[0]), "+f"(l[1]), "+r"(ctl), "+r"(nxt), "+r"(t));
        wg_wait<1>();
        reg_fence(S);
#pragma unroll
        for (int i = 0; i < 32; i++) Q[i] = pack_bf16(S[2 * i] * SM_SCALE, S[2 * i + 1] * SM_SCALE);
        reg_fence(Q);
        wait_full(g);
        wg_wait<0>();
        reg_fence(O);
        release(g - 1);
        PROF(2 + 2 * item, w);
        if (w == 0) PROF_GT(2 + 2 * item);

        const uint32_t qaddr = stg + lane * 16;
        auto put_queries = [&](const float (&A)[64]) {
#pragma unroll
            for (int i = 0; i < 8; i++)
                sts128(qaddr + (i >> 2) * 8192 + (i & 3) * 512, pack_bf16(A[8 * i] * SM_SCALE, A[8 * i + 1] * SM_SCALE), pack_bf16(A[8 * i + 2] * SM_SCALE, A[8 * i + 3] * SM_SCALE),
                       pack_bf16(A[8 * i + 4] * SM_SCALE, A[8 * i + 5] * SM_SCALE), pack_bf16(A[8 * i + 6] * SM_SCALE, A[8 * i + 7] * SM_SCALE));
        };
        auto get_queries = [&]() {
#pragma unroll
            for (int i = 0; i < 8; i++) lds128(qaddr + (i >> 2) * 8192 + (i & 3) * 512, Q[4 * i], Q[4 * i + 1], Q[4 * i + 2], Q[4 * i + 3]);
        };
        const uint32_t kdesc0 = (uint32_t)make_desc(sb, PAGE), vdesc0 = (uint32_t)make_desc(sb, 16);
        auto wait_block = [&](uint32_t word) { mbar_wait(sb + BAR_FULL + (word & 56), (word >> 6) & 1); };
        auto write_out = [&](auto early) {
            uint8_t* dst = ctx_dst(item == 5, 0);
            uint8_t* d[2] = {ptr_off(dst, chunk0), ptr_off(dst, chunk0 ^ 64)};
#pragma unroll
            for (int i = early.value ? 0 : WN; i < (early.value ? WN : 8); i++) {
                const float sc = scale[i & 1];
                uint32_t q[4];
#pragma unroll
                for (int k = 0; k < 4; k++) q[k] = pack_bf16(O[chunk_src(4 * i + k)] * sc, O[chunk_src(4 * i + k) + 1] * sc);
                if (early.value && i > 0) {
#pragma unroll
                    for (int k = 0; k < 4; k++) O[4 * (i - 1) + k] = __uint_as_float(q[k]);
                }
                stg_hint(d[(i >> 1) & 1] + (i >> 2) * PAGE + (i & 1) * 1024, q[0], q[1], q[2], q[3], item == 2 ? POL_FIRST : POL_NORMAL);
            }
            if (!early.value) mark_done(1);
        };
        put_queries(O);
        bar_sync(2 + w, 256);
        if (!(ctl & CTL_HALF)) {
            wg_fence();
            issue_qk(S, Q, kdesc0);
            wg_commit();
            wg_fence();
            wg_commit();
            wg_commit();
            bar_arrive(3 - w, 256);
            wg_wait<2>();
            reg_fence(S);
        } else {
            float T[32];
            wg_fence();
            issue_qk_half(T, Q, kdesc0);
            wg_commit();
            wg_fence();
            wg_commit();
            wg_commit();
            bar_arrive(3 - w, 256);
            wg_wait<2>();
            reg_fence(T);
#pragma unroll
            for (int i = 0; i < 32; i++) S[i] = T[i];
        }
        for (;;) {
            const bool kready = mbar_try(sb + BAR_FULL + (nxt & 56), (nxt >> 6) & 1);
            if (ctl & (CTL_HALF | CTL_MASKHI | CTL_SHIFT)) {
                if (ctl & CTL_HALF) mask_half<0>(S, lim, v);
                if (ctl & CTL_MASKHI) mask_half<8>(S, lim, v);
                if (ctl & CTL_SHIFT) shift_rows(S, mc[0], mc[1]);
            }
            float early[4 * EARLY];
#pragma unroll
            for (int j = 0; j < EARLY; j++) {
#pragma unroll
                for (int i = 4 * j; i < 4 * j + 4; i++) early[i] = ex2(S[i]);
                sum[0] = (j ? sum[0] + early[4 * j] : early[4 * j]) + early[4 * j + 1];
                sum[1] = (j ? sum[1] + early[4 * j + 2] : early[4 * j + 2]) + early[4 * j + 3];
            }
            const uint32_t tie = __float_as_uint(sum[0]) & __float_as_uint(sum[1]) & (ctl & 0x80000000u);
            if (lane < 3) mbar_arrive_cluster(empty_rel + tie + (ctl & 56));
            wg_wait<1>();
#pragma unroll
            for (int j = 0; j < EARLY; j++) {
                asm volatile("" : "+r"(Pm[2 * j]), "+r"(Pm[2 * j + 1])::"memory");
                Pm[2 * j] = pack_bf16(early[4 * j], early[4 * j + 1]);
                Pm[2 * j + 1] = pack_bf16(early[4 * j + 2], early[4 * j + 3]);
            }
            exp_groups<EARLY, 8>(S, Pm, sum);
            const bool half = ctl & CTL_HALF;
            if (!half) {
                wg_wait<0>();
                reg_fence(O);
                if (lane < ((ctl >> 16) & 3)) mbar_arrive_cluster(empty_rel + ((ctl >> 16) & 56));
                exp_groups<8, 16>(S, Pm, sum);
            } else {
                asm volatile("wgmma.wait_group.sync.aligned 0;\n" ::: "memory");
                reg_fence(O);
                if (lane < ((ctl >> 16) & 3)) asm volatile("mbarrier.arrive.shared::cluster.b64 _, [%0];\n" ::"r"(empty_rel + ((ctl >> 16) & 56)) : "memory");
            }
            const bool over = !(sum[0] + sum[1] <= SUM_HI);
            const bool first = ctl & CTL_FIRST, suspect = over || (first && !(fminf(sum[0], sum[1]) >= SUM_LO));
            if (__any_sync(~0u, suspect || !kready) || (((ctl & CTL_SWITCH) | (nxt & (CTL_SWITCH | CTL_LAST | CTL_HALF))) != 0)) {
                if (!kready) wait_block(nxt);
                bool bad = __any_sync(~0u, suspect);
                if (bad) {
                    uint32_t b0 = __ballot_sync(~0u, sum[0] >= SUM_LO), b1 = __ballot_sync(~0u, sum[1] >= SUM_LO);
                    b0 |= b0 >> 1; b1 |= b1 >> 1;
                    b0 |= b0 >> 2; b1 |= b1 >> 2;
                    bad = __any_sync(~0u, over) || (first && (b0 & b1 & 0x11111111u) != 0x11111111u);
                }
                if (bad) {
                    float d0 = fmaxf(S[0], S[1]), d1 = fmaxf(S[2], S[3]);
#pragma unroll
                    for (int j = 1; j < 8; j++) {
                        d0 = fmaxf(d0, fmaxf(S[4 * j], S[4 * j + 1]));
                        d1 = fmaxf(d1, fmaxf(S[4 * j + 2], S[4 * j + 3]));
                    }
                    if (!half) {
#pragma unroll
                        for (int j = 8; j < 16; j++) {
                            d0 = fmaxf(d0, fmaxf(S[4 * j], S[4 * j + 1]));
                            d1 = fmaxf(d1, fmaxf(S[4 * j + 2], S[4 * j + 3]));
                        }
                    }
                    d0 = fmaxf(d0, __shfl_xor_sync(~0u, d0, 1));
                    d1 = fmaxf(d1, __shfl_xor_sync(~0u, d1, 1));
                    d0 = fmaxf(d0, __shfl_xor_sync(~0u, d0, 2));
                    d1 = fmaxf(d1, __shfl_xor_sync(~0u, d1, 2));
                    if (!first) {
                        d0 = fmaxf(d0, 0.f);
                        d1 = fmaxf(d1, 0.f);
                        const float a0 = ex2(-d0), a1 = ex2(-d1);
#pragma unroll
                        for (int j = 0; j < 16; j++) {
                            O[4 * j] *= a0; O[4 * j + 1] *= a0; O[4 * j + 2] *= a1; O[4 * j + 3] *= a1;
                        }
                        l[0] *= a0; l[1] *= a1;
                    }
                    mc[0] += d0; mc[1] += d1;
                    ctl_tab |= CTL_SHIFT;
                    nxt |= CTL_SHIFT;
                    shift_rows(S, d0, d1);
                    exp_groups<0, 8>(S, Pm, sum);
                    if (!half) exp_groups<8, 16>(S, Pm, sum);
                }
                if (ctl & CTL_SWITCH) write_out(std::true_type());
                if (nxt & CTL_LAST) break;
                if (nxt & CTL_SWITCH) {
                    get_queries();
                    nxt &= ~CTL_SHIFT;
                    ctl_tab &= ~CTL_SHIFT;
                }
                if (nxt & CTL_HALF) {
                    ctl = nxt;
                    float T[32];
                    bar_sync(2 + w, 256);
                    wg_fence();
                    issue_qk_half(T, Q, kdesc0 + (ctl & 0x3800));
                    wg_commit();
                    l[0] += sum[0]; l[1] += sum[1];
                    nxt = __shfl_sync(~0u, ctl_tab, ++t);
                    wait_block(ctl >> 16);
                    const uint32_t vdesc = vdesc0 + ((ctl >> 16) & 0x3800);
                    wg_fence();
                    issue_pv<0>(O, Pm, vdesc, ctl & CTL_PVACC);
                    wg_commit();
                    issue_pv<1>(O, Pm, vdesc, 1);
                    wg_commit();
                    bar_arrive(3 - w, 256);
                    wg_wait<2>();
                    reg_fence(T);
#pragma unroll
                    for (int i = 0; i < 32; i++) S[i] = T[i];
                    continue;
                }
            }
            ctl = nxt;
            bar_sync(2 + w, 256);
            wg_fence();
            issue_qk(S, Q, kdesc0 + (ctl & 0x3800));
            wg_commit();
            l[0] += sum[0]; l[1] += sum[1];
            nxt = __shfl_sync(~0u, ctl_tab, ++t);
            if (ctl & (CTL_SWITCH | CTL_WOUT)) {
                if (ctl & CTL_SWITCH) {
                    scale[0] = rcp_approx(quad_sum(l[0]));
                    scale[1] = rcp_approx(quad_sum(l[1]));
                    l[0] = l[1] = mc[0] = mc[1] = 0.f;
                    if (w == 1) { release((ctl >> 3) - 2); release((ctl >> 3) + 1); }
                } else {
                    write_out(std::false_type());
                }
            }
            wait_block(ctl >> 16);
            const uint32_t vdesc = vdesc0 + ((ctl >> 16) & 0x3800);
            if (!(ctl & CTL_PVHALF)) {
                wg_fence();
                issue_pv<0>(O, Pm, vdesc, ctl & CTL_PVACC);
                wg_commit();
                issue_pv<1>(O, Pm, vdesc, 1);
                wg_commit();
            } else {
                wg_fence();
                issue_pv<0>(O, Pm, vdesc, ctl & CTL_PVACC);
                wg_commit();
                wg_commit();
            }
            bar_arrive(3 - w, 256);
            wg_wait<2>();
            reg_fence(S);
        }
        g += 36;
        const uint32_t vdesc = vdesc0 + (nxt & 0x3800);
        if (nxt & CTL_PVHALF) {
            wg_fence();
            issue_pv<0>(O, Pm, vdesc, nxt & CTL_PVACC);
            wg_commit();
        } else {
            wg_fence();
            issue_pv<0>(O, Pm, vdesc, nxt & CTL_PVACC);
            issue_pv<1>(O, Pm, vdesc, 1);
            wg_commit();
        }
        l[0] += sum[0]; l[1] += sum[1];
        ctl_tab = (ctl_tab & ~(0x00780078u | CTL_SHIFT)) | ((ctl_tab + 0x00200020u) & 0x00780078u);
        const float i0 = rcp_approx(quad_sum(l[0])), i1 = rcp_approx(quad_sum(l[1]));
        const uint32_t tie = __float_as_uint(i0) & __float_as_uint(i1) & (nxt & 0x80000000u);
        if (lane + tie < (w ? 0 : 3)) mbar_arrive_cluster(empty_rel + ((g - 3) & 7) * 8);
        auto finish_attention = [&](uint32_t next) {
            reg_fence(O);
            if (w == 0) release(next - 2);
            release(next - 1);
#pragma unroll
            for (int i = 0; i < 32; i++) {
                const float sc = (i & 4) ? i1 : i0;
                pk[i] = pack_bf16(O[chunk_src(i)] * sc, O[chunk_src(i) + 1] * sc);
            }
            pend = ptr_off(ctx_dst(item == 5, 1), chunk0);
            PROF(3 + 2 * item, w);
            if (w == 0) PROF_GT(3 + 2 * item);
        };
        if (item != 5) {
            wg_wait<0>();
            finish_attention(g);
            prow = 0x400;
#pragma unroll
            for (int i = 32; i < 64; i++) pk[i] = Pm[i - 32];
            continue;
        }

        float acc[64];
        uint32_t slot = 0;
        auto issue_out = [&](int first_acc) {
            wait_full(g);
            const uint64_t da = make_desc(sb + slot + w * 8192, 16), db = make_desc(sb + slot + PAGE, 8192);
            wg_fence();
#pragma unroll
            for (int q = 0; q < 4; q++) wgmma_n128_ss(acc, da + 2 * q, db + 128 * q, q ? 1 : first_acc);
            wg_commit();
            g++;
            slot = slot == SM_REGION - 2 * PAGE ? 0 : slot + 2 * PAGE;
        };
        issue_out(0);
        wg_wait<1>();
        finish_attention(g - 1);
#pragma unroll 1
        for (int kb = 1; kb < 64 - PEEL; kb++) {
            issue_out(1);
            wg_wait<1>();
            release(g - 2);
            if (kb <= 8 && !(kb & 1)) {
                store_part4(pend, (kb >> 1) - 1, pk);
                if (kb == 8) mark_done(0);
            }
            if (kb >= 32 - PEEL && ((kb + PEEL) & 3) == 2 * w) {
                uint32_t u0, u1, u2, u3;
                const uint32_t a = stg + ((kb + PEEL) & 16) * 512 + ((kb + PEEL) & 12) * 128 + lane * 16;
                mbar_wait(sb + BAR_G + w * 8, 0);
                lds128(a, u0, u1, u2, u3);
                sts128(a, pack_bf16(silu_f(bf_lo(u0)), silu_f(bf_hi(u0))), pack_bf16(silu_f(bf_lo(u1)), silu_f(bf_hi(u1))),
                       pack_bf16(silu_f(bf_lo(u2)), silu_f(bf_hi(u2))), pack_bf16(silu_f(bf_lo(u3)), silu_f(bf_hi(u3))));
            }
        }
        const uint32_t goff = (out_rows(pair) * 256 + c * 128 + w * 64 + v * 16 + (lane >> 3)) * (DM * 2) +
                              out_cols(pair) * 128 + (((lane & 7) ^ (lane >> 3)) << 4);
        uint32_t xr[32], gr[32];
        {
            const uint8_t* src[2] = {ptr_off(x, goff), ptr_off(x, goff ^ 64)};
#pragma unroll
            for (int i = 0; i < 8; i++) {
                const uint4 t = ldg_hint(src[i & 1] + (i & 3) * (4 * DM * 2) + (i >> 2) * 128, POL_FIRST);
                xr[4 * i] = t.x; xr[4 * i + 1] = t.y; xr[4 * i + 2] = t.z; xr[4 * i + 3] = t.w;
            }
        }
#pragma unroll 1
        for (int i = 0; i < PEEL; i++) {
            if (i == PEEL - STAG && w == 1) bar_sync(4, 256);
            issue_out(1);
            if (i == PEEL - 1 && w == 0) bar_arrive(4, 256);
            wg_wait<1>();
        }
        asm volatile("barrier.cluster.arrive.relaxed.aligned;" ::: "memory");
#pragma unroll
        for (int i = 0; i < 8; i++) lds128(stg + (i >> 2) * 8192 + (i & 3) * 512 + lane * 16, gr[4 * i], gr[4 * i + 1], gr[4 * i + 2], gr[4 * i + 3]);
        uint8_t* dst[2] = {ptr_off(out, goff), ptr_off(out, goff ^ 64)};
        __syncwarp();
        wg_wait<0>();
        reg_fence(acc);
        PROF(14, w);
        if (w == 0) PROF_GT(14);
#pragma unroll
        for (int s = 0; s < 8; s++)
            stmatrix_x4(slab_addr(stg, lane, s), pack_bf16(acc[8 * s], acc[8 * s + 1]), pack_bf16(acc[8 * s + 2], acc[8 * s + 3]),
                        pack_bf16(acc[8 * s + 4], acc[8 * s + 5]), pack_bf16(acc[8 * s + 6], acc[8 * s + 7]));
        __syncwarp();
        uint32_t o[32];
#pragma unroll
        for (int i = 0; i < 8; i++) lds128(stg + (i >> 2) * 8192 + (i & 3) * 512 + lane * 16, o[4 * i], o[4 * i + 1], o[4 * i + 2], o[4 * i + 3]);
#pragma unroll
        for (int i = 0; i < 8; i++) {
#pragma unroll
            for (int k = 0; k < 4; k++) xr[4 * i + k] = bf2_add(xr[4 * i + k], bf2_mul(o[4 * i + k], gr[4 * i + k]));
            __stcg(reinterpret_cast<uint4*>(dst[i & 1] + (i & 3) * (4 * DM * 2) + (i >> 2) * 128), make_uint4(xr[4 * i], xr[4 * i + 1], xr[4 * i + 2], xr[4 * i + 3]));
        }
        PROF(28, w);
        return;
    }
}

__global__ void __cluster_dims__(2, 1, 1) __launch_bounds__(384, 1)
fused_kernel(const __grid_constant__ CUtensorMap m_ckv, const __grid_constant__ CUtensorMap m_wuk,
             const __grid_constant__ CUtensorMap m_wuv, const __grid_constant__ CUtensorMap m_wq,
             const __grid_constant__ CUtensorMap m_wo, const __grid_constant__ CUtensorMap m_gate,
             const __grid_constant__ CUtensorMap m_up, const __grid_constant__ CUtensorMap m_down, const Params P) {
    extern __shared__ __align__(1024) uint8_t smem[];
    const uint32_t sb = __shfl_sync(~0u, smem_u32(smem), 0);
    const int tid = threadIdx.x;
    const int cl = blockIdx.x >> 1, c = blockIdx.x & 1;
    const int pair = cl >= 64 ? cl : cl < 4 ? cl * 16 + 15 : cl < 36 ? ((cl - 4) >> 3) * 16 + ((cl - 4) & 7)
                                                                    : ((cl - 36) / 7) * 16 + 8 + (cl - 36) % 7;
    const bool starter = tid == 256 && pair < NMAIN / 2;
    const CUtensorMap* m_wu = c ? &m_wuv : &m_wuk;
    if (tid == 256) {
        mbar_init(sb + BAR_FULL, 1);
        if (starter) {
            asm volatile("fence.mbarrier_init.release.cluster;" ::: "memory");
            mbar_expect_tx(sb + BAR_FULL, 3 * PAGE);
            tma_3d(sb, m_wu, 0, 0, kv_head(pair) * 2, sb + BAR_FULL);
            tma_3d(sb + PAGE, &m_ckv, 0, kv_tokens(pair) * 256, 0, sb + BAR_FULL);
            tma_3d(sb + 2 * PAGE, &m_ckv, 0, kv_tokens(pair) * 256 + 128, 0, sb + BAR_FULL);
        }
#pragma unroll
        for (int i = 1; i < NBAR; i++) mbar_init(sb + SM_BAR + i * 8, (i >> 3) == 1 ? 16 : i >= 25 ? 8 : 1);
        asm volatile("fence.mbarrier_init.release.cluster;" ::: "memory");
    }
    if (starter) {
#pragma unroll 1
        for (int kb = 1; kb < 4; kb++) mbar_expect_tx(sb + BAR_FULL + kb * 8, 3 * PAGE);
        tma_3d(sb + 3 * PAGE, m_wu, 0, 64, kv_head(pair) * 2, sb + BAR_FULL + 8);
    }
    PROF(18, (tid >> 7) & 1);
    __syncthreads();
    cluster_sync();
    PROF(22, (tid >> 7) & 1);
    PROF(19, (tid >> 7) & 1);
    const int warp = __shfl_sync(~0u, tid >> 5, 0), lane = tid & 31;
    auto dump_prof = [&]() {
    };
    if (pair >= NMAIN / 2) {
        if (warp < 8) ffn_cta(smem, sb, blockIdx.x - NMAIN, __ldcg(&g_sync.done) / NCTA, P.w_r);
        else if (tid == 256) ffn_producer(sb, blockIdx.x - NMAIN, &m_gate, &m_up, &m_down);
        __syncwarp();
        PROF(29, tid >> 7);
        cluster_sync();
        if (tid == 0) atomicAdd(&g_sync.done, 1u);
        if (warp < 8) dump_prof();
    } else if (warp < 8) {
        asm volatile("setmaxnreg.inc.sync.aligned.u32 232;");
        consumer(sb, pair, c, P.out, (const uint8_t*)P.x);
        PROF(29, tid >> 7);
        asm volatile("barrier.cluster.wait.aligned;" ::: "memory");
        dump_prof();
    } else {
        asm volatile("setmaxnreg.dec.sync.aligned.u32 40;");
        if (starter) {
#pragma unroll 1
            for (int kb = 1; kb < 4; kb++) {
                if (kb > 1) tma_3d(sb + kb * (3 * PAGE), m_wu, 0, kb * 64, kv_head(pair) * 2, sb + BAR_FULL + kb * 8);
                tma_3d_mc(sb + kb * (3 * PAGE) + (1 + c) * PAGE, &m_ckv, 0, kv_tokens(pair) * 256 + c * 128, kb, sb + BAR_FULL + kb * 8);
            }
        }
        if (warp == 10) {
            sync_helper(sb, lane, pair, c);
        } else if (warp & 1) {
            fetch_helper((warp & 2) ? P.w_uv : P.w_uk, sb, (warp >> 1) & 1, lane, pair, c);
        } else {
            producer(P, sb, pair, c, &m_ckv, m_wu, &m_wq, &m_wo);
        }
        bar_sync(6, 128);
        if (tid == 256) atomicAdd(&g_sync.done, 1u);
        cluster_sync();
    }
}

typedef CUresult (*EncodeFn)(CUtensorMap*, CUtensorMapDataType, cuuint32_t, void*, const cuuint64_t*, const cuuint64_t*,
                             const cuuint32_t*, const cuuint32_t*, CUtensorMapInterleave, CUtensorMapSwizzle,
                             CUtensorMapL2promotion, CUtensorMapFloatOOBfill);

void make_map_w(EncodeFn fn, CUtensorMap* m, const void* ptr, int rows, int cols, int blocks, int box_rows = 32) {
    cuuint64_t dims[3] = {64, (cuuint64_t)rows, (cuuint64_t)cols / 64};
    cuuint64_t strides[2] = {(cuuint64_t)cols * 2, 128};
    cuuint32_t box[3] = {64, (cuuint32_t)box_rows, (cuuint32_t)blocks};
    cuuint32_t es[3] = {1, 1, 1};
    fn(m, CU_TENSOR_MAP_DATA_TYPE_BFLOAT16, 3, const_cast<void*>(ptr), dims, strides, box, es, CU_TENSOR_MAP_INTERLEAVE_NONE,
       CU_TENSOR_MAP_SWIZZLE_128B, CU_TENSOR_MAP_L2_PROMOTION_L2_256B, CU_TENSOR_MAP_FLOAT_OOB_FILL_NONE);
}

}

extern "C" void kernel_launch(void* const* d_in, const int* in_sizes, int n_in, void* d_out, int out_size) {
    static EncodeFn fn = nullptr;
    if (!fn) {
        void* f = nullptr;
        cudaDriverEntryPointQueryResult qr;
        cudaGetDriverEntryPoint("cuTensorMapEncodeTiled", &f, cudaEnableDefault, &qr);
        fn = (EncodeFn)f;
        cudaFuncSetAttribute(fused_kernel, cudaFuncAttributeMaxDynamicSharedMemorySize, SMEM_BYTES);
    }
    CUtensorMap m_ckv, m_wuk, m_wuv, m_wq, m_wo, m_gate, m_up, m_down;
    make_map_w(fn, &m_gate, d_in[8], DM, FF, FS / 64, 16);
    make_map_w(fn, &m_up, d_in[9], DM, FF, FS / 64, 16);
    make_map_w(fn, &m_down, d_in[10], FF, DM, DM / 64, 16);
    make_map_w(fn, &m_ckv, d_in[1], SEQ, DC, 1, 128);
    make_map_w(fn, &m_wq, d_in[2], DM, NH * 128, 1, 64);
    make_map_w(fn, &m_wuk, d_in[3], DC, NH * 128, 2, 64);
    make_map_w(fn, &m_wuv, d_in[4], DC, NH * 128, 2, 64);
    make_map_w(fn, &m_wo, d_in[5], NH * 128, DM, 1, 64);
    Params P;
    P.x = (const __nv_bfloat16*)d_in[0];
    P.w_r = (const __nv_bfloat16*)d_in[7];
    P.c_kv = (const uint8_t*)d_in[1];
    P.w_uk = (const uint8_t*)d_in[3];
    P.w_uv = (const uint8_t*)d_in[4];
    P.out = (uint8_t*)d_out;
    fused_kernel<<<NCTA, 384, SMEM_BYTES>>>(m_ckv, m_wuk, m_wuv, m_wq, m_wo, m_gate, m_up, m_down, P);
}
```

```cpp
#include <cuda_runtime.h>
#include <cuda_bf16.h>
#include <cuda.h>
#include <stdint.h>
#include <type_traits>

namespace {

constexpr int SEQ = 2048, DM = 1024, NH = 32, DC = 512, FF = 3584;
constexpr int PAGE = 16384;
constexpr int NRING = 12;
constexpr int NCTA = 132, NMAIN = 128;
constexpr uint32_t SM_REGION = NRING * PAGE;
constexpr uint32_t SM_BAR = (NRING + 2) * PAGE;
constexpr uint32_t BAR_FULL = SM_BAR, BAR_EMPTY = SM_BAR + 64;
constexpr uint32_t BAR_DEP = SM_BAR + 128;
constexpr uint32_t BAR_G = SM_BAR + 184;
constexpr uint32_t BAR_DONE = SM_BAR + 200;
constexpr uint32_t BAR_EMPTYL = SM_BAR + 216;
constexpr int NBAR = 35;
constexpr uint32_t SM_PROF = SM_BAR + 320;
constexpr int SMEM_BYTES = SM_PROF + 512;
constexpr uint32_t SPIN_LIMIT = 1u << 16;
constexpr uint32_t POLL_MASK = 7;
constexpr int EARLY = 2;
constexpr int WN = 5;
constexpr int PEEL = 5, STAG = 3;

struct SyncBlock {
    unsigned done;       unsigned pad0[31];
    unsigned ln;         unsigned pad1[31];
    unsigned router;     unsigned pad4[31];
    unsigned ffn_ticket; unsigned pad2[31];
    unsigned ffn_done;   unsigned pad3[31];
    unsigned kv[NH * 8];
    unsigned kvfree[16 * 8];
    unsigned ctx[32 * NH];
};

__device__ __align__(1024) uint8_t g_xn[8 * 16 * 4 * 8192];
__device__ __align__(4096) uint8_t g_kv[16 * 16 * 65536];
__device__ __align__(4096) uint8_t g_ctx[16 * 64 * 16384];
__device__ __align__(16) uint4 g_routed[2 * 128];
__device__ int g_sel[2];
__device__ __align__(16) float g_r[SEQ];
__device__ __align__(16) float g_ypart[4 * 2 * DM];
__device__ SyncBlock g_sync;

__device__ __forceinline__ uint32_t smem_u32(const void* p) { return (uint32_t)__cvta_generic_to_shared(p); }

__device__ __forceinline__ void mbar_init(uint32_t bar, uint32_t count) {
    asm volatile("mbarrier.init.shared::cta.b64 [%0], %1;" ::"r"(bar), "r"(count) : "memory");
}
#define MBAR_WAIT_ASM(HINT, LIMIT)                                                                  \
    asm volatile("{\n.reg .pred p;\n.reg .u32 n;\nmov.u32 n, 0;\n"                                  \
                 "WAIT_LOOP:\n"                                                                     \
                 "mbarrier.try_wait.parity.shared::cta.b64 p, [%0], %1" HINT ";\n"                  \
                 "@p bra WAIT_DONE;\n"                                                              \
                 "add.u32 n, n, 1;\n"                                                               \
                 "setp.lt.u32 p, n, " LIMIT ";\n"                                                   \
                 "@p bra WAIT_LOOP;\n"                                                              \
                 "WAIT_DONE:\n}\n" ::"r"(bar), "r"(parity) : "memory")
__device__ __forceinline__ void mbar_wait(uint32_t bar, uint32_t parity) { MBAR_WAIT_ASM("", "131072"); }
__device__ __forceinline__ void mbar_sleep(uint32_t bar, uint32_t parity) { MBAR_WAIT_ASM(", 2000", "8192"); }
__device__ __forceinline__ bool mbar_try(uint32_t bar, uint32_t parity) {
    uint32_t ok;
    asm volatile("{\n.reg .pred p;\nmbarrier.try_wait.parity.shared::cta.b64 p, [%1], %2;\nselp.u32 %0, 1, 0, p;\n}\n"
                 : "=r"(ok) : "r"(bar), "r"(parity) : "memory");
    return ok;
}
__device__ __forceinline__ bool mbar_test(uint32_t bar, uint32_t parity) {
    uint32_t ok;
    asm volatile("{\n.reg .pred p;\nmbarrier.test_wait.parity.shared::cta.b64 p, [%1], %2;\nselp.u32 %0, 1, 0, p;\n}\n"
                 : "=r"(ok) : "r"(bar), "r"(parity) : "memory");
    return ok;
}
__device__ __forceinline__ bool elect_one() {
    uint32_t ok;
    asm volatile("{\n.reg .pred p;\nelect.sync _|p, 0xffffffff;\nselp.u32 %0, 1, 0, p;\n}\n" : "=r"(ok));
    return ok;
}
__device__ __forceinline__ void mbar_arrive(uint32_t bar) {
    asm volatile("mbarrier.arrive.shared::cta.b64 _, [%0];" ::"r"(bar) : "memory");
}
__device__ __forceinline__ void mbar_expect_tx(uint32_t bar, uint32_t bytes) {
    asm volatile("mbarrier.arrive.expect_tx.shared::cta.b64 _, [%0], %1;" ::"r"(bar), "r"(bytes) : "memory");
}
__device__ __forceinline__ void mbar_arrive_cluster(uint32_t cluster_addr) {
    asm volatile("mbarrier.arrive.shared::cluster.b64 _, [%0];" ::"r"(cluster_addr) : "memory");
}
__device__ __forceinline__ uint32_t mapa(uint32_t addr, uint32_t rank) {
    uint32_t r;
    asm("mapa.shared::cluster.u32 %0, %1, %2;" : "=r"(r) : "r"(addr), "r"(rank));
    return r;
}
__device__ __forceinline__ void tma_3d(uint32_t dst, const CUtensorMap* m, int c0, int c1, int c2, uint32_t bar) {
    asm volatile("cp.async.bulk.tensor.3d.shared::cluster.global.mbarrier::complete_tx::bytes [%0], [%1, {%3, %4, %5}], [%2];"
                 ::"r"(dst), "l"(m), "r"(bar), "r"(c0), "r"(c1), "r"(c2) : "memory");
}
__device__ __forceinline__ void tma_3d_hint(uint32_t dst, const CUtensorMap* m, int c0, int c1, int c2, uint32_t bar, uint64_t pol) {
    asm volatile("cp.async.bulk.tensor.3d.shared::cluster.global.mbarrier::complete_tx::bytes.L2::cache_hint [%0], [%1, {%3, %4, %5}], [%2], %6;"
                 ::"r"(dst), "l"(m), "r"(bar), "r"(c0), "r"(c1), "r"(c2), "l"(pol) : "memory");
}
__device__ __forceinline__ void tma_3d_mc(uint32_t dst, const CUtensorMap* m, int c0, int c1, int c2, uint32_t bar) {
    asm volatile("cp.async.bulk.tensor.3d.shared::cluster.global.mbarrier::complete_tx::bytes.multicast::cluster [%0], [%1, {%3, %4, %5}], [%2], %6;"
                 ::"r"(dst), "l"(m), "r"(bar), "r"(c0), "r"(c1), "r"(c2), "h"((uint16_t)3) : "memory");
}
__device__ __forceinline__ void bulk_load(uint32_t dst, const void* src, uint32_t bytes, uint32_t bar) {
    asm volatile("cp.async.bulk.shared::cluster.global.mbarrier::complete_tx::bytes [%0], [%1], %2, [%3];"
                 ::"r"(dst), "l"(src), "r"(bytes), "r"(bar) : "memory");
}
__device__ __forceinline__ void cp_async16(uint32_t dst, const void* src) {
    asm volatile("cp.async.cg.shared.global [%0], [%1], 16;" ::"r"(dst), "l"(src) : "memory");
}
__device__ __forceinline__ void bulk_load_mc(uint32_t dst, const void* src, uint32_t bytes, uint32_t bar) {
    asm volatile("cp.async.bulk.shared::cluster.global.mbarrier::complete_tx::bytes.multicast::cluster [%0], [%1], %2, [%3], %4;"
                 ::"r"(dst), "l"(src), "r"(bytes), "r"(bar), "h"((uint16_t)3) : "memory");
}
__device__ __forceinline__ void fence_async_smem() { asm volatile("fence.proxy.async.shared::cta;" ::: "memory"); }
__device__ __forceinline__ void prefetch_map(const CUtensorMap* m) {
    asm volatile("prefetch.tensormap [%0];" ::"l"(m) : "memory");
}
__device__ __forceinline__ void red_release(unsigned* p) {
    asm volatile("red.release.gpu.global.add.u32 [%0], 1;" ::"l"(p) : "memory");
}
__device__ __forceinline__ unsigned ld_relaxed(const unsigned* p) {
    unsigned v;
    asm volatile("ld.relaxed.gpu.global.u32 %0, [%1];" : "=r"(v) : "l"(p) : "memory");
    return v;
}
__device__ __forceinline__ void wait_counter(const unsigned* p, unsigned target) {
    for (uint32_t n = 0; (int)(ld_relaxed(p) - target) < 0 && n < SPIN_LIMIT; n++) __nanosleep(100);
    asm volatile("fence.acquire.gpu;" ::: "memory");
    asm volatile("fence.proxy.async.global;" ::: "memory");
}
__device__ __forceinline__ void bar_sync(int id, int n) { asm volatile("bar.sync %0, %1;" ::"r"(id), "r"(n) : "memory"); }
__device__ __forceinline__ void bar_arrive(int id, int n) { asm volatile("bar.arrive %0, %1;" ::"r"(id), "r"(n) : "memory"); }
__device__ __forceinline__ void cluster_sync() {
    asm volatile("barrier.cluster.arrive.relaxed.aligned;\nbarrier.cluster.wait.aligned;" ::: "memory");
}
__device__ __forceinline__ void wg_fence() { asm volatile("wgmma.fence.sync.aligned;" ::: "memory"); }
__device__ __forceinline__ void wg_commit() { asm volatile("wgmma.commit_group.sync.aligned;" ::: "memory"); }
template <int N> __device__ __forceinline__ void wg_wait() { asm volatile("wgmma.wait_group.sync.aligned %0;" ::"n"(N) : "memory"); }
template <int N> __device__ __forceinline__ void reg_fence(float (&a)[N]) {
#pragma unroll
    for (int i = 0; i < N; i++) asm volatile("" : "+f"(a[i])::"memory");
}
template <int N> __device__ __forceinline__ void reg_fence(uint32_t (&a)[N]) {
#pragma unroll
    for (int i = 0; i < N; i++) asm volatile("" : "+r"(a[i])::"memory");
}
__device__ __forceinline__ uint32_t pack_bf16(float lo, float hi) {
    uint32_t r;
    asm("cvt.rn.bf16x2.f32 %0, %1, %2;" : "=r"(r) : "f"(hi), "f"(lo));
    return r;
}
__device__ __forceinline__ float bf_lo(uint32_t v) { return __uint_as_float(v << 16); }
__device__ __forceinline__ float bf_hi(uint32_t v) { return __uint_as_float(v & 0xffff0000u); }
__device__ __forceinline__ float bf_round(float v) { return __bfloat162float(__float2bfloat16_rn(v)); }
__device__ __forceinline__ float ex2(float v) {
    float r;
    asm("ex2.approx.ftz.f32 %0, %1;" : "=f"(r) : "f"(v));
    return r;
}
__device__ __forceinline__ float sqrt_approx(float v) {
    float r;
    asm("sqrt.approx.ftz.f32 %0, %1;" : "=f"(r) : "f"(v));
    return r;
}
__device__ __forceinline__ float rcp_approx(float v) {
    float r;
    asm("rcp.approx.ftz.f32 %0, %1;" : "=f"(r) : "f"(v));
    return r;
}
__device__ __forceinline__ float silu_f(float v) { return v * rcp_approx(1.0f + ex2(v * -1.4426950408889634f)); }
__device__ __forceinline__ void stmatrix_x4(uint32_t addr, uint32_t r0, uint32_t r1, uint32_t r2, uint32_t r3) {
    asm volatile("stmatrix.sync.aligned.m8n8.x4.shared.b16 [%0], {%1, %2, %3, %4};"
                 ::"r"(addr), "r"(r0), "r"(r1), "r"(r2), "r"(r3) : "memory");
}
__device__ __forceinline__ void sts128(uint32_t addr, uint32_t r0, uint32_t r1, uint32_t r2, uint32_t r3) {
    asm volatile("st.shared.v4.b32 [%0], {%1, %2, %3, %4};" ::"r"(addr), "r"(r0), "r"(r1), "r"(r2), "r"(r3) : "memory");
}
__device__ __forceinline__ void lds128(uint32_t addr, uint32_t& r0, uint32_t& r1, uint32_t& r2, uint32_t& r3) {
    asm volatile("ld.shared.v4.b32 {%0, %1, %2, %3}, [%4];" : "=r"(r0), "=r"(r1), "=r"(r2), "=r"(r3) : "r"(addr) : "memory");
}
__device__ __forceinline__ uint32_t bf2_mul(uint32_t a, uint32_t b) {
    uint32_t r;
    asm("mul.rn.bf16x2 %0, %1, %2;" : "=r"(r) : "r"(a), "r"(b));
    return r;
}
__device__ __forceinline__ uint32_t bf2_add(uint32_t a, uint32_t b) {
    uint32_t r;
    asm("add.rn.bf16x2 %0, %1, %2;" : "=r"(r) : "r"(a), "r"(b));
    return r;
}
constexpr uint64_t POL_FIRST = 0x12F0000000000000ull, POL_NORMAL = 0x16F0000000000000ull;
__device__ __forceinline__ uint4 ldg_hint(const void* p, uint64_t pol) {
    uint4 v;
    asm volatile("ld.global.cg.L2::cache_hint.v4.u32 {%0, %1, %2, %3}, [%4], %5;" : "=r"(v.x), "=r"(v.y), "=r"(v.z), "=r"(v.w) : "l"(p), "l"(pol));
    return v;
}
__device__ __forceinline__ void stg_hint(void* p, uint32_t r0, uint32_t r1, uint32_t r2, uint32_t r3, uint64_t pol) {
    asm volatile("st.global.cg.L2::cache_hint.v4.u32 [%0], {%1, %2, %3, %4}, %5;" ::"l"(p), "r"(r0), "r"(r1), "r"(r2), "r"(r3), "l"(pol) : "memory");
}

__device__ __forceinline__ uint64_t make_desc(uint32_t addr, uint32_t lbo_bytes) {
    return (uint64_t)((addr & 0x3FFFF) >> 4) | ((uint64_t)(lbo_bytes >> 4) << 16) | ((uint64_t)(1024 >> 4) << 32) | (1ull << 62);
}

__device__ __forceinline__ void wgmma_n256_ss(float (&d)[128], uint64_t da, uint64_t db, int acc) {
    asm volatile(
        "{\n.reg .pred p;\nsetp.ne.b32 p, %130, 0;\n"
        "wgmma.mma_async.sync.aligned.m64n256k16.f32.bf16.bf16 {"
        "%0, %1, %2, %3, %4, %5, %6, %7, %8, %9, %10, %11, %12, %13, %14, %15, "
        "%16, %17, %18, %19, %20, %21, %22, %23, %24, %25, %26, %27, %28, %29, %30, %31, "
        "%32, %33, %34, %35, %36, %37, %38, %39, %40, %41, %42, %43, %44, %45, %46, %47, "
        "%48, %49, %50, %51, %52, %53, %54, %55, %56, %57, %58, %59, %60, %61, %62, %63, "
        "%64, %65, %66, %67, %68, %69, %70, %71, %72, %73, %74, %75, %76, %77, %78, %79, "
        "%80, %81, %82, %83, %84, %85, %86, %87, %88, %89, %90, %91, %92, %93, %94, %95, "
        "%96, %97, %98, %99, %100, %101, %102, %103, %104, %105, %106, %107, %108, %109, %110, %111, "
        "%112, %113, %114, %115, %116, %117, %118, %119, %120, %121, %122, %123, %124, %125, %126, %127"
        "}, %128, %129, p, 1, 1, 1, 0;\n}\n"
        :
        "+f"(d[0]), "+f"(d[1]), "+f"(d[2]), "+f"(d[3]), "+f"(d[4]), "+f"(d[5]), "+f"(d[6]), "+f"(d[7]),
        "+f"(d[8]), "+f"(d[9]), "+f"(d[10]), "+f"(d[11]), "+f"(d[12]), "+f"(d[13]), "+f"(d[14]), "+f"(d[15]),
        "+f"(d[16]), "+f"(d[17]), "+f"(d[18]), "+f"(d[19]), "+f"(d[20]), "+f"(d[21]), "+f"(d[22]), "+f"(d[23]),
        "+f"(d[24]), "+f"(d[25]), "+f"(d[26]), "+f"(d[27]), "+f"(d[28]), "+f"(d[29]), "+f"(d[30]), "+f"(d[31]),
        "+f"(d[32]), "+f"(d[33]), "+f"(d[34]), "+f"(d[35]), "+f"(d[36]), "+f"(d[37]), "+f"(d[38]), "+f"(d[39]),
        "+f"(d[40]), "+f"(d[41]), "+f"(d[42]), "+f"(d[43]), "+f"(d[44]), "+f"(d[45]), "+f"(d[46]), "+f"(d[47]),
        "+f"(d[48]), "+f"(d[49]), "+f"(d[50]), "+f"(d[51]), "+f"(d[52]), "+f"(d[53]), "+f"(d[54]), "+f"(d[55]),
        "+f"(d[56]), "+f"(d[57]), "+f"(d[58]), "+f"(d[59]), "+f"(d[60]), "+f"(d[61]), "+f"(d[62]), "+f"(d[63]),
        "+f"(d[64]), "+f"(d[65]), "+f"(d[66]), "+f"(d[67]), "+f"(d[68]), "+f"(d[69]), "+f"(d[70]), "+f"(d[71]),
        "+f"(d[72]), "+f"(d[73]), "+f"(d[74]), "+f"(d[75]), "+f"(d[76]), "+f"(d[77]), "+f"(d[78]), "+f"(d[79]),
        "+f"(d[80]), "+f"(d[81]), "+f"(d[82]), "+f"(d[83]), "+f"(d[84]), "+f"(d[85]), "+f"(d[86]), "+f"(d[87]),
        "+f"(d[88]), "+f"(d[89]), "+f"(d[90]), "+f"(d[91]), "+f"(d[92]), "+f"(d[93]), "+f"(d[94]), "+f"(d[95]),
        "+f"(d[96]), "+f"(d[97]), "+f"(d[98]), "+f"(d[99]), "+f"(d[100]), "+f"(d[101]), "+f"(d[102]), "+f"(d[103]),
        "+f"(d[104]), "+f"(d[105]), "+f"(d[106]), "+f"(d[107]), "+f"(d[108]), "+f"(d[109]), "+f"(d[110]), "+f"(d[111]),
        "+f"(d[112]), "+f"(d[113]), "+f"(d[114]), "+f"(d[115]), "+f"(d[116]), "+f"(d[117]), "+f"(d[118]), "+f"(d[119]),
        "+f"(d[120]), "+f"(d[121]), "+f"(d[122]), "+f"(d[123]), "+f"(d[124]), "+f"(d[125]), "+f"(d[126]), "+f"(d[127])
        : "l"(da), "l"(db), "r"(acc));
}

__device__ __forceinline__ void wgmma_n64_rs_tb(float* d, uint32_t a0, uint32_t a1, uint32_t a2, uint32_t a3, uint32_t db, int acc) {
    asm volatile(
        "{\n.reg .pred p;\n.reg .b64 db;\nsetp.ne.b32 p, %37, 0;\nmov.b64 db, {%36, 0x40000040};\n"
        "wgmma.mma_async.sync.aligned.m64n64k16.f32.bf16.bf16 {"
        "%0, %1, %2, %3, %4, %5, %6, %7, %8, %9, %10, %11, %12, %13, %14, %15, "
        "%16, %17, %18, %19, %20, %21, %22, %23, %24, %25, %26, %27, %28, %29, %30, %31"
        "}, {%32, %33, %34, %35}, db, p, 1, 1, 1;\n}\n"
        :
        "+f"(d[0]), "+f"(d[1]), "+f"(d[2]), "+f"(d[3]), "+f"(d[4]), "+f"(d[5]), "+f"(d[6]), "+f"(d[7]),
        "+f"(d[8]), "+f"(d[9]), "+f"(d[10]), "+f"(d[11]), "+f"(d[12]), "+f"(d[13]), "+f"(d[14]), "+f"(d[15]),
        "+f"(d[16]), "+f"(d[17]), "+f"(d[18]), "+f"(d[19]), "+f"(d[20]), "+f"(d[21]), "+f"(d[22]), "+f"(d[23]),
        "+f"(d[24]), "+f"(d[25]), "+f"(d[26]), "+f"(d[27]), "+f"(d[28]), "+f"(d[29]), "+f"(d[30]), "+f"(d[31])
        : "r"(a0), "r"(a1), "r"(a2), "r"(a3), "r"(db), "r"(acc));
}

template <int TB>
__device__ __forceinline__ void wgmma_n128_rs(float (&d)[64], uint32_t a0, uint32_t a1, uint32_t a2, uint32_t a3, uint32_t db, int acc) {
    asm volatile(
        "{\n.reg .pred p;\n.reg .b64 db;\nsetp.ne.b32 p, %69, 0;\nmov.b64 db, {%68, 0x40000040};\n"
        "wgmma.mma_async.sync.aligned.m64n128k16.f32.bf16.bf16 {"
        "%0, %1, %2, %3, %4, %5, %6, %7, %8, %9, %10, %11, %12, %13, %14, %15, "
        "%16, %17, %18, %19, %20, %21, %22, %23, %24, %25, %26, %27, %28, %29, %30, %31, "
        "%32, %33, %34, %35, %36, %37, %38, %39, %40, %41, %42, %43, %44, %45, %46, %47, "
        "%48, %49, %50, %51, %52, %53, %54, %55, %56, %57, %58, %59, %60, %61, %62, %63"
        "}, {%64, %65, %66, %67}, db, p, 1, 1, %70;\n}\n"
        :
        "+f"(d[0]), "+f"(d[1]), "+f"(d[2]), "+f"(d[3]), "+f"(d[4]), "+f"(d[5]), "+f"(d[6]), "+f"(d[7]),
        "+f"(d[8]), "+f"(d[9]), "+f"(d[10]), "+f"(d[11]), "+f"(d[12]), "+f"(d[13]), "+f"(d[14]), "+f"(d[15]),
        "+f"(d[16]), "+f"(d[17]), "+f"(d[18]), "+f"(d[19]), "+f"(d[20]), "+f"(d[21]), "+f"(d[22]), "+f"(d[23]),
        "+f"(d[24]), "+f"(d[25]), "+f"(d[26]), "+f"(d[27]), "+f"(d[28]), "+f"(d[29]), "+f"(d[30]), "+f"(d[31]),
        "+f"(d[32]), "+f"(d[33]), "+f"(d[34]), "+f"(d[35]), "+f"(d[36]), "+f"(d[37]), "+f"(d[38]), "+f"(d[39]),
        "+f"(d[40]), "+f"(d[41]), "+f"(d[42]), "+f"(d[43]), "+f"(d[44]), "+f"(d[45]), "+f"(d[46]), "+f"(d[47]),
        "+f"(d[48]), "+f"(d[49]), "+f"(d[50]), "+f"(d[51]), "+f"(d[52]), "+f"(d[53]), "+f"(d[54]), "+f"(d[55]),
        "+f"(d[56]), "+f"(d[57]), "+f"(d[58]), "+f"(d[59]), "+f"(d[60]), "+f"(d[61]), "+f"(d[62]), "+f"(d[63])
        : "r"(a0), "r"(a1), "r"(a2), "r"(a3), "r"(db), "r"(acc), "n"(TB));
}

__device__ __forceinline__ void wgmma_n128_ss(float* d, uint64_t da, uint64_t db, int acc) {
    asm volatile(
        "{\n.reg .pred p;\nsetp.ne.b32 p, %66, 0;\n"
        "wgmma.mma_async.sync.aligned.m64n128k16.f32.bf16.bf16 {"
        "%0, %1, %2, %3, %4, %5, %6, %7, %8, %9, %10, %11, %12, %13, %14, %15, "
        "%16, %17, %18, %19, %20, %21, %22, %23, %24, %25, %26, %27, %28, %29, %30, %31, "
        "%32, %33, %34, %35, %36, %37, %38, %39, %40, %41, %42, %43, %44, %45, %46, %47, "
        "%48, %49, %50, %51, %52, %53, %54, %55, %56, %57, %58, %59, %60, %61, %62, %63"
        "}, %64, %65, p, 1, 1, 0, 1;\n}\n"
        :
        "+f"(d[0]), "+f"(d[1]), "+f"(d[2]), "+f"(d[3]), "+f"(d[4]), "+f"(d[5]), "+f"(d[6]), "+f"(d[7]),
        "+f"(d[8]), "+f"(d[9]), "+f"(d[10]), "+f"(d[11]), "+f"(d[12]), "+f"(d[13]), "+f"(d[14]), "+f"(d[15]),
        "+f"(d[16]), "+f"(d[17]), "+f"(d[18]), "+f"(d[19]), "+f"(d[20]), "+f"(d[21]), "+f"(d[22]), "+f"(d[23]),
        "+f"(d[24]), "+f"(d[25]), "+f"(d[26]), "+f"(d[27]), "+f"(d[28]), "+f"(d[29]), "+f"(d[30]), "+f"(d[31]),
        "+f"(d[32]), "+f"(d[33]), "+f"(d[34]), "+f"(d[35]), "+f"(d[36]), "+f"(d[37]), "+f"(d[38]), "+f"(d[39]),
        "+f"(d[40]), "+f"(d[41]), "+f"(d[42]), "+f"(d[43]), "+f"(d[44]), "+f"(d[45]), "+f"(d[46]), "+f"(d[47]),
        "+f"(d[48]), "+f"(d[49]), "+f"(d[50]), "+f"(d[51]), "+f"(d[52]), "+f"(d[53]), "+f"(d[54]), "+f"(d[55]),
        "+f"(d[56]), "+f"(d[57]), "+f"(d[58]), "+f"(d[59]), "+f"(d[60]), "+f"(d[61]), "+f"(d[62]), "+f"(d[63])
        : "l"(da), "l"(db), "r"(acc));
}

__device__ __forceinline__ void wgmma_n8_ta(float* d, uint64_t da, uint64_t db) {
    asm volatile("wgmma.mma_async.sync.aligned.m64n8k16.f32.bf16.bf16 {%0, %1, %2, %3}, %4, %5, 1, 1, 1, 1, 0;\n"
                 : "+f"(d[0]), "+f"(d[1]), "+f"(d[2]), "+f"(d[3]) : "l"(da), "l"(db));
}

#define PROF(slot, role)
#undef PROF_GT
#define PROF_GT(slot)

struct Params {
    const __nv_bfloat16* x;
    const __nv_bfloat16* w_r;
    const uint8_t *c_kv, *w_uk, *w_uv;
    uint8_t* out;
};
__device__ __forceinline__ void lsu_prefetch(const void* p) { asm volatile("prefetch.global.L2 [%0];" ::"l"(p) : "memory"); }

template <typename T>
__device__ __forceinline__ T* ptr_off(T* base, uint32_t off) {
    uint32_t lo, hi;
    asm("mov.b64 {%0, %1}, %2;" : "=r"(lo), "=r"(hi) : "l"(base));
    asm("add.cc.u32 %0, %0, %2;\naddc.u32 %1, %1, 0;" : "+r"(lo), "+r"(hi) : "r"(off));
    T* r;
    asm("mov.b64 %0, {%1, %2};" : "=l"(r) : "r"(lo), "r"(hi));
    return r;
}
__device__ __forceinline__ int kv_head(int pair) { return pair & 7; }
__device__ __forceinline__ int kv_tokens(int pair) { return ((pair >> 3) & 1) * 4 + (pair >> 4); }
__device__ __forceinline__ int out_rows(int pair) { return pair & 7; }
__device__ __forceinline__ int out_cols(int pair) { return (pair >> 4) * 4 + ((pair >> 3) & 1) * 2; }
__device__ __forceinline__ int attn_rowblock(int pair, int seg) {
    int j = pair & 3, hl = pair >> 2;
    return (((hl & 1) | (j == 0)) ^ seg) ? j : 7 - j;
}
__device__ __forceinline__ int outproj_head(int i, int ib) {
    if (i < 16) return i;
    return 16 + 2 * (i & 7) + ((ib < 4) ^ ((i >> 3) & 1));
}

__device__ __forceinline__ void pin_value(uint32_t& v) { asm volatile("" : "+r"(v)); }
__device__ __forceinline__ void pin_value(int& v) { asm volatile("" : "+r"(v)); }
__device__ __forceinline__ void pin_value(const uint8_t*& v) { asm volatile("" : "+l"(v)); }

__device__ __forceinline__ void producer(const Params& P, uint32_t sb, int pair, int c,
                                         const CUtensorMap* m_ckv, const CUtensorMap* m_wu,
                                         const CUtensorMap* m_wq, const CUtensorMap* m_wo) {
    const int hl = pair >> 2;
    const int ibA = attn_rowblock(pair, 0), nA = 2 * ibA + 2;
    const int ib = out_rows(pair), mi = 2 * ib + c, nb = out_cols(pair);
    const bool leader = elect_one();
    uint32_t g = 4, tail = 0;
    if (leader) prefetch_map(m_wq);
    auto wait_released = [&](uint32_t need) {
#pragma unroll 1
        for (; tail <= need; tail++) mbar_wait(sb + BAR_EMPTY + (tail & 7) * 8, (tail >> 3) & 1);
    };
    auto wait_released_here = [&](uint32_t need) {
#pragma unroll 1
        for (; tail < need; tail++) mbar_wait(sb + BAR_EMPTY + (tail & 7) * 8, (tail >> 3) & 1);
        if (tail == need) mbar_wait(sb + BAR_EMPTYL + (need & 7) * 8, (need >> 3) & 1);
    };
    auto wait_released_peer = [&](uint32_t need) {
        if (tail == need) {
            uint32_t eb = sb + BAR_EMPTY + (need & 7) * 8, ep = (need >> 3) & 1;
            tail++;
            mbar_wait(eb, ep);
        }
    };
    auto full_bar = [&]() { return sb + BAR_FULL + (g & 7) * 8; };
    auto pin = [](auto&... v) { (pin_value(v), ...); };
#pragma unroll 1
    for (int rnd = 0; rnd < 2; rnd++) {
#pragma unroll 1
        for (int i = rnd ? 0 : 4; i < 16; i++) {
            int kb = i & 7, h2 = (kv_head(pair) + (i & 8) + rnd * 16) * 2, krow = kb * 64;
            uint32_t pg = sb + (i & 3) * (3 * PAGE), pb = pg + (1 + c) * PAGE, bar = full_bar();
            pin(kb, h2, krow, pg, pb, bar);
            const uint32_t need = g - 4 - (i < 2);
            wait_released_here(need);
            if (leader) {
                mbar_expect_tx(bar, 3 * PAGE);
                tma_3d(pg, m_wu, 0, krow, h2, bar);
            }
            wait_released_peer(need);
            if (leader) {
                tma_3d_mc(pb, m_ckv, 0, kv_tokens(pair) * 256 + c * 128, kb, bar);
                if (rnd == 1 && i == 3) asm volatile("red.relaxed.gpu.global.add.u32 [%0], 1;" ::"l"(ptr_off(g_sync.kvfree, hl * 32)) : "memory");
            }
            g++;
        }
        mbar_sleep(sb + BAR_DEP, 0);
        const uint8_t* xa = ptr_off(g_xn, ibA * (16 * 32768) + c * PAGE);
        const uint8_t* xb = ptr_off(g_xn, (7 - ibA) * (16 * 32768) + (1 - c) * PAGE);
#pragma unroll 1
        for (int kb = 0; kb < DM / 64; kb++) {
            uint32_t pg = sb + (kb & 3) * (3 * PAGE), pw = pg + 2 * PAGE + c * 8192, bar = full_bar(), p2 = pg + PAGE;
            int krow = kb * 64;
            pin(pg, pw, p2, bar, krow);
            wait_released_here(g - 4);
            if (leader) {
                mbar_expect_tx(bar, 3 * PAGE);
                bulk_load(pg, xa, PAGE, bar);
            }
            wait_released_peer(g - 4);
            if (leader) {
                tma_3d_mc(pw, m_wq, 0, krow, (rnd * 16 + hl) * 2 + c, bar);
                bulk_load(p2, xb, PAGE, bar);
            }
            g++;
            xa += 32768;
            xb += 32768;
        }
        mbar_sleep(sb + BAR_DEP + 8 + rnd * 16, 0);
        if (rnd == 1 && leader) prefetch_map(m_wo);
        uint32_t pg = sb + c * PAGE;
#pragma unroll 1
        for (int j = 0; j < 36; j++) {
            const bool isk = j == 0 || ((j & 1) && j != 35);
            const int t = isk ? (j + 1) >> 1 : (j - 1) >> 1;
            const uint8_t* src = ptr_off(g_kv, (hl * 16 + (t >= nA ? t - nA : t)) * 65536 + (isk ? 0 : 32768) + c * PAGE);
            uint32_t bar = full_bar(), need = g - 6 + (j < 2) + (j < 5);
            pin(src, bar, need);
            wait_released(need);
            if (leader) {
                mbar_expect_tx(bar, 2 * PAGE);
                bulk_load_mc(pg, src, PAGE, bar);
            }
            g++;
            if (rnd == 0 && j >= 22 && j < 34) {
                const int cta = pair * 2 + c, i = j - 22;
                const uint32_t l = (threadIdx.x & 31) * 128;
                if (i < 8) lsu_prefetch(ptr_off(i & 1 ? P.w_uv : P.w_uk, cta * 32768 + (i >> 1) * 8192 + 4096 + l));
                else lsu_prefetch(ptr_off(P.c_kv, cta * 16384 + (i - 8) * 4096 + l));
            }
            pg = pg >= sb + SM_REGION - 2 * PAGE ? pg - (SM_REGION - 2 * PAGE) : pg + 2 * PAGE;
        }
    }
    uint32_t pg = sb;
#pragma unroll 1
    for (int i = 0; i < 64; i++) {
        if ((i & 15) == 0 && i != 16) mbar_sleep(sb + BAR_DEP + 32 + (i >> 1) - (i ? 8 : 0), 0);
        const int kb = outproj_head(i >> 1, ib) * 2 + (i & 1);
        const uint8_t* src = ptr_off(g_ctx, (mi * 64 + kb) * PAGE);
        uint32_t bar = full_bar(), pw = pg + PAGE + c * 8192;
        int krow = kb * 64;
        pin(src, bar, pw, krow);
        wait_released_here(g - 6);
        if (leader) {
            mbar_expect_tx(bar, 2 * PAGE);
            bulk_load(pg, src, PAGE, bar);
        }
        wait_released_peer(g - 6);
        if (leader) tma_3d_mc(pw, m_wo, 0, krow, nb + c, bar);
        g++;
        pg = pg == sb + SM_REGION - 2 * PAGE ? sb : pg + 2 * PAGE;
    }
}

__device__ __forceinline__ uint32_t xn_block(int row64, int kb) {
    return (((row64 >> 2) * 16 + kb) * 4 + ((row64 & 1) * 2 + (((row64 >> 1) & 1) ^ 1))) * 8192;
}
__device__ __forceinline__ uint32_t image_offset(int row, int ch) {
    return xn_block(row >> 6, ch >> 3) + (row & 63) * 128 + (((ch & 7) ^ (row & 7)) << 4);
}
__device__ __forceinline__ uint32_t bf2_sub(uint32_t a, uint32_t b) {
    uint32_t r;
    asm("sub.rn.bf16x2 %0, %1, %2;" : "=r"(r) : "r"(a), "r"(b));
    return r;
}
__device__ __forceinline__ uint32_t bf2_fma(uint32_t a, uint32_t b, uint32_t c) {
    uint32_t r;
    asm("fma.rn.bf16x2 %0, %1, %2, %3;" : "=r"(r) : "r"(a), "r"(b), "r"(c));
    return r;
}
template <int N0, int N>
__device__ __forceinline__ void ln_sums(const uint32_t (&u)[N], float& sum, float& sq) {
    float s0 = 0.f, s1 = 0.f, q0 = 0.f, q1 = 0.f;
#pragma unroll
    for (int k = N0; k < N0 + 16; k++) {
        const float a = bf_lo(u[k]), b = bf_hi(u[k]);
        s0 += a; s1 += b;
        q0 = fmaf(a, a, q0); q1 = fmaf(b, b, q1);
    }
    sum = s0 + s1;
    sq = q0 + q1;
}
__device__ __forceinline__ void ln_finish(float sum, float sq, uint32_t& mean2, uint32_t& rhi2, uint32_t& rlo2) {
    const float ms = sum * (1.0f / DM);
    const float var = fmaxf(fmaf(-ms, ms, sq * (1.0f / DM)), 0.f);
    const float rden = rcp_approx(bf_round(sqrt_approx(bf_round(bf_round(var) + 1e-5f))));
    const float rhi = bf_round(rden);
    mean2 = pack_bf16(ms, ms);
    rhi2 = pack_bf16(rhi, rhi);
    rlo2 = pack_bf16(rden - rhi, rden - rhi);
}
template <int N0, int N>
__device__ __forceinline__ void ln_apply(uint32_t (&u)[N], uint32_t mean2, uint32_t rhi2, uint32_t rlo2, uint8_t* dst) {
#pragma unroll
    for (int i = 0; i < 4; i++) {
        uint32_t o[4];
#pragma unroll
        for (int k = 0; k < 4; k++) {
            const uint32_t d = bf2_sub(u[N0 + 4 * i + k], mean2);
            o[k] = bf2_fma(d, rhi2, bf2_mul(d, rlo2));
        }
#pragma unroll
        for (int k = 0; k < 4; k++) u[N0 + 4 * i + k] = o[k];
        __stcg(reinterpret_cast<uint4*>(dst + i * 131072), make_uint4(o[0], o[1], o[2], o[3]));
    }
}
__device__ __forceinline__ int query_rowblock(int pair, int c, int w, int seg) {
    const int qA = (w ? 0 : 2) + c;
    return 4 * attn_rowblock(pair, seg) + (seg ? 3 - qA : qA);
}

__device__ __noinline__ void fetch_helper(const uint8_t* w_u, uint32_t sb, int w, int lane, int pair, int c) {
    const uint32_t page = sb + SM_REGION + w * PAGE + lane * 16;
    mbar_sleep(sb + BAR_FULL + 5 * 8, 0);
#pragma unroll 1
    for (int i = 0; i < 2; i++) {
        lsu_prefetch(ptr_off(w_u, ((pair * 2 + c) * 4 + i * 2 + (lane >> 4)) * 8192 + 2048 + (lane & 15) * 128));
        __nanosleep(300);
    }
    const unsigned e1 = __ldcg(&g_sync.done) / NCTA + 1;
#pragma unroll 1
    for (int e = 1; e <= 7; e += 2) mbar_sleep(sb + BAR_DONE + 8, (e >> 1) & 1);
    const int rb = out_rows(pair) * 4 + c * 2 + w, kb0 = out_cols(pair);
    const uint8_t* src = ptr_off(g_xn, xn_block(rb, kb0) + lane * 16);
#pragma unroll 1
    for (int i = 0; i < 32; i += 4) {
#pragma unroll
        for (int k = 0; k < 4; k++) cp_async16(page + (i + k) * 512, src + (i + k) * 512 + (i >> 4) * (32768 - 8192));
        __nanosleep(200);
    }
    wait_counter(&g_sync.ffn_done, e1);
    const int r = __ldcg(ptr_off(g_sel, (lane >> 4) * 4)) - rb * 64, ch = lane & 15;
    const uint4 t = __ldcg(ptr_off(g_routed, ((lane >> 4) * 128 + kb0 * 8 + ch) * 16));
    asm volatile("cp.async.wait_all;" ::: "memory");
    __syncwarp();
    if (r >= 0 && r < 64)
        sts128(sb + SM_REGION + w * PAGE + (ch >> 3) * 8192 + r * 128 + (((ch & 7) ^ (r & 7)) << 4), t.x, t.y, t.z, t.w);
    __syncwarp();
    if (lane == 0) mbar_arrive(sb + BAR_G + w * 8);
    PROF(20, 2);
}

__device__ __noinline__ void sync_helper(uint32_t sb, int lane, int pair, int c) {
    const unsigned e1 = __ldcg(&g_sync.done) / NCTA + 1;
    const int ib = out_rows(pair);
    int e = 0, b = 0;
#pragma unroll 1
    for (uint32_t n = 0; (e < 9 || b < 7) && n < SPIN_LIMIT; n++) {
        if (e < 9 && __all_sync(~0u, mbar_test(sb + BAR_DONE + (e & 1) * 8, (e >> 1) & 1))) {
            const int rnd = e > 4, ev = (e - 1) & 3;
            unsigned* flag = e == 0 ? &g_sync.ln
                           : ev < 2 ? ptr_off(g_sync.kv, (rnd * 16 + kv_head(pair) + 8 * ev) * 32)
                                    : ptr_off(g_sync.ctx, (query_rowblock(pair, c, lane & 1, ev & 1) * NH + rnd * 16 + (pair >> 2)) * 4);
            asm volatile("fence.proxy.async.global;\nfence.release.gpu;" ::: "memory");
            if (lane < ((e == 0 || ev < 2) ? 1 : 2)) asm volatile("red.relaxed.gpu.global.add.u32 [%0], 1;" ::"l"(flag) : "memory");
            PROF(10 + e, 2);
            e++;
        }
        if (b < 7 && e > 0 && (b < 4 || (n & POLL_MASK) == 0)) {
            const int i = b == 4 ? lane >> 1 : 8 * b - 24 + ((lane >> 1) & 7);
            const unsigned* cnt = b == 0 ? &g_sync.ln
                                : b == 2 ? ptr_off(g_sync.kvfree, (kv_head(pair) + 8 * (lane & 1)) * 32)
                                : b < 4 ? ptr_off(g_sync.kv, ((b >> 1) * 16 + (pair >> 2)) * 32)
                                        : ptr_off(g_sync.ctx, ((4 * ib + 2 * c + (lane & 1)) * NH + outproj_head(i & 31, ib)) * 4);
            if (__all_sync(~0u, (int)(ld_relaxed(cnt) - e1 * (b == 0 ? NMAIN : b == 2 ? 8 : b < 4 ? 16 : 1)) >= 0)) {
                asm volatile("fence.acquire.gpu;\nfence.proxy.async.global;" ::: "memory");
                __syncwarp();
                if (lane == 0) mbar_arrive(sb + BAR_DEP + b * 8);
                PROF(1 + b, 2);
                b++;
            }
        }
        __nanosleep(150);
    }
}

__device__ __forceinline__ unsigned long long block_max_key(unsigned long long k, unsigned long long* red, int tid) {
#pragma unroll
    for (int o = 16; o; o >>= 1) {
        unsigned long long t = __shfl_xor_sync(~0u, k, o);
        k = t > k ? t : k;
    }
    bar_sync(1, 256);
    if ((tid & 31) == 0) red[tid >> 5] = k;
    bar_sync(1, 256);
    k = red[0];
#pragma unroll
    for (int i = 1; i < 8; i++) k = red[i] > k ? red[i] : k;
    return k;
}

constexpr int FS = FF / 4;
constexpr int FSTAGE = 32768, FNST = 6;
constexpr int FN1 = 2 * (DM / 16), FN2 = FS / 16;

__device__ __forceinline__ void ffn_producer(uint32_t sb, int s, const CUtensorMap* m_gate, const CUtensorMap* m_up,
                                             const CUtensorMap* m_down) {
    wait_counter(&g_sync.ln, (__ldcg(&g_sync.done) / NCTA + 1) * NMAIN);
    int slot = 0, ph = 1;
#pragma unroll 1
    for (int st = 0; st < FN1 + FN2; st++) {
        mbar_sleep(sb + BAR_EMPTY + slot * 8, ph);
        const uint32_t bar = sb + BAR_FULL + slot * 8;
        const bool up = st < FN1;
        mbar_expect_tx(bar, up ? FS * 32 : DM * 32);
        tma_3d_hint(sb + slot * FSTAGE, up ? ((st & 1) ? m_up : m_gate) : m_down, 0,
                    up ? (st >> 1) * 16 : s * FS + (st - FN1) * 16, up ? s * (FS / 64) : 0, bar, POL_FIRST);
        if (++slot == FNST) { slot = 0; ph ^= 1; }
    }
}

__device__ __forceinline__ void ffn_cta(uint8_t* smem, uint32_t sb, int s, unsigned epoch, const __nv_bfloat16* w_r) {
    const int tid = threadIdx.x, lane = tid & 31;
    const int warp = __shfl_sync(~0u, tid >> 5, 0), w = warp >> 2;
    constexpr uint32_t XB = FNST * FSTAGE, HB = XB + 16384, AUX = HB + 14336;
    unsigned long long* red = reinterpret_cast<unsigned long long*>(smem + AUX);
    unsigned* flag = reinterpret_cast<unsigned*>(smem + AUX + 128);
    const unsigned e1 = epoch + 1;
    for (int i = tid; i < (16384 + 14336) / 16; i += 256) reinterpret_cast<uint4*>(smem + XB)[i] = make_uint4(0, 0, 0, 0);
    {
        float wf[32];
#pragma unroll
        for (int i = 0; i < 4; i++) {
            const uint4 t = __ldg(reinterpret_cast<const uint4*>(w_r) + lane + 32 * i);
            const uint32_t tu[4] = {t.x, t.y, t.z, t.w};
#pragma unroll
            for (int k = 0; k < 4; k++) { wf[8 * i + 2 * k] = bf_lo(tu[k]); wf[8 * i + 2 * k + 1] = bf_hi(tu[k]); }
        }
        if (tid == 0) wait_counter(&g_sync.ln, e1 * NMAIN);
        bar_sync(1, 256);
#pragma unroll 1
        for (int r0 = s * (SEQ / 4) + warp * (SEQ / 32); r0 < s * (SEQ / 4) + (warp + 1) * (SEQ / 32); r0 += 4) {
            uint4 t[4][4];
#pragma unroll
            for (int r = 0; r < 4; r++)
#pragma unroll
                for (int i = 0; i < 4; i++) t[r][i] = __ldcg(reinterpret_cast<const uint4*>(g_xn + image_offset(r0 + r, lane) + i * 131072));
            float acc[4];
#pragma unroll
            for (int r = 0; r < 4; r++) {
                float a = 0.f, b = 0.f;
#pragma unroll
                for (int i = 0; i < 4; i++) {
                    const uint32_t tu[4] = {t[r][i].x, t[r][i].y, t[r][i].z, t[r][i].w};
#pragma unroll
                    for (int k = 0; k < 4; k++) {
                        a = fmaf(bf_lo(tu[k]), wf[8 * i + 2 * k], a);
                        b = fmaf(bf_hi(tu[k]), wf[8 * i + 2 * k + 1], b);
                    }
                }
                acc[r] = a + b;
            }
#pragma unroll
            for (int o = 16; o; o >>= 1)
#pragma unroll
                for (int r = 0; r < 4; r++) acc[r] += __shfl_xor_sync(~0u, acc[r], o);
            if (lane < 4) __stcg(&g_r[r0 + lane], bf_round(lane == 0 ? acc[0] : lane == 1 ? acc[1] : lane == 2 ? acc[2] : acc[3]));
        }
        __threadfence();
        bar_sync(1, 256);
        if (tid == 0) {
            red_release(&g_sync.router);
            wait_counter(&g_sync.router, e1 * 4);
        }
        bar_sync(1, 256);
    }
    unsigned long long keys[8];
    unsigned long long best = 0;
#pragma unroll
    for (int i = 0; i < 8; i++) {
        int idx = tid + 256 * i;
        uint32_t b = __float_as_uint(__ldcg(&g_r[idx]) + 0.0f);
        b = (b & 0x80000000u) ? ~b : (b | 0x80000000u);
        keys[i] = ((unsigned long long)b << 32) | (unsigned)(SEQ - 1 - idx);
        best = keys[i] > best ? keys[i] : best;
    }
    const unsigned long long k0 = block_max_key(best, red, tid);
    best = 0;
#pragma unroll
    for (int i = 0; i < 8; i++) best = (keys[i] != k0 && keys[i] > best) ? keys[i] : best;
    const unsigned long long k1 = block_max_key(best, red, tid);
    const int row = SEQ - 1 - (int)((w ? k1 : k0) & 0xffffffffu);
    const int ch = tid & 127;
    const uint4 xrow = __ldcg(reinterpret_cast<const uint4*>(g_xn + image_offset(row, ch)));
    *reinterpret_cast<uint4*>(smem + XB + (ch >> 3) * 1024 + w * 128 + (((ch & 7) ^ w) << 4)) = xrow;
    fence_async_smem();
    bar_sync(1, 256);
    PROF(20, tid >> 7);
    int slot = 0, ph = 0, prev = 0;
    auto next_stage = [&](bool has_prev) {
        wg_commit();
        wg_wait<1>();
        if (has_prev && lane < 2) mbar_arrive(sb + BAR_EMPTY + prev * 8);
        prev = slot;
        if (++slot == FNST) { slot = 0; ph ^= 1; }
    };
    {
        float ag[28], au[28];
#pragma unroll
        for (int i = 0; i < 28; i++) ag[i] = au[i] = 0.f;
#pragma unroll 1
        for (int ks = 0; ks < DM / 16; ks++) {
            const uint64_t db = make_desc(sb + XB + (ks >> 2) * 1024 + (ks & 3) * 32, 16);
            mbar_wait(sb + BAR_FULL + slot * 8, ph);
            uint64_t da = make_desc(sb + slot * FSTAGE + w * (7 * 2048), 16);
            wg_fence();
#pragma unroll
            for (int b = 0; b < 7; b++) wgmma_n8_ta(ag + 4 * b, da + b * 128, db);
            next_stage(ks > 0);
            mbar_wait(sb + BAR_FULL + slot * 8, ph);
            da = make_desc(sb + slot * FSTAGE + w * (7 * 2048), 16);
            wg_fence();
#pragma unroll
            for (int b = 0; b < 7; b++) wgmma_n8_ta(au + 4 * b, da + b * 128, db);
            next_stage(true);
        }
        wg_wait<0>();
        reg_fence(ag);
        reg_fence(au);
        if ((lane & 3) == 0) {
#pragma unroll
            for (int i = 0; i < 28; i++) {
                const int f = (warp & 3) * 16 + (lane >> 2) + (i & 2) * 4, tok = i & 1;
                const float h = bf_round(silu_f(bf_round(ag[i]))) * bf_round(au[i]);
                *reinterpret_cast<__nv_bfloat16*>(smem + HB + (w * 7 + (i >> 2)) * 1024 + tok * 128 + (((f >> 3) ^ tok) << 4) + (f & 7) * 2) =
                    __float2bfloat16_rn(h);
            }
        }
    }
    fence_async_smem();
    bar_sync(1, 256);
    PROF(21, tid >> 7);
    {
        float ay[32];
#pragma unroll
        for (int i = 0; i < 32; i++) ay[i] = 0.f;
#pragma unroll 1
        for (int ks = 0; ks < FN2; ks++) {
            const uint64_t db = make_desc(sb + HB + (ks >> 2) * 1024 + (ks & 3) * 32, 16);
            mbar_wait(sb + BAR_FULL + slot * 8, ph);
            const uint64_t da = make_desc(sb + slot * FSTAGE + w * (8 * 2048), 16);
            wg_fence();
#pragma unroll
            for (int b = 0; b < 8; b++) wgmma_n8_ta(ay + 4 * b, da + b * 128, db);
            next_stage(true);
        }
        wg_wait<0>();
        reg_fence(ay);
        if ((lane & 3) == 0) {
#pragma unroll
            for (int i = 0; i < 32; i++)
                g_ypart[(s * 2 + (i & 1)) * DM + (w * 8 + (i >> 2)) * 64 + (warp & 3) * 16 + (lane >> 2) + (i & 2) * 4] = ay[i];
        }
    }
    PROF(23, tid >> 7);
    __threadfence();
    bar_sync(1, 256);
    if (tid == 0) {
        *flag = atomicAdd(&g_sync.ffn_ticket, 1u) == epoch * 4 + 3;
        __threadfence();
    }
    bar_sync(1, 256);
    if (*flag) {
        const float sg = bf_round(__fdividef(1.0f, 1.0f + __expf(-__ldcg(&g_r[row]))));
        const uint32_t xu[4] = {xrow.x, xrow.y, xrow.z, xrow.w};
        uint32_t o[4];
#pragma unroll
        for (int k = 0; k < 4; k++) {
            float y0 = 0.f, y1 = 0.f;
#pragma unroll
            for (int q = 0; q < 4; q++) {
                const float2 y = __ldcg(reinterpret_cast<const float2*>(&g_ypart[(q * 2 + w) * DM + ch * 8 + 2 * k]));
                y0 += y.x; y1 += y.y;
            }
            o[k] = pack_bf16(bf_lo(xu[k]) + bf_round(bf_round(y0) * sg), bf_hi(xu[k]) + bf_round(bf_round(y1) * sg));
        }
        g_routed[w * 128 + ch] = make_uint4(o[0], o[1], o[2], o[3]);
        if (ch == 0) g_sel[w] = row;
        bar_sync(1, 256);
        if (tid == 0) red_release(&g_sync.ffn_done);
    }
}

__device__ __forceinline__ uint32_t slab_addr(uint32_t stg, int lane, int s) {
    const int row = ((lane >> 3) & 1) * 8 + (lane & 7);
    const int chunk = 2 * (s & 3) + (lane >> 4);
    return stg + row * 128 + (s >> 2) * 8192 + ((chunk ^ (lane & 7)) << 4);
}

constexpr float SM_SCALE = 0.08838834764831845f * 1.4426950408889634f;
constexpr float SUM_HI = 1048576.f, SUM_LO = 1.0f / 1048576.f;

template <int I0, int I1, int J0>
__device__ __forceinline__ void mask_range(float (&S)[64], float limf) {
#pragma unroll
    for (int i = I0; i < I1; i++) {
        const int j = i >> 2;
        float t;
        asm("add.sat.f32 %0, %1, %2;" : "=f"(t) : "f"((float)(32 * (j >> 2) + 2 * (j & 3) + (i & 1) - (i & 2) * 4)), "f"(-limf));
        S[4 * J0 + i] = fmaf(t, -1e30f, S[4 * J0 + i]);
    }
}
template <int J0>
__device__ __forceinline__ void mask_half(float (&S)[64], float limf, int v) {
    asm volatile("" : "+f"(limf));
    if (v < 2) {
        mask_range<0, 16, J0>(S, limf);
#pragma unroll
        for (int i = 16; i < 32; i++) S[4 * J0 + i] = -1e30f;
    } else {
        mask_range<16, 32, J0>(S, limf);
    }
}
__device__ __forceinline__ void issue_qk(float (&S)[64], const uint32_t (&Q)[32], uint32_t d0) {
#pragma unroll
    for (int s = 0; s < 8; s++)
        wgmma_n128_rs<1>(S, Q[4 * s], Q[4 * s + 1], Q[4 * s + 2], Q[4 * s + 3], d0 + s * 128, s > 0);
}
__device__ __forceinline__ void issue_qk_half(float (&T)[32], const uint32_t (&Q)[32], uint32_t d0) {
#pragma unroll
    for (int s = 0; s < 8; s++) wgmma_n64_rs_tb(T, Q[4 * s], Q[4 * s + 1], Q[4 * s + 2], Q[4 * s + 3], d0 + s * 128, s > 0);
}
template <int H>
__device__ __forceinline__ void issue_pv(float (&O)[64], const uint32_t (&Pm)[32], uint32_t d0, int acc) {
#pragma unroll
    for (int s = 4 * H; s < 4 * H + 4; s++)
        wgmma_n128_rs<0>(O, Pm[4 * s], Pm[4 * s + 1], Pm[4 * s + 2], Pm[4 * s + 3], d0 + H * (PAGE >> 4) + (s & 3) * 2, s > 0 ? 1 : acc);
}
template <int J0, int J1>
__device__ __forceinline__ void exp_groups(const float (&S)[64], uint32_t (&Pm)[32], float (&sum)[2]) {
#pragma unroll
    for (int i = 2 * J0; i < 2 * J1; i++) asm volatile("" : "+r"(Pm[i])::"memory");
#pragma unroll
    for (int j = J0; j < J1; j++) {
        const float e0 = ex2(S[4 * j]), e1 = ex2(S[4 * j + 1]), e2 = ex2(S[4 * j + 2]), e3 = ex2(S[4 * j + 3]);
        sum[0] = (j ? sum[0] + e0 : e0) + e1;
        sum[1] = (j ? sum[1] + e2 : e2) + e3;
        Pm[2 * j] = pack_bf16(e0, e1);
        Pm[2 * j + 1] = pack_bf16(e2, e3);
    }
}
__device__ __forceinline__ void shift_rows(float (&S)[64], float d0, float d1) {
#pragma unroll
    for (int j = 0; j < 16; j++) {
        S[4 * j] -= d0; S[4 * j + 1] -= d0; S[4 * j + 2] -= d1; S[4 * j + 3] -= d1;
    }
}
__device__ constexpr int chunk_src(int i) { return 4 * (4 * (i >> 3) + (i & 3)) + 2 * ((i >> 2) & 1); }
enum : uint32_t { CTL_FIRST = 1, CTL_SWITCH = 2, CTL_LAST = 4, CTL_HALF = 128, CTL_MASKHI = 256, CTL_WOUT = 512, CTL_PVHALF = 1024, CTL_PVACC = 16384,
                  CTL_SHIFT = 32768 };
__device__ __forceinline__ float quad_sum(float v) {
    v += __shfl_xor_sync(~0u, v, 1);
    return v + __shfl_xor_sync(~0u, v, 2);
}

__device__ __forceinline__ void store_part(uint8_t* base, uint32_t row_bits, int p, const uint32_t (&pk)[64], uint64_t pol) {
    asm volatile("{\n.reg .b64 d0, d1;\nxor.b64 d0, %0, %1;\nxor.b64 d1, d0, 64;\n"
                 "TS: .branchtargets P0, P1, P2, P3, P4, P5, P6, P7;\n"
                 "brx.idx.uni %2, TS;\n"
                 "P0:\n st.global.cg.L2::cache_hint.v4.u32 [d0 + 0], {%3, %4, %5, %6}, %67;\n st.global.cg.L2::cache_hint.v4.u32 [d1 + 0], {%11, %12, %13, %14}, %67;\n bra.uni DONE;\n"
                 "P1:\n st.global.cg.L2::cache_hint.v4.u32 [d0 + 0], {%7, %8, %9, %10}, %67;\n st.global.cg.L2::cache_hint.v4.u32 [d1 + 0], {%15, %16, %17, %18}, %67;\n bra.uni DONE;\n"
                 "P2:\n st.global.cg.L2::cache_hint.v4.u32 [d0 + 16384], {%19, %20, %21, %22}, %67;\n st.global.cg.L2::cache_hint.v4.u32 [d1 + 16384], {%27, %28, %29, %30}, %67;\n bra.uni DONE;\n"
                 "P3:\n st.global.cg.L2::cache_hint.v4.u32 [d0 + 16384], {%23, %24, %25, %26}, %67;\n st.global.cg.L2::cache_hint.v4.u32 [d1 + 16384], {%31, %32, %33, %34}, %67;\n bra.uni DONE;\n"
                 "P4:\n st.global.cg.L2::cache_hint.v4.u32 [d0 + 65536], {%35, %36, %37, %38}, %67;\n st.global.cg.L2::cache_hint.v4.u32 [d1 + 65536], {%43, %44, %45, %46}, %67;\n bra.uni DONE;\n"
                 "P5:\n st.global.cg.L2::cache_hint.v4.u32 [d0 + 65536], {%39, %40, %41, %42}, %67;\n st.global.cg.L2::cache_hint.v4.u32 [d1 + 65536], {%47, %48, %49, %50}, %67;\n bra.uni DONE;\n"
                 "P6:\n st.global.cg.L2::cache_hint.v4.u32 [d0 + 81920], {%51, %52, %53, %54}, %67;\n st.global.cg.L2::cache_hint.v4.u32 [d1 + 81920], {%59, %60, %61, %62}, %67;\n bra.uni DONE;\n"
                 "P7:\n st.global.cg.L2::cache_hint.v4.u32 [d0 + 81920], {%55, %56, %57, %58}, %67;\n st.global.cg.L2::cache_hint.v4.u32 [d1 + 81920], {%63, %64, %65, %66}, %67;\n bra.uni DONE;\n"
                 "DONE:\n}\n"
                 ::"l"(base), "l"((uint64_t)((p & 1) ? row_bits : 0)), "r"(p), "r"(pk[0]), "r"(pk[1]), "r"(pk[2]), "r"(pk[3]), "r"(pk[4]), "r"(pk[5]), "r"(pk[6]), "r"(pk[7]), "r"(pk[8]), "r"(pk[9]), "r"(pk[10]), "r"(pk[11]), "r"(pk[12]), "r"(pk[13]), "r"(pk[14]), "r"(pk[15]), "r"(pk[16]), "r"(pk[17]), "r"(pk[18]), "r"(pk[19]), "r"(pk[20]), "r"(pk[21]), "r"(pk[22]), "r"(pk[23]), "r"(pk[24]), "r"(pk[25]), "r"(pk[26]), "r"(pk[27]), "r"(pk[28]), "r"(pk[29]), "r"(pk[30]), "r"(pk[31]), "r"(pk[32]), "r"(pk[33]), "r"(pk[34]), "r"(pk[35]), "r"(pk[36]), "r"(pk[37]), "r"(pk[38]), "r"(pk[39]), "r"(pk[40]), "r"(pk[41]), "r"(pk[42]), "r"(pk[43]), "r"(pk[44]), "r"(pk[45]), "r"(pk[46]), "r"(pk[47]), "r"(pk[48]), "r"(pk[49]), "r"(pk[50]), "r"(pk[51]), "r"(pk[52]), "r"(pk[53]), "r"(pk[54]), "r"(pk[55]), "r"(pk[56]), "r"(pk[57]), "r"(pk[58]), "r"(pk[59]), "r"(pk[60]), "r"(pk[61]), "r"(pk[62]), "r"(pk[63]), "l"(pol)
                 : "memory");
}

__device__ __forceinline__ void store_part4(uint8_t* d0, int p, const uint32_t (&pk)[64]) {
    asm volatile("{\n.reg .b64 d1;\nxor.b64 d1, %0, 64;\n"
                 "TS: .branchtargets P0, P1, P2, P3;\n"
                 "brx.idx.uni %1, TS;\n"
                 "P0:\n st.global.cg.v4.u32 [%0 + 0], {%2, %3, %4, %5};\n st.global.cg.v4.u32 [d1 + 0], {%10, %11, %12, %13};\n bra.uni DONE;\n"
                 "P1:\n st.global.cg.v4.u32 [%0 + 1024], {%6, %7, %8, %9};\n st.global.cg.v4.u32 [d1 + 1024], {%14, %15, %16, %17};\n bra.uni DONE;\n"
                 "P2:\n st.global.cg.v4.u32 [%0 + 16384], {%18, %19, %20, %21};\n st.global.cg.v4.u32 [d1 + 16384], {%26, %27, %28, %29};\n bra.uni DONE;\n"
                 "P3:\n st.global.cg.v4.u32 [%0 + 17408], {%22, %23, %24, %25};\n st.global.cg.v4.u32 [d1 + 17408], {%30, %31, %32, %33};\n bra.uni DONE;\n"
                 "DONE:\n}\n"
                 ::"l"(d0), "r"(p), "r"(pk[0]), "r"(pk[1]), "r"(pk[2]), "r"(pk[3]), "r"(pk[4]), "r"(pk[5]), "r"(pk[6]), "r"(pk[7]), "r"(pk[8]), "r"(pk[9]), "r"(pk[10]), "r"(pk[11]), "r"(pk[12]), "r"(pk[13]), "r"(pk[14]), "r"(pk[15]), "r"(pk[16]), "r"(pk[17]), "r"(pk[18]), "r"(pk[19]), "r"(pk[20]), "r"(pk[21]), "r"(pk[22]), "r"(pk[23]), "r"(pk[24]), "r"(pk[25]), "r"(pk[26]), "r"(pk[27]), "r"(pk[28]), "r"(pk[29]), "r"(pk[30]), "r"(pk[31])
                 : "memory");
}

__device__ __forceinline__ void consumer(uint32_t sb, int pair, int c, uint8_t* out, const uint8_t* x) {
    const int tid = threadIdx.x;
    const int warp = __shfl_sync(~0u, tid >> 5, 0);
    const int w = warp >> 2, v = warp & 3;
    const int lane = __shfl_sync(~0u, tid & 31, tid & 31);

    const uint32_t empty_rel = lane == 2 ? mapa(sb + BAR_EMPTYL, c) : mapa(sb + BAR_EMPTY, lane & 1);
    auto release = [&](uint32_t grp) {
        if (lane < 3) mbar_arrive_cluster(empty_rel + (grp & 7) * 8);
    };
    auto wait_full = [&](uint32_t grp) { mbar_wait(sb + BAR_FULL + (grp & 7) * 8, (grp >> 3) & 1); };

    uint32_t g = 0;
    const uint32_t stg = sb + SM_REGION + w * PAGE + v * 2048;
    const uint32_t chunk0 = (lane >> 2) * 128 + (((lane & 3) ^ (lane >> 2)) << 4);
    auto mark_done = [&](int odd) {
        __syncwarp();
        if (lane == 0) mbar_arrive(sb + BAR_DONE + odd * 8);
    };
    auto ctx_dst = [&](int rnd, int seg) {
        const int rb = query_rowblock(pair, c, w, seg);
        return ptr_off(g_ctx, ((rb >> 1) * 64 + (rnd * 16 + (pair >> 2)) * 2) * PAGE + (rb & 1) * 8192 + v * 2048);
    };

    uint32_t ctl_tab;
    {
        const int t = lane, firstB = 2 * attn_rowblock(pair, 0) + 2 - w;
        auto is_half = [&](int u) { return (u == firstB - 1 || u == 16) && c == (u >= firstB); };
        auto block = [&](int u) { return u + (w == 1 && u >= firstB); };
        auto place = [](int j) { return ((j & 15) << 3) | ((j - (j * 43 >> 8) * 6) << 11); };
        const int jv = t ? min(2 * block(t - 1) + 2, 35) : -1, jk = t == 17 ? jv : max(2 * block(t) - 1, 0);
        const bool diag = t == firstB - 1 || t == 16;
        ctl_tab = ((t == 0 || t == firstB) ? CTL_FIRST : 0) | (t == firstB ? CTL_SWITCH : 0) | (t == 17 ? CTL_LAST : 0) |
                  (diag ? (is_half(t) ? CTL_HALF : CTL_MASKHI) : 0) | (t == firstB + 1 ? CTL_WOUT : 0) |
                  (is_half(t - 1) ? CTL_PVHALF : 0) | ((t == 1 || t == firstB + 1) ? 0 : CTL_PVACC) |
                  place(jk) | (place(jv) << 16);
    }

    uint32_t pk[64];
#pragma unroll
    for (int i = 0; i < 64; i++) asm volatile("" : "=r"(pk[i]));
    uint8_t* pend = nullptr;
    uint32_t prow = 0x400;
    auto write_part = [&](int p, uint64_t pol = POL_NORMAL) { store_part(pend, prow, p, pk, pol); };
    if (w == 1) bar_arrive(2, 256);

    for (int item = 0; item < 6; item++) {
        if ((0x1B >> item) & 1) {
            constexpr int nk = DC / 64;
            float acc[128];
            auto issue_kblock = [&](int first_acc) {
                wait_full(g);
                const uint32_t pg = sb + (g & 3) * (3 * PAGE);
                const uint64_t da = make_desc(pg + w * 8192, 16), db = make_desc(pg + PAGE, 16);
                wg_fence();
                wgmma_n256_ss(acc, da, db, first_acc);
                wgmma_n256_ss(acc, da + 128, db + 2, 1);
                wgmma_n256_ss(acc, da + 256, db + 4, 1);
                wgmma_n256_ss(acc, da + 384, db + 6, 1);
                wg_commit();
                g++;
            };
            if (item == 0) PROF(17, w);
            issue_kblock(0);
            if (item == 0) PROF(1, w);
            if (item == 0 && w == 0) PROF_GT(1);
            const int nparts = item == 0 ? 0 : (item == 3 ? 4 : 8);
            const int ln_row = (pair * 2 + c) * 16 + warp * 2;
            if (item == 0) {
                const uint8_t* src = ptr_off(x, ln_row * (DM * 2) + lane * 16);
#pragma unroll
                for (int i = 0; i < 8; i++) {
                    const uint4 t = __ldcg(reinterpret_cast<const uint4*>(src + i * 512));
                    pk[4 * i] = t.x; pk[4 * i + 1] = t.y; pk[4 * i + 2] = t.z; pk[4 * i + 3] = t.w;
                }
            }
#pragma unroll 1
            for (int kb = 1; kb < nk; kb++) {
                if (kb == nk - 1 && w == 1) bar_sync(4, 256);
                issue_kblock(1);
                if (kb == nk - 1 && w == 0) bar_arrive(4, 256);
                wg_wait<1>();
                release(g - 2);
                if (kb <= nparts) {
                    if (item == 4 && kb == 1) mbar_wait(sb + BAR_DEP + 16, 0);
                    write_part(kb - 1, item == 3 ? POL_FIRST : POL_NORMAL);
                    if (kb == nk - 1) write_part(nk - 1);
                    if (kb == nparts || kb == nk - 1) mark_done(item != 3);
                }
                if (g < 8) {
                    float s[2], q[2];
                    if (g == 4) {
                        ln_sums<0>(pk, s[0], q[0]);
                        pk[32] = __float_as_uint(s[0]); pk[33] = __float_as_uint(q[0]);
                    }
                    if (g == 5) {
                        ln_sums<16>(pk, s[1], q[1]);
                        pk[34] = __float_as_uint(s[1]); pk[35] = __float_as_uint(q[1]);
                    }
                    if (g == 6) {
#pragma unroll
                        for (int r = 0; r < 2; r++) { s[r] = __uint_as_float(pk[32 + 2 * r]); q[r] = __uint_as_float(pk[33 + 2 * r]); }
                        const bool hi = lane & 16, od = lane & 8;
                        float a = hi ? s[1] : s[0], b = hi ? q[1] : q[0];
                        a += __shfl_xor_sync(~0u, hi ? s[0] : s[1], 16);
                        b += __shfl_xor_sync(~0u, hi ? q[0] : q[1], 16);
                        float t = od ? b : a;
                        t += __shfl_xor_sync(~0u, od ? a : b, 8);
#pragma unroll
                        for (int o = 4; o; o >>= 1) t += __shfl_xor_sync(~0u, t, o);
#pragma unroll
                        for (int r = 0; r < 2; r++) {
                            s[r] = __shfl_sync(~0u, t, 16 * r);
                            q[r] = __shfl_sync(~0u, t, 16 * r + 8);
                        }
                        ln_finish(s[0], q[0], pk[36], pk[37], pk[38]);
                        ln_finish(s[1], q[1], pk[39], pk[40], pk[41]);
                    }
                    if (g == 6) ln_apply<0>(pk, pk[36], pk[37], pk[38], ptr_off(g_xn, image_offset(ln_row, lane)));
                    if (g == 7) {
                        ln_apply<16>(pk, pk[39], pk[40], pk[41], ptr_off(g_xn, image_offset(ln_row + 1, lane)));
                        mark_done(0);
                    }
                }
            }
            wg_wait<0>();
            reg_fence(acc);
            release(g - 1);
            PROF(2 + 2 * item, w);
            if (w == 0) PROF_GT(2 + 2 * item);
#pragma unroll
            for (int i = 0; i < 64; i++) pk[i] = pack_bf16(acc[chunk_src(i)], acc[chunk_src(i) + 1]);
            const uint32_t vrow = (v >> 1) * 32 + (lane >> 3) * 8 + (v & 1) * 4 + ((lane >> 2) & 1);
            pend = ptr_off(g_kv, ((kv_head(pair) + (item == 1 || item == 4 ? 8 : 0)) * 16 + kv_tokens(pair) * 2) * 65536 + w * 8192 +
                                     (c ? 32768 + vrow * 128 + (((lane & 3) ^ (vrow & 7)) << 4) : v * 2048 + chunk0));
            prow = c ? 0x120 : 0x400;
            PROF(3 + 2 * item, w);
            continue;
        }

        float O[64], S[64];
        auto issue_q = [&](int first_acc) {
            wait_full(g);
            const uint32_t pg = sb + (g & 3) * (3 * PAGE);
            const uint64_t da = make_desc(pg + w * 8192, 16), db = make_desc(pg + 2 * PAGE, 8192);
            const uint64_t dab = make_desc(pg + PAGE + (1 - w) * 8192, 16);
            wg_fence();
#pragma unroll
            for (int q = 0; q < 4; q++) wgmma_n128_ss(S, da + 2 * q, db + 128 * q, q ? 1 : first_acc);
            wg_commit();
#pragma unroll
            for (int q = 0; q < 4; q++) wgmma_n128_ss(O, dab + 2 * q, db + 128 * q, q ? 1 : first_acc);
            wg_commit();
            g++;
        };
        issue_q(0);
#pragma unroll 1
        for (int kb = 1; kb < DM / 64; kb++) {
            if (kb == DM / 64 - 2 && w == 1) bar_sync(4, 256);
            issue_q(1);
            if (kb == DM / 64 - 1 && w == 0) bar_arrive(4, 256);
            wg_wait<2>();
            release(g - 2);
            if (kb <= 8) {
                write_part(kb - 1);
                if (kb == 8) mark_done(0);
            }
        }
        uint32_t Q[32], Pm[32];
#pragma unroll
        for (int i = 0; i < 32; i++) Pm[i] = pk[32 + i];
        float lim = (float)(v * 16 + (lane >> 2) - 8 * (lane & 3));
        float mc[2] = {0.f, 0.f}, l[2] = {0.f, 0.f}, scale[2] = {0.f, 0.f}, sum[2];
        uint32_t ctl = __shfl_sync(~0u, ctl_tab, 0), nxt = __shfl_sync(~0u, ctl_tab, 1);
        int t = 1;
        asm volatile("" : "+f"(lim), "+f"(mc[0]), "+f"(mc[1]), "+f"(l[0]), "+f"(l[1]), "+r"(ctl), "+r"(nxt), "+r"(t));
        wg_wait<1>();
        reg_fence(S);
#pragma unroll
        for (int i = 0; i < 32; i++) Q[i] = pack_bf16(S[2 * i] * SM_SCALE, S[2 * i + 1] * SM_SCALE);
        reg_fence(Q);
        wait_full(g);
        wg_wait<0>();
        reg_fence(O);
        PROF(2 + 2 * item, w);
        if (w == 0) PROF_GT(2 + 2 * item);

        const uint32_t qaddr = stg + lane * 16;
        auto put_queries = [&](const float (&A)[64]) {
#pragma unroll
            for (int i = 0; i < 8; i++)
                sts128(qaddr + (i >> 2) * 8192 + (i & 3) * 512, pack_bf16(A[8 * i] * SM_SCALE, A[8 * i + 1] * SM_SCALE), pack_bf16(A[8 * i + 2] * SM_SCALE, A[8 * i + 3] * SM_SCALE),
                       pack_bf16(A[8 * i + 4] * SM_SCALE, A[8 * i + 5] * SM_SCALE), pack_bf16(A[8 * i + 6] * SM_SCALE, A[8 * i + 7] * SM_SCALE));
        };
        auto get_queries = [&]() {
#pragma unroll
            for (int i = 0; i < 8; i++) lds128(qaddr + (i >> 2) * 8192 + (i & 3) * 512, Q[4 * i], Q[4 * i + 1], Q[4 * i + 2], Q[4 * i + 3]);
        };
        const uint32_t kdesc0 = (uint32_t)make_desc(sb, PAGE), vdesc0 = (uint32_t)make_desc(sb, 16);
        auto wait_block = [&](uint32_t word) { mbar_wait(sb + BAR_FULL + (word & 56), (word >> 6) & 1); };
        auto write_out = [&](auto early) {
            uint8_t* dst = ctx_dst(item == 5, 0);
            uint8_t* d[2] = {ptr_off(dst, chunk0), ptr_off(dst, chunk0 ^ 64)};
#pragma unroll
            for (int i = early.value ? 0 : WN; i < (early.value ? WN : 8); i++) {
                const float sc = scale[i & 1];
                uint32_t q[4];
#pragma unroll
                for (int k = 0; k < 4; k++) q[k] = pack_bf16(O[chunk_src(4 * i + k)] * sc, O[chunk_src(4 * i + k) + 1] * sc);
                if (early.value && i > 0) {
#pragma unroll
                    for (int k = 0; k < 4; k++) O[4 * (i - 1) + k] = __uint_as_float(q[k]);
                }
                stg_hint(d[(i >> 1) & 1] + (i >> 2) * PAGE + (i & 1) * 1024, q[0], q[1], q[2], q[3], item == 2 ? POL_FIRST : POL_NORMAL);
            }
            if (!early.value) mark_done(1);
        };
        put_queries(O);
        bar_sync(2 + w, 256);
        if (!(ctl & CTL_HALF)) {
            wg_fence();
            issue_qk(S, Q, kdesc0);
            wg_commit();
            wg_fence();
            wg_commit();
            wg_commit();
            bar_arrive(3 - w, 256);
            wg_wait<2>();
            reg_fence(S);
        } else {
            float T[32];
            wg_fence();
            issue_qk_half(T, Q, kdesc0);
            wg_commit();
            wg_fence();
            wg_commit();
            wg_commit();
            bar_arrive(3 - w, 256);
            wg_wait<2>();
            reg_fence(T);
#pragma unroll
            for (int i = 0; i < 32; i++) S[i] = T[i];
        }
        for (;;) {
            const bool kready = mbar_try(sb + BAR_FULL + (nxt & 56), (nxt >> 6) & 1);
            if (ctl & (CTL_HALF | CTL_MASKHI | CTL_SHIFT)) {
                if (ctl & CTL_HALF) mask_half<0>(S, lim, v);
                if (ctl & CTL_MASKHI) mask_half<8>(S, lim, v);
                if (ctl & CTL_SHIFT) shift_rows(S, mc[0], mc[1]);
            }
            float early[4 * EARLY];
#pragma unroll
            for (int j = 0; j < EARLY; j++) {
#pragma unroll
                for (int i = 4 * j; i < 4 * j + 4; i++) early[i] = ex2(S[i]);
                sum[0] = (j ? sum[0] + early[4 * j] : early[4 * j]) + early[4 * j + 1];
                sum[1] = (j ? sum[1] + early[4 * j + 2] : early[4 * j + 2]) + early[4 * j + 3];
            }
            const uint32_t tie = __float_as_uint(sum[0]) & __float_as_uint(sum[1]) & (ctl & 0x80000000u);
            if (lane < 3) mbar_arrive_cluster(empty_rel + tie + (ctl & 56));
            wg_wait<1>();
#pragma unroll
            for (int j = 0; j < EARLY; j++) {
                asm volatile("" : "+r"(Pm[2 * j]), "+r"(Pm[2 * j + 1])::"memory");
                Pm[2 * j] = pack_bf16(early[4 * j], early[4 * j + 1]);
                Pm[2 * j + 1] = pack_bf16(early[4 * j + 2], early[4 * j + 3]);
            }
            exp_groups<EARLY, 8>(S, Pm, sum);
            const bool half = ctl & CTL_HALF;
            if (!half) {
                wg_wait<0>();
                reg_fence(O);
                if (lane < 3) mbar_arrive_cluster(empty_rel + ((ctl >> 16) & 56));
                exp_groups<8, 16>(S, Pm, sum);
            } else {
                asm volatile("wgmma.wait_group.sync.aligned 0;\n" ::: "memory");
                reg_fence(O);
                if (lane < 3) asm volatile("mbarrier.arrive.shared::cluster.b64 _, [%0];\n" ::"r"(empty_rel + ((ctl >> 16) & 56)) : "memory");
            }
            const bool over = !(sum[0] + sum[1] <= SUM_HI);
            const bool first = ctl & CTL_FIRST, suspect = over || (first && !(fminf(sum[0], sum[1]) >= SUM_LO));
            if (__any_sync(~0u, suspect || !kready) || (((ctl & CTL_SWITCH) | (nxt & (CTL_SWITCH | CTL_LAST | CTL_HALF))) != 0)) {
                if (!kready) wait_block(nxt);
                bool bad = __any_sync(~0u, suspect);
                if (bad) {
                    uint32_t b0 = __ballot_sync(~0u, sum[0] >= SUM_LO), b1 = __ballot_sync(~0u, sum[1] >= SUM_LO);
                    b0 |= b0 >> 1; b1 |= b1 >> 1;
                    b0 |= b0 >> 2; b1 |= b1 >> 2;
                    bad = __any_sync(~0u, over) || (first && (b0 & b1 & 0x11111111u) != 0x11111111u);
                }
                if (bad) {
                    float d0 = fmaxf(S[0], S[1]), d1 = fmaxf(S[2], S[3]);
#pragma unroll
                    for (int j = 1; j < 8; j++) {
                        d0 = fmaxf(d0, fmaxf(S[4 * j], S[4 * j + 1]));
                        d1 = fmaxf(d1, fmaxf(S[4 * j + 2], S[4 * j + 3]));
                    }
                    if (!half) {
#pragma unroll
                        for (int j = 8; j < 16; j++) {
                            d0 = fmaxf(d0, fmaxf(S[4 * j], S[4 * j + 1]));
                            d1 = fmaxf(d1, fmaxf(S[4 * j + 2], S[4 * j + 3]));
                        }
                    }
                    d0 = fmaxf(d0, __shfl_xor_sync(~0u, d0, 1));
                    d1 = fmaxf(d1, __shfl_xor_sync(~0u, d1, 1));
                    d0 = fmaxf(d0, __shfl_xor_sync(~0u, d0, 2));
                    d1 = fmaxf(d1, __shfl_xor_sync(~0u, d1, 2));
                    if (!first) {
                        d0 = fmaxf(d0, 0.f);
                        d1 = fmaxf(d1, 0.f);
                        const float a0 = ex2(-d0), a1 = ex2(-d1);
#pragma unroll
                        for (int j = 0; j < 16; j++) {
                            O[4 * j] *= a0; O[4 * j + 1] *= a0; O[4 * j + 2] *= a1; O[4 * j + 3] *= a1;
                        }
                        l[0] *= a0; l[1] *= a1;
                    }
                    mc[0] += d0; mc[1] += d1;
                    ctl_tab |= CTL_SHIFT;
                    nxt |= CTL_SHIFT;
                    shift_rows(S, d0, d1);
                    exp_groups<0, 8>(S, Pm, sum);
                    if (!half) exp_groups<8, 16>(S, Pm, sum);
                }
                if (ctl & CTL_SWITCH) write_out(std::true_type());
                if (nxt & CTL_LAST) break;
                if (nxt & CTL_SWITCH) {
                    get_queries();
                    nxt &= ~CTL_SHIFT;
                    ctl_tab &= ~CTL_SHIFT;
                }
                if (nxt & CTL_HALF) {
                    ctl = nxt;
                    float T[32];
                    bar_sync(2 + w, 256);
                    wg_fence();
                    issue_qk_half(T, Q, kdesc0 + (ctl & 0x3800));
                    wg_commit();
                    l[0] += sum[0]; l[1] += sum[1];
                    nxt = __shfl_sync(~0u, ctl_tab, ++t);
                    wait_block(ctl >> 16);
                    const uint32_t vdesc = vdesc0 + ((ctl >> 16) & 0x3800);
                    wg_fence();
                    issue_pv<0>(O, Pm, vdesc, ctl & CTL_PVACC);
                    wg_commit();
                    issue_pv<1>(O, Pm, vdesc, 1);
                    wg_commit();
                    bar_arrive(3 - w, 256);
                    wg_wait<2>();
                    reg_fence(T);
#pragma unroll
                    for (int i = 0; i < 32; i++) S[i] = T[i];
                    continue;
                }
            }
            ctl = nxt;
            bar_sync(2 + w, 256);
            wg_fence();
            issue_qk(S, Q, kdesc0 + (ctl & 0x3800));
            wg_commit();
            l[0] += sum[0]; l[1] += sum[1];
            nxt = __shfl_sync(~0u, ctl_tab, ++t);
            if (ctl & (CTL_SWITCH | CTL_WOUT)) {
                if (ctl & CTL_SWITCH) {
                    scale[0] = rcp_approx(quad_sum(l[0]));
                    scale[1] = rcp_approx(quad_sum(l[1]));
                    l[0] = l[1] = mc[0] = mc[1] = 0.f;
                    if (w == 1) { release((ctl >> 3) - 2); release((ctl >> 3) + 1); }
                } else {
                    write_out(std::false_type());
                }
            }
            wait_block(ctl >> 16);
            const uint32_t vdesc = vdesc0 + ((ctl >> 16) & 0x3800);
            if (!(ctl & CTL_PVHALF)) {
                wg_fence();
                issue_pv<0>(O, Pm, vdesc, ctl & CTL_PVACC);
                wg_commit();
                issue_pv<1>(O, Pm, vdesc, 1);
                wg_commit();
            } else {
                wg_fence();
                issue_pv<0>(O, Pm, vdesc, ctl & CTL_PVACC);
                wg_commit();
                wg_commit();
            }
            bar_arrive(3 - w, 256);
            wg_wait<2>();
            reg_fence(S);
        }
        g += 36;
        const uint32_t vdesc = vdesc0 + (nxt & 0x3800);
        if (nxt & CTL_PVHALF) {
            wg_fence();
            issue_pv<0>(O, Pm, vdesc, nxt & CTL_PVACC);
            wg_commit();
        } else {
            wg_fence();
            issue_pv<0>(O, Pm, vdesc, nxt & CTL_PVACC);
            issue_pv<1>(O, Pm, vdesc, 1);
            wg_commit();
        }
        l[0] += sum[0]; l[1] += sum[1];
        ctl_tab = (ctl_tab & ~(0x00780078u | CTL_SHIFT)) | ((ctl_tab + 0x00200020u) & 0x00780078u);
        const float i0 = rcp_approx(quad_sum(l[0])), i1 = rcp_approx(quad_sum(l[1]));
        const uint32_t tie = __float_as_uint(i0) & __float_as_uint(i1) & (nxt & 0x80000000u);
        if (lane + tie < (w ? 0 : 3)) mbar_arrive_cluster(empty_rel + ((g - 3) & 7) * 8);
        auto finish_attention = [&](uint32_t next) {
            reg_fence(O);
            if (w == 0) release(next - 2);
            release(next - 1);
#pragma unroll
            for (int i = 0; i < 32; i++) {
                const float sc = (i & 4) ? i1 : i0;
                pk[i] = pack_bf16(O[chunk_src(i)] * sc, O[chunk_src(i) + 1] * sc);
            }
            pend = ptr_off(ctx_dst(item == 5, 1), chunk0);
            PROF(3 + 2 * item, w);
            if (w == 0) PROF_GT(3 + 2 * item);
        };
        if (item != 5) {
            wg_wait<0>();
            finish_attention(g);
            prow = 0x400;
#pragma unroll
            for (int i = 32; i < 64; i++) pk[i] = Pm[i - 32];
            continue;
        }

        float acc[64];
        uint32_t slot = 0;
        auto issue_out = [&](int first_acc) {
            wait_full(g);
            const uint64_t da = make_desc(sb + slot + w * 8192, 16), db = make_desc(sb + slot + PAGE, 8192);
            wg_fence();
#pragma unroll
            for (int q = 0; q < 4; q++) wgmma_n128_ss(acc, da + 2 * q, db + 128 * q, q ? 1 : first_acc);
            wg_commit();
            g++;
            slot = slot == SM_REGION - 2 * PAGE ? 0 : slot + 2 * PAGE;
        };
        issue_out(0);
        wg_wait<1>();
        finish_attention(g - 1);
#pragma unroll 1
        for (int kb = 1; kb < 64 - PEEL; kb++) {
            issue_out(1);
            wg_wait<1>();
            release(g - 2);
            if (kb <= 8 && !(kb & 1)) {
                store_part4(pend, (kb >> 1) - 1, pk);
                if (kb == 8) mark_done(0);
            }
            if (kb >= 32 - PEEL && ((kb + PEEL) & 3) == 2 * w) {
                uint32_t u0, u1, u2, u3;
                const uint32_t a = stg + ((kb + PEEL) & 16) * 512 + ((kb + PEEL) & 12) * 128 + lane * 16;
                mbar_wait(sb + BAR_G + w * 8, 0);
                lds128(a, u0, u1, u2, u3);
                sts128(a, pack_bf16(silu_f(bf_lo(u0)), silu_f(bf_hi(u0))), pack_bf16(silu_f(bf_lo(u1)), silu_f(bf_hi(u1))),
                       pack_bf16(silu_f(bf_lo(u2)), silu_f(bf_hi(u2))), pack_bf16(silu_f(bf_lo(u3)), silu_f(bf_hi(u3))));
            }
        }
        const uint32_t goff = (out_rows(pair) * 256 + c * 128 + w * 64 + v * 16 + (lane >> 3)) * (DM * 2) +
                              out_cols(pair) * 128 + (((lane & 7) ^ (lane >> 3)) << 4);
        uint32_t xr[32], gr[32];
        {
            const uint8_t* src[2] = {ptr_off(x, goff), ptr_off(x, goff ^ 64)};
#pragma unroll
            for (int i = 0; i < 8; i++) {
                const uint4 t = ldg_hint(src[i & 1] + (i & 3) * (4 * DM * 2) + (i >> 2) * 128, POL_FIRST);
                xr[4 * i] = t.x; xr[4 * i + 1] = t.y; xr[4 * i + 2] = t.z; xr[4 * i + 3] = t.w;
            }
        }
#pragma unroll 1
        for (int i = 0; i < PEEL; i++) {
            if (i == PEEL - STAG && w == 1) bar_sync(4, 256);
            issue_out(1);
            if (i == PEEL - 1 && w == 0) bar_arrive(4, 256);
            wg_wait<1>();
        }
        asm volatile("barrier.cluster.arrive.relaxed.aligned;" ::: "memory");
#pragma unroll
        for (int i = 0; i < 8; i++) lds128(stg + (i >> 2) * 8192 + (i & 3) * 512 + lane * 16, gr[4 * i], gr[4 * i + 1], gr[4 * i + 2], gr[4 * i + 3]);
        uint8_t* dst[2] = {ptr_off(out, goff), ptr_off(out, goff ^ 64)};
        __syncwarp();
        wg_wait<0>();
        reg_fence(acc);
        PROF(14, w);
        if (w == 0) PROF_GT(14);
#pragma unroll
        for (int s = 0; s < 8; s++)
            stmatrix_x4(slab_addr(stg, lane, s), pack_bf16(acc[8 * s], acc[8 * s + 1]), pack_bf16(acc[8 * s + 2], acc[8 * s + 3]),
                        pack_bf16(acc[8 * s + 4], acc[8 * s + 5]), pack_bf16(acc[8 * s + 6], acc[8 * s + 7]));
        __syncwarp();
        uint32_t o[32];
#pragma unroll
        for (int i = 0; i < 8; i++) lds128(stg + (i >> 2) * 8192 + (i & 3) * 512 + lane * 16, o[4 * i], o[4 * i + 1], o[4 * i + 2], o[4 * i + 3]);
#pragma unroll
        for (int i = 0; i < 8; i++) {
#pragma unroll
            for (int k = 0; k < 4; k++) xr[4 * i + k] = bf2_add(xr[4 * i + k], bf2_mul(o[4 * i + k], gr[4 * i + k]));
            __stcg(reinterpret_cast<uint4*>(dst[i & 1] + (i & 3) * (4 * DM * 2) + (i >> 2) * 128), make_uint4(xr[4 * i], xr[4 * i + 1], xr[4 * i + 2], xr[4 * i + 3]));
        }
        PROF(28, w);
        return;
    }
}

__global__ void __cluster_dims__(2, 1, 1) __launch_bounds__(384, 1)
fused_kernel(const __grid_constant__ CUtensorMap m_ckv, const __grid_constant__ CUtensorMap m_wuk,
             const __grid_constant__ CUtensorMap m_wuv, const __grid_constant__ CUtensorMap m_wq,
             const __grid_constant__ CUtensorMap m_wo, const __grid_constant__ CUtensorMap m_gate,
             const __grid_constant__ CUtensorMap m_up, const __grid_constant__ CUtensorMap m_down, const Params P) {
    extern __shared__ __align__(1024) uint8_t smem[];
    const uint32_t sb = __shfl_sync(~0u, smem_u32(smem), 0);
    const int tid = threadIdx.x;
    const int cl = blockIdx.x >> 1, c = blockIdx.x & 1;
    const int pair = cl >= 64 ? cl : cl < 4 ? cl * 16 + 15 : cl < 36 ? ((cl - 4) >> 3) * 16 + ((cl - 4) & 7)
                                                                    : ((cl - 36) / 7) * 16 + 8 + (cl - 36) % 7;
    const bool starter = tid == 256 && pair < NMAIN / 2;
    const CUtensorMap* m_wu = c ? &m_wuv : &m_wuk;
    if (tid == 256) {
        mbar_init(sb + BAR_FULL, 1);
        if (starter) {
            asm volatile("fence.mbarrier_init.release.cluster;" ::: "memory");
            mbar_expect_tx(sb + BAR_FULL, 3 * PAGE);
            tma_3d(sb, m_wu, 0, 0, kv_head(pair) * 2, sb + BAR_FULL);
            tma_3d(sb + PAGE, &m_ckv, 0, kv_tokens(pair) * 256, 0, sb + BAR_FULL);
            tma_3d(sb + 2 * PAGE, &m_ckv, 0, kv_tokens(pair) * 256 + 128, 0, sb + BAR_FULL);
        }
#pragma unroll
        for (int i = 1; i < NBAR; i++) mbar_init(sb + SM_BAR + i * 8, (i >> 3) == 1 ? 16 : i >= 25 ? 8 : 1);
        asm volatile("fence.mbarrier_init.release.cluster;" ::: "memory");
    }
    if (starter) {
#pragma unroll 1
        for (int kb = 1; kb < 4; kb++) mbar_expect_tx(sb + BAR_FULL + kb * 8, 3 * PAGE);
        tma_3d(sb + 3 * PAGE, m_wu, 0, 64, kv_head(pair) * 2, sb + BAR_FULL + 8);
    }
    PROF(18, (tid >> 7) & 1);
    __syncthreads();
    cluster_sync();
    PROF(22, (tid >> 7) & 1);
    PROF(19, (tid >> 7) & 1);
    const int warp = __shfl_sync(~0u, tid >> 5, 0), lane = tid & 31;
    auto dump_prof = [&]() {
    };
    if (pair >= NMAIN / 2) {
        if (warp < 8) ffn_cta(smem, sb, blockIdx.x - NMAIN, __ldcg(&g_sync.done) / NCTA, P.w_r);
        else if (tid == 256) ffn_producer(sb, blockIdx.x - NMAIN, &m_gate, &m_up, &m_down);
        __syncwarp();
        PROF(29, tid >> 7);
        cluster_sync();
        if (tid == 0) atomicAdd(&g_sync.done, 1u);
        if (warp < 8) dump_prof();
    } else if (warp < 8) {
        asm volatile("setmaxnreg.inc.sync.aligned.u32 232;");
        consumer(sb, pair, c, P.out, (const uint8_t*)P.x);
        PROF(29, tid >> 7);
        asm volatile("barrier.cluster.wait.aligned;" ::: "memory");
        dump_prof();
    } else {
        asm volatile("setmaxnreg.dec.sync.aligned.u32 40;");
        if (starter) {
#pragma unroll 1
            for (int kb = 1; kb < 4; kb++) {
                if (kb > 1) tma_3d(sb + kb * (3 * PAGE), m_wu, 0, kb * 64, kv_head(pair) * 2, sb + BAR_FULL + kb * 8);
                tma_3d_mc(sb + kb * (3 * PAGE) + (1 + c) * PAGE, &m_ckv, 0, kv_tokens(pair) * 256 + c * 128, kb, sb + BAR_FULL + kb * 8);
            }
        }
        if (warp == 10) {
            sync_helper(sb, lane, pair, c);
        } else if (warp & 1) {
            fetch_helper((warp & 2) ? P.w_uv : P.w_uk, sb, (warp >> 1) & 1, lane, pair, c);
        } else {
            producer(P, sb, pair, c, &m_ckv, m_wu, &m_wq, &m_wo);
        }
        bar_sync(6, 128);
        if (tid == 256) atomicAdd(&g_sync.done, 1u);
        cluster_sync();
    }
}

typedef CUresult (*EncodeFn)(CUtensorMap*, CUtensorMapDataType, cuuint32_t, void*, const cuuint64_t*, const cuuint64_t*,
                             const cuuint32_t*, const cuuint32_t*, CUtensorMapInterleave, CUtensorMapSwizzle,
                             CUtensorMapL2promotion, CUtensorMapFloatOOBfill);

void make_map_w(EncodeFn fn, CUtensorMap* m, const void* ptr, int rows, int cols, int blocks, int box_rows = 32) {
    cuuint64_t dims[3] = {64, (cuuint64_t)rows, (cuuint64_t)cols / 64};
    cuuint64_t strides[2] = {(cuuint64_t)cols * 2, 128};
    cuuint32_t box[3] = {64, (cuuint32_t)box_rows, (cuuint32_t)blocks};
    cuuint32_t es[3] = {1, 1, 1};
    fn(m, CU_TENSOR_MAP_DATA_TYPE_BFLOAT16, 3, const_cast<void*>(ptr), dims, strides, box, es, CU_TENSOR_MAP_INTERLEAVE_NONE,
       CU_TENSOR_MAP_SWIZZLE_128B, CU_TENSOR_MAP_L2_PROMOTION_L2_256B, CU_TENSOR_MAP_FLOAT_OOB_FILL_NONE);
}

}

extern "C" void kernel_launch(void* const* d_in, const int* in_sizes, int n_in, void* d_out, int out_size) {
    static EncodeFn fn = nullptr;
    if (!fn) {
        void* f = nullptr;
        cudaDriverEntryPointQueryResult qr;
        cudaGetDriverEntryPoint("cuTensorMapEncodeTiled", &f, cudaEnableDefault, &qr);
        fn = (EncodeFn)f;
        cudaFuncSetAttribute(fused_kernel, cudaFuncAttributeMaxDynamicSharedMemorySize, SMEM_BYTES);
    }
    CUtensorMap m_ckv, m_wuk, m_wuv, m_wq, m_wo, m_gate, m_up, m_down;
    make_map_w(fn, &m_gate, d_in[8], DM, FF, FS / 64, 16);
    make_map_w(fn, &m_up, d_in[9], DM, FF, FS / 64, 16);
    make_map_w(fn, &m_down, d_in[10], FF, DM, DM / 64, 16);
    make_map_w(fn, &m_ckv, d_in[1], SEQ, DC, 1, 128);
    make_map_w(fn, &m_wq, d_in[2], DM, NH * 128, 1, 64);
    make_map_w(fn, &m_wuk, d_in[3], DC, NH * 128, 2, 64);
    make_map_w(fn, &m_wuv, d_in[4], DC, NH * 128, 2, 64);
    make_map_w(fn, &m_wo, d_in[5], NH * 128, DM, 1, 64);
    Params P;
    P.x = (const __nv_bfloat16*)d_in[0];
    P.w_r = (const __nv_bfloat16*)d_in[7];
    P.c_kv = (const uint8_t*)d_in[1];
    P.w_uk = (const uint8_t*)d_in[3];
    P.w_uv = (const uint8_t*)d_in[4];
    P.out = (uint8_t*)d_out;
    fused_kernel<<<NCTA, 384, SMEM_BYTES>>>(m_ckv, m_wuk, m_wuv, m_wq, m_wo, m_gate, m_up, m_down, P);
}
```

```cpp
#include <cuda_runtime.h>
#include <cuda_bf16.h>
#include <cuda.h>
#include <stdint.h>
#include <type_traits>

namespace {

constexpr int SEQ = 2048, DM = 1024, NH = 32, DC = 512, FF = 3584;
constexpr int PAGE = 16384;
constexpr int NRING = 12;
constexpr int NCTA = 132, NMAIN = 128;
constexpr uint32_t SM_REGION = NRING * PAGE;
constexpr uint32_t SM_BAR = (NRING + 2) * PAGE;
constexpr uint32_t BAR_FULL = SM_BAR, BAR_EMPTY = SM_BAR + 64;
constexpr uint32_t BAR_DEP = SM_BAR + 128;
constexpr uint32_t BAR_G = SM_BAR + 184;
constexpr uint32_t BAR_DONE = SM_BAR + 200;
constexpr uint32_t BAR_EMPTYL = SM_BAR + 216;
constexpr int NBAR = 35;
constexpr uint32_t SM_PROF = SM_BAR + 320;
constexpr int SMEM_BYTES = SM_PROF + 512;
constexpr uint32_t SPIN_LIMIT = 1u << 16;
constexpr uint32_t POLL_MASK = 7;
constexpr int EARLY = 2;
constexpr int WN = 5;
constexpr int PEEL = 5, STAG = 3;

struct SyncBlock {
    unsigned done;       unsigned pad0[31];
    unsigned ln;         unsigned pad1[31];
    unsigned router;     unsigned pad4[31];
    unsigned ffn_ticket; unsigned pad2[31];
    unsigned ffn_done;   unsigned pad3[31];
    unsigned kv[NH * 8];
    unsigned kvfree[16 * 8];
    unsigned ctx[32 * NH];
};

__device__ __align__(1024) uint8_t g_xn[8 * 16 * 4 * 8192];
__device__ __align__(4096) uint8_t g_kv[16 * 16 * 65536];
__device__ __align__(4096) uint8_t g_ctx[16 * 64 * 16384];
__device__ __align__(16) uint4 g_routed[2 * 128];
__device__ int g_sel[2];
__device__ __align__(16) float g_r[SEQ];
__device__ __align__(16) float g_ypart[4 * 2 * DM];
__device__ SyncBlock g_sync;

__device__ __forceinline__ uint32_t smem_u32(const void* p) { return (uint32_t)__cvta_generic_to_shared(p); }

__device__ __forceinline__ void mbar_init(uint32_t bar, uint32_t count) {
    asm volatile("mbarrier.init.shared::cta.b64 [%0], %1;" ::"r"(bar), "r"(count) : "memory");
}
#define MBAR_WAIT_ASM(HINT, LIMIT)                                                                  \
    asm volatile("{\n.reg .pred p;\n.reg .u32 n;\nmov.u32 n, 0;\n"                                  \
                 "WAIT_LOOP:\n"                                                                     \
                 "mbarrier.try_wait.parity.shared::cta.b64 p, [%0], %1" HINT ";\n"                  \
                 "@p bra WAIT_DONE;\n"                                                              \
                 "add.u32 n, n, 1;\n"                                                               \
                 "setp.lt.u32 p, n, " LIMIT ";\n"                                                   \
                 "@p bra WAIT_LOOP;\n"                                                              \
                 "WAIT_DONE:\n}\n" ::"r"(bar), "r"(parity) : "memory")
__device__ __forceinline__ void mbar_wait(uint32_t bar, uint32_t parity) { MBAR_WAIT_ASM("", "131072"); }
__device__ __forceinline__ void mbar_sleep(uint32_t bar, uint32_t parity) { MBAR_WAIT_ASM(", 2000", "8192"); }
__device__ __forceinline__ bool mbar_try(uint32_t bar, uint32_t parity) {
    uint32_t ok;
    asm volatile("{\n.reg .pred p;\nmbarrier.try_wait.parity.shared::cta.b64 p, [%1], %2;\nselp.u32 %0, 1, 0, p;\n}\n"
                 : "=r"(ok) : "r"(bar), "r"(parity) : "memory");
    return ok;
}
__device__ __forceinline__ bool mbar_test(uint32_t bar, uint32_t parity) {
    uint32_t ok;
    asm volatile("{\n.reg .pred p;\nmbarrier.test_wait.parity.shared::cta.b64 p, [%1], %2;\nselp.u32 %0, 1, 0, p;\n}\n"
                 : "=r"(ok) : "r"(bar), "r"(parity) : "memory");
    return ok;
}
__device__ __forceinline__ bool elect_one() {
    uint32_t ok;
    asm volatile("{\n.reg .pred p;\nelect.sync _|p, 0xffffffff;\nselp.u32 %0, 1, 0, p;\n}\n" : "=r"(ok));
    return ok;
}
__device__ __forceinline__ void mbar_arrive(uint32_t bar) {
    asm volatile("mbarrier.arrive.shared::cta.b64 _, [%0];" ::"r"(bar) : "memory");
}
__device__ __forceinline__ void mbar_expect_tx(uint32_t bar, uint32_t bytes) {
    asm volatile("mbarrier.arrive.expect_tx.shared::cta.b64 _, [%0], %1;" ::"r"(bar), "r"(bytes) : "memory");
}
__device__ __forceinline__ void mbar_arrive_cluster(uint32_t cluster_addr) {
    asm volatile("mbarrier.arrive.shared::cluster.b64 _, [%0];" ::"r"(cluster_addr) : "memory");
}
__device__ __forceinline__ uint32_t mapa(uint32_t addr, uint32_t rank) {
    uint32_t r;
    asm("mapa.shared::cluster.u32 %0, %1, %2;" : "=r"(r) : "r"(addr), "r"(rank));
    return r;
}
__device__ __forceinline__ void tma_3d(uint32_t dst, const CUtensorMap* m, int c0, int c1, int c2, uint32_t bar) {
    asm volatile("cp.async.bulk.tensor.3d.shared::cluster.global.mbarrier::complete_tx::bytes [%0], [%1, {%3, %4, %5}], [%2];"
                 ::"r"(dst), "l"(m), "r"(bar), "r"(c0), "r"(c1), "r"(c2) : "memory");
}
__device__ __forceinline__ void tma_3d_hint(uint32_t dst, const CUtensorMap* m, int c0, int c1, int c2, uint32_t bar, uint64_t pol) {
    asm volatile("cp.async.bulk.tensor.3d.shared::cluster.global.mbarrier::complete_tx::bytes.L2::cache_hint [%0], [%1, {%3, %4, %5}], [%2], %6;"
                 ::"r"(dst), "l"(m), "r"(bar), "r"(c0), "r"(c1), "r"(c2), "l"(pol) : "memory");
}
__device__ __forceinline__ void tma_3d_mc(uint32_t dst, const CUtensorMap* m, int c0, int c1, int c2, uint32_t bar) {
    asm volatile("cp.async.bulk.tensor.3d.shared::cluster.global.mbarrier::complete_tx::bytes.multicast::cluster [%0], [%1, {%3, %4, %5}], [%2], %6;"
                 ::"r"(dst), "l"(m), "r"(bar), "r"(c0), "r"(c1), "r"(c2), "h"((uint16_t)3) : "memory");
}
__device__ __forceinline__ void bulk_load(uint32_t dst, const void* src, uint32_t bytes, uint32_t bar) {
    asm volatile("cp.async.bulk.shared::cluster.global.mbarrier::complete_tx::bytes [%0], [%1], %2, [%3];"
                 ::"r"(dst), "l"(src), "r"(bytes), "r"(bar) : "memory");
}
__device__ __forceinline__ void cp_async16(uint32_t dst, const void* src) {
    asm volatile("cp.async.cg.shared.global [%0], [%1], 16;" ::"r"(dst), "l"(src) : "memory");
}
__device__ __forceinline__ void bulk_load_mc(uint32_t dst, const void* src, uint32_t bytes, uint32_t bar) {
    asm volatile("cp.async.bulk.shared::cluster.global.mbarrier::complete_tx::bytes.multicast::cluster [%0], [%1], %2, [%3], %4;"
                 ::"r"(dst), "l"(src), "r"(bytes), "r"(bar), "h"((uint16_t)3) : "memory");
}
__device__ __forceinline__ void fence_async_smem() { asm volatile("fence.proxy.async.shared::cta;" ::: "memory"); }
__device__ __forceinline__ void prefetch_map(const CUtensorMap* m) {
    asm volatile("prefetch.tensormap [%0];" ::"l"(m) : "memory");
}
__device__ __forceinline__ void red_release(unsigned* p) {
    asm volatile("red.release.gpu.global.add.u32 [%0], 1;" ::"l"(p) : "memory");
}
__device__ __forceinline__ unsigned ld_relaxed(const unsigned* p) {
    unsigned v;
    asm volatile("ld.relaxed.gpu.global.u32 %0, [%1];" : "=r"(v) : "l"(p) : "memory");
    return v;
}
__device__ __forceinline__ void wait_counter(const unsigned* p, unsigned target) {
    for (uint32_t n = 0; (int)(ld_relaxed(p) - target) < 0 && n < SPIN_LIMIT; n++) __nanosleep(100);
    asm volatile("fence.acquire.gpu;" ::: "memory");
    asm volatile("fence.proxy.async.global;" ::: "memory");
}
__device__ __forceinline__ void bar_sync(int id, int n) { asm volatile("bar.sync %0, %1;" ::"r"(id), "r"(n) : "memory"); }
__device__ __forceinline__ void bar_arrive(int id, int n) { asm volatile("bar.arrive %0, %1;" ::"r"(id), "r"(n) : "memory"); }
__device__ __forceinline__ void cluster_sync() {
    asm volatile("barrier.cluster.arrive.relaxed.aligned;\nbarrier.cluster.wait.aligned;" ::: "memory");
}
__device__ __forceinline__ void wg_fence() { asm volatile("wgmma.fence.sync.aligned;" ::: "memory"); }
__device__ __forceinline__ void wg_commit() { asm volatile("wgmma.commit_group.sync.aligned;" ::: "memory"); }
template <int N> __device__ __forceinline__ void wg_wait() { asm volatile("wgmma.wait_group.sync.aligned %0;" ::"n"(N) : "memory"); }
template <int N> __device__ __forceinline__ void reg_fence(float (&a)[N]) {
#pragma unroll
    for (int i = 0; i < N; i++) asm volatile("" : "+f"(a[i])::"memory");
}
template <int N> __device__ __forceinline__ void reg_fence(uint32_t (&a)[N]) {
#pragma unroll
    for (int i = 0; i < N; i++) asm volatile("" : "+r"(a[i])::"memory");
}
__device__ __forceinline__ uint32_t pack_bf16(float lo, float hi) {
    uint32_t r;
    asm("cvt.rn.bf16x2.f32 %0, %1, %2;" : "=r"(r) : "f"(hi), "f"(lo));
    return r;
}
__device__ __forceinline__ float bf_lo(uint32_t v) { return __uint_as_float(v << 16); }
__device__ __forceinline__ float bf_hi(uint32_t v) { return __uint_as_float(v & 0xffff0000u); }
__device__ __forceinline__ float bf_round(float v) { return __bfloat162float(__float2bfloat16_rn(v)); }
__device__ __forceinline__ float ex2(float v) {
    float r;
    asm("ex2.approx.ftz.f32 %0, %1;" : "=f"(r) : "f"(v));
    return r;
}
__device__ __forceinline__ float sqrt_approx(float v) {
    float r;
    asm("sqrt.approx.ftz.f32 %0, %1;" : "=f"(r) : "f"(v));
    return r;
}
__device__ __forceinline__ float rcp_approx(float v) {
    float r;
    asm("rcp.approx.ftz.f32 %0, %1;" : "=f"(r) : "f"(v));
    return r;
}
__device__ __forceinline__ float silu_f(float v) { return v * rcp_approx(1.0f + ex2(v * -1.4426950408889634f)); }
__device__ __forceinline__ void stmatrix_x4(uint32_t addr, uint32_t r0, uint32_t r1, uint32_t r2, uint32_t r3) {
    asm volatile("stmatrix.sync.aligned.m8n8.x4.shared.b16 [%0], {%1, %2, %3, %4};"
                 ::"r"(addr), "r"(r0), "r"(r1), "r"(r2), "r"(r3) : "memory");
}
__device__ __forceinline__ void sts128(uint32_t addr, uint32_t r0, uint32_t r1, uint32_t r2, uint32_t r3) {
    asm volatile("st.shared.v4.b32 [%0], {%1, %2, %3, %4};" ::"r"(addr), "r"(r0), "r"(r1), "r"(r2), "r"(r3) : "memory");
}
__device__ __forceinline__ void lds128(uint32_t addr, uint32_t& r0, uint32_t& r1, uint32_t& r2, uint32_t& r3) {
    asm volatile("ld.shared.v4.b32 {%0, %1, %2, %3}, [%4];" : "=r"(r0), "=r"(r1), "=r"(r2), "=r"(r3) : "r"(addr) : "memory");
}
__device__ __forceinline__ uint32_t bf2_mul(uint32_t a, uint32_t b) {
    uint32_t r;
    asm("mul.rn.bf16x2 %0, %1, %2;" : "=r"(r) : "r"(a), "r"(b));
    return r;
}
__device__ __forceinline__ uint32_t bf2_add(uint32_t a, uint32_t b) {
    uint32_t r;
    asm("add.rn.bf16x2 %0, %1, %2;" : "=r"(r) : "r"(a), "r"(b));
    return r;
}
__device__ __forceinline__ uint64_t evict_first() {
    uint64_t p;
    asm("createpolicy.fractional.L2::evict_first.b64 %0, 1.0;" : "=l"(p));
    return p;
}
__device__ __forceinline__ uint64_t evict_normal() {
    uint64_t p;
    asm("createpolicy.fractional.L2::evict_normal.b64 %0, 1.0;" : "=l"(p));
    return p;
}
__device__ __forceinline__ uint4 ldg_hint(const void* p, uint64_t pol) {
    uint4 v;
    asm volatile("ld.global.cg.L2::cache_hint.v4.u32 {%0, %1, %2, %3}, [%4], %5;" : "=r"(v.x), "=r"(v.y), "=r"(v.z), "=r"(v.w) : "l"(p), "l"(pol));
    return v;
}
__device__ __forceinline__ void stg_hint(void* p, uint32_t r0, uint32_t r1, uint32_t r2, uint32_t r3, uint64_t pol) {
    asm volatile("st.global.cg.L2::cache_hint.v4.u32 [%0], {%1, %2, %3, %4}, %5;" ::"l"(p), "r"(r0), "r"(r1), "r"(r2), "r"(r3), "l"(pol) : "memory");
}

__device__ __forceinline__ uint64_t make_desc(uint32_t addr, uint32_t lbo_bytes) {
    return (uint64_t)((addr & 0x3FFFF) >> 4) | ((uint64_t)(lbo_bytes >> 4) << 16) | ((uint64_t)(1024 >> 4) << 32) | (1ull << 62);
}

__device__ __forceinline__ void wgmma_n256_ss(float (&d)[128], uint64_t da, uint64_t db, int acc) {
    asm volatile(
        "{\n.reg .pred p;\nsetp.ne.b32 p, %130, 0;\n"
        "wgmma.mma_async.sync.aligned.m64n256k16.f32.bf16.bf16 {"
        "%0, %1, %2, %3, %4, %5, %6, %7, %8, %9, %10, %11, %12, %13, %14, %15, "
        "%16, %17, %18, %19, %20, %21, %22, %23, %24, %25, %26, %27, %28, %29, %30, %31, "
        "%32, %33, %34, %35, %36, %37, %38, %39, %40, %41, %42, %43, %44, %45, %46, %47, "
        "%48, %49, %50, %51, %52, %53, %54, %55, %56, %57, %58, %59, %60, %61, %62, %63, "
        "%64, %65, %66, %67, %68, %69, %70, %71, %72, %73, %74, %75, %76, %77, %78, %79, "
        "%80, %81, %82, %83, %84, %85, %86, %87, %88, %89, %90, %91, %92, %93, %94, %95, "
        "%96, %97, %98, %99, %100, %101, %102, %103, %104, %105, %106, %107, %108, %109, %110, %111, "
        "%112, %113, %114, %115, %116, %117, %118, %119, %120, %121, %122, %123, %124, %125, %126, %127"
        "}, %128, %129, p, 1, 1, 1, 0;\n}\n"
        :
        "+f"(d[0]), "+f"(d[1]), "+f"(d[2]), "+f"(d[3]), "+f"(d[4]), "+f"(d[5]), "+f"(d[6]), "+f"(d[7]),
        "+f"(d[8]), "+f"(d[9]), "+f"(d[10]), "+f"(d[11]), "+f"(d[12]), "+f"(d[13]), "+f"(d[14]), "+f"(d[15]),
        "+f"(d[16]), "+f"(d[17]), "+f"(d[18]), "+f"(d[19]), "+f"(d[20]), "+f"(d[21]), "+f"(d[22]), "+f"(d[23]),
        "+f"(d[24]), "+f"(d[25]), "+f"(d[26]), "+f"(d[27]), "+f"(d[28]), "+f"(d[29]), "+f"(d[30]), "+f"(d[31]),
        "+f"(d[32]), "+f"(d[33]), "+f"(d[34]), "+f"(d[35]), "+f"(d[36]), "+f"(d[37]), "+f"(d[38]), "+f"(d[39]),
        "+f"(d[40]), "+f"(d[41]), "+f"(d[42]), "+f"(d[43]), "+f"(d[44]), "+f"(d[45]), "+f"(d[46]), "+f"(d[47]),
        "+f"(d[48]), "+f"(d[49]), "+f"(d[50]), "+f"(d[51]), "+f"(d[52]), "+f"(d[53]), "+f"(d[54]), "+f"(d[55]),
        "+f"(d[56]), "+f"(d[57]), "+f"(d[58]), "+f"(d[59]), "+f"(d[60]), "+f"(d[61]), "+f"(d[62]), "+f"(d[63]),
        "+f"(d[64]), "+f"(d[65]), "+f"(d[66]), "+f"(d[67]), "+f"(d[68]), "+f"(d[69]), "+f"(d[70]), "+f"(d[71]),
        "+f"(d[72]), "+f"(d[73]), "+f"(d[74]), "+f"(d[75]), "+f"(d[76]), "+f"(d[77]), "+f"(d[78]), "+f"(d[79]),
        "+f"(d[80]), "+f"(d[81]), "+f"(d[82]), "+f"(d[83]), "+f"(d[84]), "+f"(d[85]), "+f"(d[86]), "+f"(d[87]),
        "+f"(d[88]), "+f"(d[89]), "+f"(d[90]), "+f"(d[91]), "+f"(d[92]), "+f"(d[93]), "+f"(d[94]), "+f"(d[95]),
        "+f"(d[96]), "+f"(d[97]), "+f"(d[98]), "+f"(d[99]), "+f"(d[100]), "+f"(d[101]), "+f"(d[102]), "+f"(d[103]),
        "+f"(d[104]), "+f"(d[105]), "+f"(d[106]), "+f"(d[107]), "+f"(d[108]), "+f"(d[109]), "+f"(d[110]), "+f"(d[111]),
        "+f"(d[112]), "+f"(d[113]), "+f"(d[114]), "+f"(d[115]), "+f"(d[116]), "+f"(d[117]), "+f"(d[118]), "+f"(d[119]),
        "+f"(d[120]), "+f"(d[121]), "+f"(d[122]), "+f"(d[123]), "+f"(d[124]), "+f"(d[125]), "+f"(d[126]), "+f"(d[127])
        : "l"(da), "l"(db), "r"(acc));
}

__device__ __forceinline__ void wgmma_n64_rs_tb(float* d, uint32_t a0, uint32_t a1, uint32_t a2, uint32_t a3, uint32_t db, int acc) {
    asm volatile(
        "{\n.reg .pred p;\n.reg .b64 db;\nsetp.ne.b32 p, %37, 0;\nmov.b64 db, {%36, 0x40000040};\n"
        "wgmma.mma_async.sync.aligned.m64n64k16.f32.bf16.bf16 {"
        "%0, %1, %2, %3, %4, %5, %6, %7, %8, %9, %10, %11, %12, %13, %14, %15, "
        "%16, %17, %18, %19, %20, %21, %22, %23, %24, %25, %26, %27, %28, %29, %30, %31"
        "}, {%32, %33, %34, %35}, db, p, 1, 1, 1;\n}\n"
        :
        "+f"(d[0]), "+f"(d[1]), "+f"(d[2]), "+f"(d[3]), "+f"(d[4]), "+f"(d[5]), "+f"(d[6]), "+f"(d[7]),
        "+f"(d[8]), "+f"(d[9]), "+f"(d[10]), "+f"(d[11]), "+f"(d[12]), "+f"(d[13]), "+f"(d[14]), "+f"(d[15]),
        "+f"(d[16]), "+f"(d[17]), "+f"(d[18]), "+f"(d[19]), "+f"(d[20]), "+f"(d[21]), "+f"(d[22]), "+f"(d[23]),
        "+f"(d[24]), "+f"(d[25]), "+f"(d[26]), "+f"(d[27]), "+f"(d[28]), "+f"(d[29]), "+f"(d[30]), "+f"(d[31])
        : "r"(a0), "r"(a1), "r"(a2), "r"(a3), "r"(db), "r"(acc));
}

template <int TB>
__device__ __forceinline__ void wgmma_n128_rs(float (&d)[64], uint32_t a0, uint32_t a1, uint32_t a2, uint32_t a3, uint32_t db, int acc) {
    asm volatile(
        "{\n.reg .pred p;\n.reg .b64 db;\nsetp.ne.b32 p, %69, 0;\nmov.b64 db, {%68, 0x40000040};\n"
        "wgmma.mma_async.sync.aligned.m64n128k16.f32.bf16.bf16 {"
        "%0, %1, %2, %3, %4, %5, %6, %7, %8, %9, %10, %11, %12, %13, %14, %15, "
        "%16, %17, %18, %19, %20, %21, %22, %23, %24, %25, %26, %27, %28, %29, %30, %31, "
        "%32, %33, %34, %35, %36, %37, %38, %39, %40, %41, %42, %43, %44, %45, %46, %47, "
        "%48, %49, %50, %51, %52, %53, %54, %55, %56, %57, %58, %59, %60, %61, %62, %63"
        "}, {%64, %65, %66, %67}, db, p, 1, 1, %70;\n}\n"
        :
        "+f"(d[0]), "+f"(d[1]), "+f"(d[2]), "+f"(d[3]), "+f"(d[4]), "+f"(d[5]), "+f"(d[6]), "+f"(d[7]),
        "+f"(d[8]), "+f"(d[9]), "+f"(d[10]), "+f"(d[11]), "+f"(d[12]), "+f"(d[13]), "+f"(d[14]), "+f"(d[15]),
        "+f"(d[16]), "+f"(d[17]), "+f"(d[18]), "+f"(d[19]), "+f"(d[20]), "+f"(d[21]), "+f"(d[22]), "+f"(d[23]),
        "+f"(d[24]), "+f"(d[25]), "+f"(d[26]), "+f"(d[27]), "+f"(d[28]), "+f"(d[29]), "+f"(d[30]), "+f"(d[31]),
        "+f"(d[32]), "+f"(d[33]), "+f"(d[34]), "+f"(d[35]), "+f"(d[36]), "+f"(d[37]), "+f"(d[38]), "+f"(d[39]),
        "+f"(d[40]), "+f"(d[41]), "+f"(d[42]), "+f"(d[43]), "+f"(d[44]), "+f"(d[45]), "+f"(d[46]), "+f"(d[47]),
        "+f"(d[48]), "+f"(d[49]), "+f"(d[50]), "+f"(d[51]), "+f"(d[52]), "+f"(d[53]), "+f"(d[54]), "+f"(d[55]),
        "+f"(d[56]), "+f"(d[57]), "+f"(d[58]), "+f"(d[59]), "+f"(d[60]), "+f"(d[61]), "+f"(d[62]), "+f"(d[63])
        : "r"(a0), "r"(a1), "r"(a2), "r"(a3), "r"(db), "r"(acc), "n"(TB));
}

__device__ __forceinline__ void wgmma_n128_ss(float* d, uint64_t da, uint64_t db, int acc) {
    asm volatile(
        "{\n.reg .pred p;\nsetp.ne.b32 p, %66, 0;\n"
        "wgmma.mma_async.sync.aligned.m64n128k16.f32.bf16.bf16 {"
        "%0, %1, %2, %3, %4, %5, %6, %7, %8, %9, %10, %11, %12, %13, %14, %15, "
        "%16, %17, %18, %19, %20, %21, %22, %23, %24, %25, %26, %27, %28, %29, %30, %31, "
        "%32, %33, %34, %35, %36, %37, %38, %39, %40, %41, %42, %43, %44, %45, %46, %47, "
        "%48, %49, %50, %51, %52, %53, %54, %55, %56, %57, %58, %59, %60, %61, %62, %63"
        "}, %64, %65, p, 1, 1, 0, 1;\n}\n"
        :
        "+f"(d[0]), "+f"(d[1]), "+f"(d[2]), "+f"(d[3]), "+f"(d[4]), "+f"(d[5]), "+f"(d[6]), "+f"(d[7]),
        "+f"(d[8]), "+f"(d[9]), "+f"(d[10]), "+f"(d[11]), "+f"(d[12]), "+f"(d[13]), "+f"(d[14]), "+f"(d[15]),
        "+f"(d[16]), "+f"(d[17]), "+f"(d[18]), "+f"(d[19]), "+f"(d[20]), "+f"(d[21]), "+f"(d[22]), "+f"(d[23]),
        "+f"(d[24]), "+f"(d[25]), "+f"(d[26]), "+f"(d[27]), "+f"(d[28]), "+f"(d[29]), "+f"(d[30]), "+f"(d[31]),
        "+f"(d[32]), "+f"(d[33]), "+f"(d[34]), "+f"(d[35]), "+f"(d[36]), "+f"(d[37]), "+f"(d[38]), "+f"(d[39]),
        "+f"(d[40]), "+f"(d[41]), "+f"(d[42]), "+f"(d[43]), "+f"(d[44]), "+f"(d[45]), "+f"(d[46]), "+f"(d[47]),
        "+f"(d[48]), "+f"(d[49]), "+f"(d[50]), "+f"(d[51]), "+f"(d[52]), "+f"(d[53]), "+f"(d[54]), "+f"(d[55]),
        "+f"(d[56]), "+f"(d[57]), "+f"(d[58]), "+f"(d[59]), "+f"(d[60]), "+f"(d[61]), "+f"(d[62]), "+f"(d[63])
        : "l"(da), "l"(db), "r"(acc));
}

__device__ __forceinline__ void wgmma_n8_ta(float* d, uint64_t da, uint64_t db) {
    asm volatile("wgmma.mma_async.sync.aligned.m64n8k16.f32.bf16.bf16 {%0, %1, %2, %3}, %4, %5, 1, 1, 1, 1, 0;\n"
                 : "+f"(d[0]), "+f"(d[1]), "+f"(d[2]), "+f"(d[3]) : "l"(da), "l"(db));
}

#define PROF(slot, role)
#undef PROF_GT
#define PROF_GT(slot)

struct Params {
    const __nv_bfloat16* x;
    const __nv_bfloat16* w_r;
    const uint8_t *c_kv, *w_uk, *w_uv;
    uint8_t* out;
};
__device__ __forceinline__ void lsu_prefetch(const void* p) { asm volatile("prefetch.global.L2 [%0];" ::"l"(p) : "memory"); }

template <typename T>
__device__ __forceinline__ T* ptr_off(T* base, uint32_t off) {
    uint32_t lo, hi;
    asm("mov.b64 {%0, %1}, %2;" : "=r"(lo), "=r"(hi) : "l"(base));
    asm("add.cc.u32 %0, %0, %2;\naddc.u32 %1, %1, 0;" : "+r"(lo), "+r"(hi) : "r"(off));
    T* r;
    asm("mov.b64 %0, {%1, %2};" : "=l"(r) : "r"(lo), "r"(hi));
    return r;
}
__device__ __forceinline__ int kv_head(int pair) { return pair & 7; }
__device__ __forceinline__ int kv_tokens(int pair) { return ((pair >> 3) & 1) * 4 + (pair >> 4); }
__device__ __forceinline__ int out_rows(int pair) { return pair & 7; }
__device__ __forceinline__ int out_cols(int pair) { return (pair >> 4) * 4 + ((pair >> 3) & 1) * 2; }
__device__ __forceinline__ int attn_rowblock(int pair, int seg) {
    int j = pair & 3, hl = pair >> 2;
    return (((hl & 1) | (j == 0)) ^ seg) ? j : 7 - j;
}
__device__ __forceinline__ int outproj_head(int i, int ib) {
    if (i < 16) return i;
    return 16 + 2 * (i & 7) + ((ib < 4) ^ ((i >> 3) & 1));
}

__device__ __forceinline__ void pin_value(uint32_t& v) { asm volatile("" : "+r"(v)); }
__device__ __forceinline__ void pin_value(int& v) { asm volatile("" : "+r"(v)); }
__device__ __forceinline__ void pin_value(const uint8_t*& v) { asm volatile("" : "+l"(v)); }

__device__ __forceinline__ void producer(const Params& P, uint32_t sb, int pair, int c,
                                         const CUtensorMap* m_ckv, const CUtensorMap* m_wu,
                                         const CUtensorMap* m_wq, const CUtensorMap* m_wo) {
    const int hl = pair >> 2;
    const int ibA = attn_rowblock(pair, 0), nA = 2 * ibA + 2;
    const int ib = out_rows(pair), mi = 2 * ib + c, nb = out_cols(pair);
    const bool leader = elect_one();
    uint32_t g = 4, tail = 0;
    if (leader) prefetch_map(m_wq);
    auto wait_released = [&](uint32_t need) {
#pragma unroll 1
        for (; tail <= need; tail++) mbar_wait(sb + BAR_EMPTY + (tail & 7) * 8, (tail >> 3) & 1);
    };
    auto wait_released_here = [&](uint32_t need) {
#pragma unroll 1
        for (; tail < need; tail++) mbar_wait(sb + BAR_EMPTY + (tail & 7) * 8, (tail >> 3) & 1);
        if (tail == need) mbar_wait(sb + BAR_EMPTYL + (need & 7) * 8, (need >> 3) & 1);
    };
    auto wait_released_peer = [&](uint32_t need) {
        if (tail == need) {
            uint32_t eb = sb + BAR_EMPTY + (need & 7) * 8, ep = (need >> 3) & 1;
            tail++;
            mbar_wait(eb, ep);
        }
    };
    auto full_bar = [&]() { return sb + BAR_FULL + (g & 7) * 8; };
    auto pin = [](auto&... v) { (pin_value(v), ...); };
#pragma unroll 1
    for (int rnd = 0; rnd < 2; rnd++) {
#pragma unroll 1
        for (int i = rnd ? 0 : 4; i < 16; i++) {
            int kb = i & 7, h2 = (kv_head(pair) + (i & 8) + rnd * 16) * 2, krow = kb * 64;
            uint32_t pg = sb + (i & 3) * (3 * PAGE), pb = pg + (1 + c) * PAGE, bar = full_bar();
            pin(kb, h2, krow, pg, pb, bar);
            const uint32_t need = g - 4 - (i < 2);
            wait_released_here(need);
            if (leader) {
                mbar_expect_tx(bar, 3 * PAGE);
                tma_3d(pg, m_wu, 0, krow, h2, bar);
            }
            wait_released_peer(need);
            if (leader) {
                tma_3d_mc(pb, m_ckv, 0, kv_tokens(pair) * 256 + c * 128, kb, bar);
                if (rnd == 1 && i == 3) asm volatile("red.relaxed.gpu.global.add.u32 [%0], 1;" ::"l"(ptr_off(g_sync.kvfree, hl * 32)) : "memory");
            }
            g++;
        }
        mbar_sleep(sb + BAR_DEP, 0);
        const uint8_t* xa = ptr_off(g_xn, ibA * (16 * 32768) + c * PAGE);
        const uint8_t* xb = ptr_off(g_xn, (7 - ibA) * (16 * 32768) + (1 - c) * PAGE);
#pragma unroll 1
        for (int kb = 0; kb < DM / 64; kb++) {
            uint32_t pg = sb + (kb & 3) * (3 * PAGE), pw = pg + 2 * PAGE + c * 8192, bar = full_bar(), p2 = pg + PAGE;
            int krow = kb * 64;
            pin(pg, pw, p2, bar, krow);
            wait_released_here(g - 4);
            if (leader) {
                mbar_expect_tx(bar, 3 * PAGE);
                bulk_load(pg, xa, PAGE, bar);
            }
            wait_released_peer(g - 4);
            if (leader) {
                tma_3d_mc(pw, m_wq, 0, krow, (rnd * 16 + hl) * 2 + c, bar);
                bulk_load(p2, xb, PAGE, bar);
            }
            g++;
            xa += 32768;
            xb += 32768;
        }
        mbar_sleep(sb + BAR_DEP + 8 + rnd * 16, 0);
        if (rnd == 1 && leader) prefetch_map(m_wo);
        uint32_t pg = sb + c * PAGE;
#pragma unroll 1
        for (int j = 0; j < 36; j++) {
            const bool isk = j == 0 || ((j & 1) && j != 35);
            const int t = isk ? (j + 1) >> 1 : (j - 1) >> 1;
            const uint8_t* src = ptr_off(g_kv, (hl * 16 + (t >= nA ? t - nA : t)) * 65536 + (isk ? 0 : 32768) + c * PAGE);
            uint32_t bar = full_bar(), need = g - 6 + (j < 2) + (j < 5);
            pin(src, bar, need);
            wait_released(need);
            if (leader) {
                mbar_expect_tx(bar, 2 * PAGE);
                bulk_load_mc(pg, src, PAGE, bar);
            }
            g++;
            if (rnd == 0 && j >= 22 && j < 34) {
                const int cta = pair * 2 + c, i = j - 22;
                const uint32_t l = (threadIdx.x & 31) * 128;
                if (i < 8) lsu_prefetch(ptr_off(i & 1 ? P.w_uv : P.w_uk, cta * 32768 + (i >> 1) * 8192 + 4096 + l));
                else lsu_prefetch(ptr_off(P.c_kv, cta * 16384 + (i - 8) * 4096 + l));
            }
            pg = pg >= sb + SM_REGION - 2 * PAGE ? pg - (SM_REGION - 2 * PAGE) : pg + 2 * PAGE;
        }
    }
    uint32_t pg = sb;
#pragma unroll 1
    for (int i = 0; i < 64; i++) {
        if ((i & 15) == 0 && i != 16) mbar_sleep(sb + BAR_DEP + 32 + (i >> 1) - (i ? 8 : 0), 0);
        const int kb = outproj_head(i >> 1, ib) * 2 + (i & 1);
        const uint8_t* src = ptr_off(g_ctx, (mi * 64 + kb) * PAGE);
        uint32_t bar = full_bar(), pw = pg + PAGE + c * 8192;
        int krow = kb * 64;
        pin(src, bar, pw, krow);
        wait_released_here(g - 6);
        if (leader) {
            mbar_expect_tx(bar, 2 * PAGE);
            bulk_load(pg, src, PAGE, bar);
        }
        wait_released_peer(g - 6);
        if (leader) tma_3d_mc(pw, m_wo, 0, krow, nb + c, bar);
        g++;
        pg = pg == sb + SM_REGION - 2 * PAGE ? sb : pg + 2 * PAGE;
    }
}

__device__ __forceinline__ uint32_t xn_block(int row64, int kb) {
    return (((row64 >> 2) * 16 + kb) * 4 + ((row64 & 1) * 2 + (((row64 >> 1) & 1) ^ 1))) * 8192;
}
__device__ __forceinline__ uint32_t image_offset(int row, int ch) {
    return xn_block(row >> 6, ch >> 3) + (row & 63) * 128 + (((ch & 7) ^ (row & 7)) << 4);
}
__device__ __forceinline__ uint32_t bf2_sub(uint32_t a, uint32_t b) {
    uint32_t r;
    asm("sub.rn.bf16x2 %0, %1, %2;" : "=r"(r) : "r"(a), "r"(b));
    return r;
}
__device__ __forceinline__ uint32_t bf2_fma(uint32_t a, uint32_t b, uint32_t c) {
    uint32_t r;
    asm("fma.rn.bf16x2 %0, %1, %2, %3;" : "=r"(r) : "r"(a), "r"(b), "r"(c));
    return r;
}
template <int N0, int N>
__device__ __forceinline__ void ln_sums(const uint32_t (&u)[N], float& sum, float& sq) {
    float s0 = 0.f, s1 = 0.f, q0 = 0.f, q1 = 0.f;
#pragma unroll
    for (int k = N0; k < N0 + 16; k++) {
        const float a = bf_lo(u[k]), b = bf_hi(u[k]);
        s0 += a; s1 += b;
        q0 = fmaf(a, a, q0); q1 = fmaf(b, b, q1);
    }
    sum = s0 + s1;
    sq = q0 + q1;
}
__device__ __forceinline__ void ln_finish(float sum, float sq, uint32_t& mean2, uint32_t& rhi2, uint32_t& rlo2) {
    const float ms = sum * (1.0f / DM);
    const float var = fmaxf(fmaf(-ms, ms, sq * (1.0f / DM)), 0.f);
    const float rden = rcp_approx(bf_round(sqrt_approx(bf_round(bf_round(var) + 1e-5f))));
    const float rhi = bf_round(rden);
    mean2 = pack_bf16(ms, ms);
    rhi2 = pack_bf16(rhi, rhi);
    rlo2 = pack_bf16(rden - rhi, rden - rhi);
}
template <int N0, int N>
__device__ __forceinline__ void ln_apply(uint32_t (&u)[N], uint32_t mean2, uint32_t rhi2, uint32_t rlo2, uint8_t* dst) {
#pragma unroll
    for (int i = 0; i < 4; i++) {
        uint32_t o[4];
#pragma unroll
        for (int k = 0; k < 4; k++) {
            const uint32_t d = bf2_sub(u[N0 + 4 * i + k], mean2);
            o[k] = bf2_fma(d, rhi2, bf2_mul(d, rlo2));
        }
#pragma unroll
        for (int k = 0; k < 4; k++) u[N0 + 4 * i + k] = o[k];
        __stcg(reinterpret_cast<uint4*>(dst + i * 131072), make_uint4(o[0], o[1], o[2], o[3]));
    }
}
__device__ __forceinline__ int query_rowblock(int pair, int c, int w, int seg) {
    const int qA = (w ? 0 : 2) + c;
    return 4 * attn_rowblock(pair, seg) + (seg ? 3 - qA : qA);
}

__device__ __noinline__ void fetch_helper(const uint8_t* w_u, uint32_t sb, int w, int lane, int pair, int c) {
    const uint32_t page = sb + SM_REGION + w * PAGE + lane * 16;
    mbar_sleep(sb + BAR_FULL + 5 * 8, 0);
#pragma unroll 1
    for (int i = 0; i < 2; i++) {
        lsu_prefetch(ptr_off(w_u, ((pair * 2 + c) * 4 + i * 2 + (lane >> 4)) * 8192 + 2048 + (lane & 15) * 128));
        __nanosleep(300);
    }
    const unsigned e1 = __ldcg(&g_sync.done) / NCTA + 1;
#pragma unroll 1
    for (int e = 1; e <= 7; e += 2) mbar_sleep(sb + BAR_DONE + 8, (e >> 1) & 1);
    const int rb = out_rows(pair) * 4 + c * 2 + w, kb0 = out_cols(pair);
    const uint8_t* src = ptr_off(g_xn, xn_block(rb, kb0) + lane * 16);
#pragma unroll 1
    for (int i = 0; i < 32; i += 4) {
#pragma unroll
        for (int k = 0; k < 4; k++) cp_async16(page + (i + k) * 512, src + (i + k) * 512 + (i >> 4) * (32768 - 8192));
        __nanosleep(200);
    }
    wait_counter(&g_sync.ffn_done, e1);
    const int r = __ldcg(ptr_off(g_sel, (lane >> 4) * 4)) - rb * 64, ch = lane & 15;
    const uint4 t = __ldcg(ptr_off(g_routed, ((lane >> 4) * 128 + kb0 * 8 + ch) * 16));
    asm volatile("cp.async.wait_all;" ::: "memory");
    __syncwarp();
    if (r >= 0 && r < 64)
        sts128(sb + SM_REGION + w * PAGE + (ch >> 3) * 8192 + r * 128 + (((ch & 7) ^ (r & 7)) << 4), t.x, t.y, t.z, t.w);
    __syncwarp();
    if (lane == 0) mbar_arrive(sb + BAR_G + w * 8);
    PROF(20, 2);
}

__device__ __noinline__ void sync_helper(uint32_t sb, int lane, int pair, int c) {
    const unsigned e1 = __ldcg(&g_sync.done) / NCTA + 1;
    const int ib = out_rows(pair);
    int e = 0, b = 0;
#pragma unroll 1
    for (uint32_t n = 0; (e < 9 || b < 7) && n < SPIN_LIMIT; n++) {
        if (e < 9 && __all_sync(~0u, mbar_test(sb + BAR_DONE + (e & 1) * 8, (e >> 1) & 1))) {
            const int rnd = e > 4, ev = (e - 1) & 3;
            unsigned* flag = e == 0 ? &g_sync.ln
                           : ev < 2 ? ptr_off(g_sync.kv, (rnd * 16 + kv_head(pair) + 8 * ev) * 32)
                                    : ptr_off(g_sync.ctx, (query_rowblock(pair, c, lane & 1, ev & 1) * NH + rnd * 16 + (pair >> 2)) * 4);
            asm volatile("fence.proxy.async.global;\nfence.release.gpu;" ::: "memory");
            if (lane < ((e == 0 || ev < 2) ? 1 : 2)) asm volatile("red.relaxed.gpu.global.add.u32 [%0], 1;" ::"l"(flag) : "memory");
            PROF(10 + e, 2);
            e++;
        }
        if (b < 7 && e > 0 && (b < 4 || (n & POLL_MASK) == 0)) {
            const int i = b == 4 ? lane >> 1 : 8 * b - 24 + ((lane >> 1) & 7);
            const unsigned* cnt = b == 0 ? &g_sync.ln
                                : b == 2 ? ptr_off(g_sync.kvfree, (kv_head(pair) + 8 * (lane & 1)) * 32)
                                : b < 4 ? ptr_off(g_sync.kv, ((b >> 1) * 16 + (pair >> 2)) * 32)
                                        : ptr_off(g_sync.ctx, ((4 * ib + 2 * c + (lane & 1)) * NH + outproj_head(i & 31, ib)) * 4);
            if (__all_sync(~0u, (int)(ld_relaxed(cnt) - e1 * (b == 0 ? NMAIN : b == 2 ? 8 : b < 4 ? 16 : 1)) >= 0)) {
                asm volatile("fence.acquire.gpu;\nfence.proxy.async.global;" ::: "memory");
                __syncwarp();
                if (lane == 0) mbar_arrive(sb + BAR_DEP + b * 8);
                PROF(1 + b, 2);
                b++;
            }
        }
        __nanosleep(150);
    }
}

__device__ __forceinline__ unsigned long long block_max_key(unsigned long long k, unsigned long long* red, int tid) {
#pragma unroll
    for (int o = 16; o; o >>= 1) {
        unsigned long long t = __shfl_xor_sync(~0u, k, o);
        k = t > k ? t : k;
    }
    bar_sync(1, 256);
    if ((tid & 31) == 0) red[tid >> 5] = k;
    bar_sync(1, 256);
    k = red[0];
#pragma unroll
    for (int i = 1; i < 8; i++) k = red[i] > k ? red[i] : k;
    return k;
}

constexpr int FS = FF / 4;
constexpr int FSTAGE = 32768, FNST = 6;
constexpr int FN1 = 2 * (DM / 16), FN2 = FS / 16;

__device__ __forceinline__ void ffn_producer(uint32_t sb, int s, const CUtensorMap* m_gate, const CUtensorMap* m_up,
                                             const CUtensorMap* m_down) {
    wait_counter(&g_sync.ln, (__ldcg(&g_sync.done) / NCTA + 1) * NMAIN);
    int slot = 0, ph = 1;
#pragma unroll 1
    for (int st = 0; st < FN1 + FN2; st++) {
        mbar_sleep(sb + BAR_EMPTY + slot * 8, ph);
        const uint32_t bar = sb + BAR_FULL + slot * 8;
        const bool up = st < FN1;
        mbar_expect_tx(bar, up ? FS * 32 : DM * 32);
        tma_3d_hint(sb + slot * FSTAGE, up ? ((st & 1) ? m_up : m_gate) : m_down, 0,
                    up ? (st >> 1) * 16 : s * FS + (st - FN1) * 16, up ? s * (FS / 64) : 0, bar, evict_first());
        if (++slot == FNST) { slot = 0; ph ^= 1; }
    }
}

__device__ __forceinline__ void ffn_cta(uint8_t* smem, uint32_t sb, int s, unsigned epoch, const __nv_bfloat16* w_r) {
    const int tid = threadIdx.x, lane = tid & 31;
    const int warp = __shfl_sync(~0u, tid >> 5, 0), w = warp >> 2;
    constexpr uint32_t XB = FNST * FSTAGE, HB = XB + 16384, AUX = HB + 14336;
    unsigned long long* red = reinterpret_cast<unsigned long long*>(smem + AUX);
    unsigned* flag = reinterpret_cast<unsigned*>(smem + AUX + 128);
    const unsigned e1 = epoch + 1;
    for (int i = tid; i < (16384 + 14336) / 16; i += 256) reinterpret_cast<uint4*>(smem + XB)[i] = make_uint4(0, 0, 0, 0);
    {
        float wf[32];
#pragma unroll
        for (int i = 0; i < 4; i++) {
            const uint4 t = __ldg(reinterpret_cast<const uint4*>(w_r) + lane + 32 * i);
            const uint32_t tu[4] = {t.x, t.y, t.z, t.w};
#pragma unroll
            for (int k = 0; k < 4; k++) { wf[8 * i + 2 * k] = bf_lo(tu[k]); wf[8 * i + 2 * k + 1] = bf_hi(tu[k]); }
        }
        if (tid == 0) wait_counter(&g_sync.ln, e1 * NMAIN);
        bar_sync(1, 256);
#pragma unroll 1
        for (int r0 = s * (SEQ / 4) + warp * (SEQ / 32); r0 < s * (SEQ / 4) + (warp + 1) * (SEQ / 32); r0 += 4) {
            uint4 t[4][4];
#pragma unroll
            for (int r = 0; r < 4; r++)
#pragma unroll
                for (int i = 0; i < 4; i++) t[r][i] = __ldcg(reinterpret_cast<const uint4*>(g_xn + image_offset(r0 + r, lane) + i * 131072));
            float acc[4];
#pragma unroll
            for (int r = 0; r < 4; r++) {
                float a = 0.f, b = 0.f;
#pragma unroll
                for (int i = 0; i < 4; i++) {
                    const uint32_t tu[4] = {t[r][i].x, t[r][i].y, t[r][i].z, t[r][i].w};
#pragma unroll
                    for (int k = 0; k < 4; k++) {
                        a = fmaf(bf_lo(tu[k]), wf[8 * i + 2 * k], a);
                        b = fmaf(bf_hi(tu[k]), wf[8 * i + 2 * k + 1], b);
                    }
                }
                acc[r] = a + b;
            }
#pragma unroll
            for (int o = 16; o; o >>= 1)
#pragma unroll
                for (int r = 0; r < 4; r++) acc[r] += __shfl_xor_sync(~0u, acc[r], o);
            if (lane < 4) __stcg(&g_r[r0 + lane], bf_round(lane == 0 ? acc[0] : lane == 1 ? acc[1] : lane == 2 ? acc[2] : acc[3]));
        }
        __threadfence();
        bar_sync(1, 256);
        if (tid == 0) {
            red_release(&g_sync.router);
            wait_counter(&g_sync.router, e1 * 4);
        }
        bar_sync(1, 256);
    }
    unsigned long long keys[8];
    unsigned long long best = 0;
#pragma unroll
    for (int i = 0; i < 8; i++) {
        int idx = tid + 256 * i;
        uint32_t b = __float_as_uint(__ldcg(&g_r[idx]) + 0.0f);
        b = (b & 0x80000000u) ? ~b : (b | 0x80000000u);
        keys[i] = ((unsigned long long)b << 32) | (unsigned)(SEQ - 1 - idx);
        best = keys[i] > best ? keys[i] : best;
    }
    const unsigned long long k0 = block_max_key(best, red, tid);
    best = 0;
#pragma unroll
    for (int i = 0; i < 8; i++) best = (keys[i] != k0 && keys[i] > best) ? keys[i] : best;
    const unsigned long long k1 = block_max_key(best, red, tid);
    const int row = SEQ - 1 - (int)((w ? k1 : k0) & 0xffffffffu);
    const int ch = tid & 127;
    const uint4 xrow = __ldcg(reinterpret_cast<const uint4*>(g_xn + image_offset(row, ch)));
    *reinterpret_cast<uint4*>(smem + XB + (ch >> 3) * 1024 + w * 128 + (((ch & 7) ^ w) << 4)) = xrow;
    fence_async_smem();
    bar_sync(1, 256);
    PROF(20, tid >> 7);
    int slot = 0, ph = 0, prev = 0;
    auto next_stage = [&](bool has_prev) {
        wg_commit();
        wg_wait<1>();
        if (has_prev && lane < 2) mbar_arrive(sb + BAR_EMPTY + prev * 8);
        prev = slot;
        if (++slot == FNST) { slot = 0; ph ^= 1; }
    };
    {
        float ag[28], au[28];
#pragma unroll
        for (int i = 0; i < 28; i++) ag[i] = au[i] = 0.f;
#pragma unroll 1
        for (int ks = 0; ks < DM / 16; ks++) {
            const uint64_t db = make_desc(sb + XB + (ks >> 2) * 1024 + (ks & 3) * 32, 16);
            mbar_wait(sb + BAR_FULL + slot * 8, ph);
            uint64_t da = make_desc(sb + slot * FSTAGE + w * (7 * 2048), 16);
            wg_fence();
#pragma unroll
            for (int b = 0; b < 7; b++) wgmma_n8_ta(ag + 4 * b, da + b * 128, db);
            next_stage(ks > 0);
            mbar_wait(sb + BAR_FULL + slot * 8, ph);
            da = make_desc(sb + slot * FSTAGE + w * (7 * 2048), 16);
            wg_fence();
#pragma unroll
            for (int b = 0; b < 7; b++) wgmma_n8_ta(au + 4 * b, da + b * 128, db);
            next_stage(true);
        }
        wg_wait<0>();
        reg_fence(ag);
        reg_fence(au);
        if ((lane & 3) == 0) {
#pragma unroll
            for (int i = 0; i < 28; i++) {
                const int f = (warp & 3) * 16 + (lane >> 2) + (i & 2) * 4, tok = i & 1;
                const float h = bf_round(silu_f(bf_round(ag[i]))) * bf_round(au[i]);
                *reinterpret_cast<__nv_bfloat16*>(smem + HB + (w * 7 + (i >> 2)) * 1024 + tok * 128 + (((f >> 3) ^ tok) << 4) + (f & 7) * 2) =
                    __float2bfloat16_rn(h);
            }
        }
    }
    fence_async_smem();
    bar_sync(1, 256);
    PROF(21, tid >> 7);
    {
        float ay[32];
#pragma unroll
        for (int i = 0; i < 32; i++) ay[i] = 0.f;
#pragma unroll 1
        for (int ks = 0; ks < FN2; ks++) {
            const uint64_t db = make_desc(sb + HB + (ks >> 2) * 1024 + (ks & 3) * 32, 16);
            mbar_wait(sb + BAR_FULL + slot * 8, ph);
            const uint64_t da = make_desc(sb + slot * FSTAGE + w * (8 * 2048), 16);
            wg_fence();
#pragma unroll
            for (int b = 0; b < 8; b++) wgmma_n8_ta(ay + 4 * b, da + b * 128, db);
            next_stage(true);
        }
        wg_wait<0>();
        reg_fence(ay);
        if ((lane & 3) == 0) {
#pragma unroll
            for (int i = 0; i < 32; i++)
                g_ypart[(s * 2 + (i & 1)) * DM + (w * 8 + (i >> 2)) * 64 + (warp & 3) * 16 + (lane >> 2) + (i & 2) * 4] = ay[i];
        }
    }
    PROF(23, tid >> 7);
    __threadfence();
    bar_sync(1, 256);
    if (tid == 0) {
        *flag = atomicAdd(&g_sync.ffn_ticket, 1u) == epoch * 4 + 3;
        __threadfence();
    }
    bar_sync(1, 256);
    if (*flag) {
        const float sg = bf_round(__fdividef(1.0f, 1.0f + __expf(-__ldcg(&g_r[row]))));
        const uint32_t xu[4] = {xrow.x, xrow.y, xrow.z, xrow.w};
        uint32_t o[4];
#pragma unroll
        for (int k = 0; k < 4; k++) {
            float y0 = 0.f, y1 = 0.f;
#pragma unroll
            for (int q = 0; q < 4; q++) {
                const float2 y = __ldcg(reinterpret_cast<const float2*>(&g_ypart[(q * 2 + w) * DM + ch * 8 + 2 * k]));
                y0 += y.x; y1 += y.y;
            }
            o[k] = pack_bf16(bf_lo(xu[k]) + bf_round(bf_round(y0) * sg), bf_hi(xu[k]) + bf_round(bf_round(y1) * sg));
        }
        g_routed[w * 128 + ch] = make_uint4(o[0], o[1], o[2], o[3]);
        if (ch == 0) g_sel[w] = row;
        bar_sync(1, 256);
        if (tid == 0) red_release(&g_sync.ffn_done);
    }
}

__device__ __forceinline__ uint32_t slab_addr(uint32_t stg, int lane, int s) {
    const int row = ((lane >> 3) & 1) * 8 + (lane & 7);
    const int chunk = 2 * (s & 3) + (lane >> 4);
    return stg + row * 128 + (s >> 2) * 8192 + ((chunk ^ (lane & 7)) << 4);
}

constexpr float SM_SCALE = 0.08838834764831845f * 1.4426950408889634f;
constexpr float SUM_HI = 1048576.f, SUM_LO = 1.0f / 1048576.f;

template <int I0, int I1, int J0>
__device__ __forceinline__ void mask_range(float (&S)[64], float limf) {
#pragma unroll
    for (int i = I0; i < I1; i++) {
        const int j = i >> 2;
        float t;
        asm("add.sat.f32 %0, %1, %2;" : "=f"(t) : "f"((float)(32 * (j >> 2) + 2 * (j & 3) + (i & 1) - (i & 2) * 4)), "f"(-limf));
        S[4 * J0 + i] = fmaf(t, -1e30f, S[4 * J0 + i]);
    }
}
template <int J0>
__device__ __forceinline__ void mask_half(float (&S)[64], float limf, int v) {
    asm volatile("" : "+f"(limf));
    if (v < 2) {
        mask_range<0, 16, J0>(S, limf);
#pragma unroll
        for (int i = 16; i < 32; i++) S[4 * J0 + i] = -1e30f;
    } else {
        mask_range<16, 32, J0>(S, limf);
    }
}
__device__ __forceinline__ void issue_qk(float (&S)[64], const uint32_t (&Q)[32], uint32_t d0) {
#pragma unroll
    for (int s = 0; s < 8; s++)
        wgmma_n128_rs<1>(S, Q[4 * s], Q[4 * s + 1], Q[4 * s + 2], Q[4 * s + 3], d0 + s * 128, s > 0);
}
__device__ __forceinline__ void issue_qk_half(float (&T)[32], const uint32_t (&Q)[32], uint32_t d0) {
#pragma unroll
    for (int s = 0; s < 8; s++) wgmma_n64_rs_tb(T, Q[4 * s], Q[4 * s + 1], Q[4 * s + 2], Q[4 * s + 3], d0 + s * 128, s > 0);
}
template <int H>
__device__ __forceinline__ void issue_pv(float (&O)[64], const uint32_t (&Pm)[32], uint32_t d0, int acc) {
#pragma unroll
    for (int s = 4 * H; s < 4 * H + 4; s++)
        wgmma_n128_rs<0>(O, Pm[4 * s], Pm[4 * s + 1], Pm[4 * s + 2], Pm[4 * s + 3], d0 + H * (PAGE >> 4) + (s & 3) * 2, s > 0 ? 1 : acc);
}
template <int J0, int J1>
__device__ __forceinline__ void exp_groups(const float (&S)[64], uint32_t (&Pm)[32], float (&sum)[2]) {
#pragma unroll
    for (int i = 2 * J0; i < 2 * J1; i++) asm volatile("" : "+r"(Pm[i])::"memory");
#pragma unroll
    for (int j = J0; j < J1; j++) {
        const float e0 = ex2(S[4 * j]), e1 = ex2(S[4 * j + 1]), e2 = ex2(S[4 * j + 2]), e3 = ex2(S[4 * j + 3]);
        sum[0] = (j ? sum[0] + e0 : e0) + e1;
        sum[1] = (j ? sum[1] + e2 : e2) + e3;
        Pm[2 * j] = pack_bf16(e0, e1);
        Pm[2 * j + 1] = pack_bf16(e2, e3);
    }
}
__device__ __forceinline__ void shift_rows(float (&S)[64], float d0, float d1) {
#pragma unroll
    for (int j = 0; j < 16; j++) {
        S[4 * j] -= d0; S[4 * j + 1] -= d0; S[4 * j + 2] -= d1; S[4 * j + 3] -= d1;
    }
}
__device__ constexpr int chunk_src(int i) { return 4 * (4 * (i >> 3) + (i & 3)) + 2 * ((i >> 2) & 1); }
enum : uint32_t { CTL_FIRST = 1, CTL_SWITCH = 2, CTL_LAST = 4, CTL_HALF = 128, CTL_MASKHI = 256, CTL_WOUT = 512, CTL_PVHALF = 1024, CTL_PVACC = 16384,
                  CTL_SHIFT = 32768 };
__device__ __forceinline__ float quad_sum(float v) {
    v += __shfl_xor_sync(~0u, v, 1);
    return v + __shfl_xor_sync(~0u, v, 2);
}

__device__ __forceinline__ void store_part(uint8_t* base, uint32_t row_bits, int p, const uint32_t (&pk)[64], uint64_t pol) {
    asm volatile("{\n.reg .b64 d0, d1;\nxor.b64 d0, %0, %1;\nxor.b64 d1, d0, 64;\n"
                 "TS: .branchtargets P0, P1, P2, P3, P4, P5, P6, P7;\n"
                 "brx.idx.uni %2, TS;\n"
                 "P0:\n st.global.cg.L2::cache_hint.v4.u32 [d0 + 0], {%3, %4, %5, %6}, %67;\n st.global.cg.L2::cache_hint.v4.u32 [d1 + 0], {%11, %12, %13, %14}, %67;\n bra.uni DONE;\n"
                 "P1:\n st.global.cg.L2::cache_hint.v4.u32 [d0 + 0], {%7, %8, %9, %10}, %67;\n st.global.cg.L2::cache_hint.v4.u32 [d1 + 0], {%15, %16, %17, %18}, %67;\n bra.uni DONE;\n"
                 "P2:\n st.global.cg.L2::cache_hint.v4.u32 [d0 + 16384], {%19, %20, %21, %22}, %67;\n st.global.cg.L2::cache_hint.v4.u32 [d1 + 16384], {%27, %28, %29, %30}, %67;\n bra.uni DONE;\n"
                 "P3:\n st.global.cg.L2::cache_hint.v4.u32 [d0 + 16384], {%23, %24, %25, %26}, %67;\n st.global.cg.L2::cache_hint.v4.u32 [d1 + 16384], {%31, %32, %33, %34}, %67;\n bra.uni DONE;\n"
                 "P4:\n st.global.cg.L2::cache_hint.v4.u32 [d0 + 65536], {%35, %36, %37, %38}, %67;\n st.global.cg.L2::cache_hint.v4.u32 [d1 + 65536], {%43, %44, %45, %46}, %67;\n bra.uni DONE;\n"
                 "P5:\n st.global.cg.L2::cache_hint.v4.u32 [d0 + 65536], {%39, %40, %41, %42}, %67;\n st.global.cg.L2::cache_hint.v4.u32 [d1 + 65536], {%47, %48, %49, %50}, %67;\n bra.uni DONE;\n"
                 "P6:\n st.global.cg.L2::cache_hint.v4.u32 [d0 + 81920], {%51, %52, %53, %54}, %67;\n st.global.cg.L2::cache_hint.v4.u32 [d1 + 81920], {%59, %60, %61, %62}, %67;\n bra.uni DONE;\n"
                 "P7:\n st.global.cg.L2::cache_hint.v4.u32 [d0 + 81920], {%55, %56, %57, %58}, %67;\n st.global.cg.L2::cache_hint.v4.u32 [d1 + 81920], {%63, %64, %65, %66}, %67;\n bra.uni DONE;\n"
                 "DONE:\n}\n"
                 ::"l"(base), "l"((uint64_t)((p & 1) ? row_bits : 0)), "r"(p), "r"(pk[0]), "r"(pk[1]), "r"(pk[2]), "r"(pk[3]), "r"(pk[4]), "r"(pk[5]), "r"(pk[6]), "r"(pk[7]), "r"(pk[8]), "r"(pk[9]), "r"(pk[10]), "r"(pk[11]), "r"(pk[12]), "r"(pk[13]), "r"(pk[14]), "r"(pk[15]), "r"(pk[16]), "r"(pk[17]), "r"(pk[18]), "r"(pk[19]), "r"(pk[20]), "r"(pk[21]), "r"(pk[22]), "r"(pk[23]), "r"(pk[24]), "r"(pk[25]), "r"(pk[26]), "r"(pk[27]), "r"(pk[28]), "r"(pk[29]), "r"(pk[30]), "r"(pk[31]), "r"(pk[32]), "r"(pk[33]), "r"(pk[34]), "r"(pk[35]), "r"(pk[36]), "r"(pk[37]), "r"(pk[38]), "r"(pk[39]), "r"(pk[40]), "r"(pk[41]), "r"(pk[42]), "r"(pk[43]), "r"(pk[44]), "r"(pk[45]), "r"(pk[46]), "r"(pk[47]), "r"(pk[48]), "r"(pk[49]), "r"(pk[50]), "r"(pk[51]), "r"(pk[52]), "r"(pk[53]), "r"(pk[54]), "r"(pk[55]), "r"(pk[56]), "r"(pk[57]), "r"(pk[58]), "r"(pk[59]), "r"(pk[60]), "r"(pk[61]), "r"(pk[62]), "r"(pk[63]), "l"(pol)
                 : "memory");
}

__device__ __forceinline__ void store_part4(uint8_t* d0, int p, const uint32_t (&pk)[64]) {
    asm volatile("{\n.reg .b64 d1;\nxor.b64 d1, %0, 64;\n"
                 "TS: .branchtargets P0, P1, P2, P3;\n"
                 "brx.idx.uni %1, TS;\n"
                 "P0:\n st.global.cg.v4.u32 [%0 + 0], {%2, %3, %4, %5};\n st.global.cg.v4.u32 [d1 + 0], {%10, %11, %12, %13};\n bra.uni DONE;\n"
                 "P1:\n st.global.cg.v4.u32 [%0 + 1024], {%6, %7, %8, %9};\n st.global.cg.v4.u32 [d1 + 1024], {%14, %15, %16, %17};\n bra.uni DONE;\n"
                 "P2:\n st.global.cg.v4.u32 [%0 + 16384], {%18, %19, %20, %21};\n st.global.cg.v4.u32 [d1 + 16384], {%26, %27, %28, %29};\n bra.uni DONE;\n"
                 "P3:\n st.global.cg.v4.u32 [%0 + 17408], {%22, %23, %24, %25};\n st.global.cg.v4.u32 [d1 + 17408], {%30, %31, %32, %33};\n bra.uni DONE;\n"
                 "DONE:\n}\n"
                 ::"l"(d0), "r"(p), "r"(pk[0]), "r"(pk[1]), "r"(pk[2]), "r"(pk[3]), "r"(pk[4]), "r"(pk[5]), "r"(pk[6]), "r"(pk[7]), "r"(pk[8]), "r"(pk[9]), "r"(pk[10]), "r"(pk[11]), "r"(pk[12]), "r"(pk[13]), "r"(pk[14]), "r"(pk[15]), "r"(pk[16]), "r"(pk[17]), "r"(pk[18]), "r"(pk[19]), "r"(pk[20]), "r"(pk[21]), "r"(pk[22]), "r"(pk[23]), "r"(pk[24]), "r"(pk[25]), "r"(pk[26]), "r"(pk[27]), "r"(pk[28]), "r"(pk[29]), "r"(pk[30]), "r"(pk[31])
                 : "memory");
}

__device__ __forceinline__ void consumer(uint32_t sb, int pair, int c, uint8_t* out, const uint8_t* x) {
    const int tid = threadIdx.x;
    const int warp = __shfl_sync(~0u, tid >> 5, 0);
    const int w = warp >> 2, v = warp & 3;
    const int lane = __shfl_sync(~0u, tid & 31, tid & 31);

    const uint32_t empty_rel = lane == 2 ? mapa(sb + BAR_EMPTYL, c) : mapa(sb + BAR_EMPTY, lane & 1);
    auto release = [&](uint32_t grp) {
        if (lane < 3) mbar_arrive_cluster(empty_rel + (grp & 7) * 8);
    };
    auto wait_full = [&](uint32_t grp) { mbar_wait(sb + BAR_FULL + (grp & 7) * 8, (grp >> 3) & 1); };

    uint32_t g = 0;
    const uint32_t stg = sb + SM_REGION + w * PAGE + v * 2048;
    const uint32_t chunk0 = (lane >> 2) * 128 + (((lane & 3) ^ (lane >> 2)) << 4);
    auto mark_done = [&](int odd) {
        __syncwarp();
        if (lane == 0) mbar_arrive(sb + BAR_DONE + odd * 8);
    };
    auto ctx_dst = [&](int rnd, int seg) {
        const int rb = query_rowblock(pair, c, w, seg);
        return ptr_off(g_ctx, ((rb >> 1) * 64 + (rnd * 16 + (pair >> 2)) * 2) * PAGE + (rb & 1) * 8192 + v * 2048);
    };

    uint32_t ctl_tab;
    {
        const int t = lane, firstB = 2 * attn_rowblock(pair, 0) + 2 - w;
        auto is_half = [&](int u) { return (u == firstB - 1 || u == 16) && c == (u >= firstB); };
        auto block = [&](int u) { return u + (w == 1 && u >= firstB); };
        auto place = [](int j) { return ((j & 15) << 3) | ((j - (j * 43 >> 8) * 6) << 11); };
        const int jv = t ? min(2 * block(t - 1) + 2, 35) : -1, jk = t == 17 ? jv : max(2 * block(t) - 1, 0);
        const bool diag = t == firstB - 1 || t == 16;
        ctl_tab = ((t == 0 || t == firstB) ? CTL_FIRST : 0) | (t == firstB ? CTL_SWITCH : 0) | (t == 17 ? CTL_LAST : 0) |
                  (diag ? (is_half(t) ? CTL_HALF : CTL_MASKHI) : 0) | (t == firstB + 1 ? CTL_WOUT : 0) |
                  (is_half(t - 1) ? CTL_PVHALF : 0) | ((t == 1 || t == firstB + 1) ? 0 : CTL_PVACC) |
                  place(jk) | (place(jv) << 16);
    }

    uint32_t pk[64];
#pragma unroll
    for (int i = 0; i < 64; i++) asm volatile("" : "=r"(pk[i]));
    uint8_t* pend = nullptr;
    uint32_t prow = 0x400;
    auto write_part = [&](int p, uint64_t pol = evict_normal()) { store_part(pend, prow, p, pk, pol); };
    if (w == 1) bar_arrive(2, 256);

    for (int item = 0; item < 6; item++) {
        if ((0x1B >> item) & 1) {
            constexpr int nk = DC / 64;
            float acc[128];
            auto issue_kblock = [&](int first_acc) {
                wait_full(g);
                const uint32_t pg = sb + (g & 3) * (3 * PAGE);
                const uint64_t da = make_desc(pg + w * 8192, 16), db = make_desc(pg + PAGE, 16);
                wg_fence();
                wgmma_n256_ss(acc, da, db, first_acc);
                wgmma_n256_ss(acc, da + 128, db + 2, 1);
                wgmma_n256_ss(acc, da + 256, db + 4, 1);
                wgmma_n256_ss(acc, da + 384, db + 6, 1);
                wg_commit();
                g++;
            };
            if (item == 0) PROF(17, w);
            issue_kblock(0);
            if (item == 0) PROF(1, w);
            if (item == 0 && w == 0) PROF_GT(1);
            const int nparts = item == 0 ? 0 : (item == 3 ? 4 : 8);
            const int ln_row = (pair * 2 + c) * 16 + warp * 2;
            if (item == 0) {
                const uint8_t* src = ptr_off(x, ln_row * (DM * 2) + lane * 16);
#pragma unroll
                for (int i = 0; i < 8; i++) {
                    const uint4 t = __ldcg(reinterpret_cast<const uint4*>(src + i * 512));
                    pk[4 * i] = t.x; pk[4 * i + 1] = t.y; pk[4 * i + 2] = t.z; pk[4 * i + 3] = t.w;
                }
            }
#pragma unroll 1
            for (int kb = 1; kb < nk; kb++) {
                if (kb == nk - 1 && w == 1) bar_sync(4, 256);
                issue_kblock(1);
                if (kb == nk - 1 && w == 0) bar_arrive(4, 256);
                wg_wait<1>();
                release(g - 2);
                if (kb <= nparts) {
                    if (item == 4 && kb == 1) mbar_wait(sb + BAR_DEP + 16, 0);
                    write_part(kb - 1, item == 3 ? evict_first() : evict_normal());
                    if (kb == nk - 1) write_part(nk - 1);
                    if (kb == nparts || kb == nk - 1) mark_done(item != 3);
                }
                if (g < 8) {
                    float s[2], q[2];
                    if (g == 4) {
                        ln_sums<0>(pk, s[0], q[0]);
                        pk[32] = __float_as_uint(s[0]); pk[33] = __float_as_uint(q[0]);
                    }
                    if (g == 5) {
                        ln_sums<16>(pk, s[1], q[1]);
                        pk[34] = __float_as_uint(s[1]); pk[35] = __float_as_uint(q[1]);
                    }
                    if (g == 6) {
#pragma unroll
                        for (int r = 0; r < 2; r++) { s[r] = __uint_as_float(pk[32 + 2 * r]); q[r] = __uint_as_float(pk[33 + 2 * r]); }
                        const bool hi = lane & 16, od = lane & 8;
                        float a = hi ? s[1] : s[0], b = hi ? q[1] : q[0];
                        a += __shfl_xor_sync(~0u, hi ? s[0] : s[1], 16);
                        b += __shfl_xor_sync(~0u, hi ? q[0] : q[1], 16);
                        float t = od ? b : a;
                        t += __shfl_xor_sync(~0u, od ? a : b, 8);
#pragma unroll
                        for (int o = 4; o; o >>= 1) t += __shfl_xor_sync(~0u, t, o);
#pragma unroll
                        for (int r = 0; r < 2; r++) {
                            s[r] = __shfl_sync(~0u, t, 16 * r);
                            q[r] = __shfl_sync(~0u, t, 16 * r + 8);
                        }
                        ln_finish(s[0], q[0], pk[36], pk[37], pk[38]);
                        ln_finish(s[1], q[1], pk[39], pk[40], pk[41]);
                    }
                    if (g == 6) ln_apply<0>(pk, pk[36], pk[37], pk[38], ptr_off(g_xn, image_offset(ln_row, lane)));
                    if (g == 7) {
                        ln_apply<16>(pk, pk[39], pk[40], pk[41], ptr_off(g_xn, image_offset(ln_row + 1, lane)));
                        mark_done(0);
                    }
                }
            }
            wg_wait<0>();
            reg_fence(acc);
            release(g - 1);
            PROF(2 + 2 * item, w);
            if (w == 0) PROF_GT(2 + 2 * item);
#pragma unroll
            for (int i = 0; i < 64; i++) pk[i] = pack_bf16(acc[chunk_src(i)], acc[chunk_src(i) + 1]);
            const uint32_t vrow = (v >> 1) * 32 + (lane >> 3) * 8 + (v & 1) * 4 + ((lane >> 2) & 1);
            pend = ptr_off(g_kv, ((kv_head(pair) + (item == 1 || item == 4 ? 8 : 0)) * 16 + kv_tokens(pair) * 2) * 65536 + w * 8192 +
                                     (c ? 32768 + vrow * 128 + (((lane & 3) ^ (vrow & 7)) << 4) : v * 2048 + chunk0));
            prow = c ? 0x120 : 0x400;
            PROF(3 + 2 * item, w);
            continue;
        }

        float O[64], S[64];
        auto issue_q = [&](int first_acc) {
            wait_full(g);
            const uint32_t pg = sb + (g & 3) * (3 * PAGE);
            const uint64_t da = make_desc(pg + w * 8192, 16), db = make_desc(pg + 2 * PAGE, 8192);
            const uint64_t dab = make_desc(pg + PAGE + (1 - w) * 8192, 16);
            wg_fence();
#pragma unroll
            for (int q = 0; q < 4; q++) wgmma_n128_ss(S, da + 2 * q, db + 128 * q, q ? 1 : first_acc);
            wg_commit();
#pragma unroll
            for (int q = 0; q < 4; q++) wgmma_n128_ss(O, dab + 2 * q, db + 128 * q, q ? 1 : first_acc);
            wg_commit();
            g++;
        };
        issue_q(0);
#pragma unroll 1
        for (int kb = 1; kb < DM / 64; kb++) {
            if (kb == DM / 64 - 2 && w == 1) bar_sync(4, 256);
            issue_q(1);
            if (kb == DM / 64 - 1 && w == 0) bar_arrive(4, 256);
            wg_wait<2>();
            release(g - 2);
            if (kb <= 8) {
                write_part(kb - 1);
                if (kb == 8) mark_done(0);
            }
        }
        uint32_t Q[32], Pm[32];
#pragma unroll
        for (int i = 0; i < 32; i++) Pm[i] = pk[32 + i];
        float lim = (float)(v * 16 + (lane >> 2) - 8 * (lane & 3));
        float mc[2] = {0.f, 0.f}, l[2] = {0.f, 0.f}, scale[2] = {0.f, 0.f}, sum[2];
        uint32_t ctl = __shfl_sync(~0u, ctl_tab, 0), nxt = __shfl_sync(~0u, ctl_tab, 1);
        int t = 1;
        asm volatile("" : "+f"(lim), "+f"(mc[0]), "+f"(mc[1]), "+f"(l[0]), "+f"(l[1]), "+r"(ctl), "+r"(nxt), "+r"(t));
        wg_wait<1>();
        reg_fence(S);
#pragma unroll
        for (int i = 0; i < 32; i++) Q[i] = pack_bf16(S[2 * i] * SM_SCALE, S[2 * i + 1] * SM_SCALE);
        reg_fence(Q);
        wait_full(g);
        wg_wait<0>();
        reg_fence(O);
        PROF(2 + 2 * item, w);
        if (w == 0) PROF_GT(2 + 2 * item);

        const uint32_t qaddr = stg + lane * 16;
        auto put_queries = [&](const float (&A)[64]) {
#pragma unroll
            for (int i = 0; i < 8; i++)
                sts128(qaddr + (i >> 2) * 8192 + (i & 3) * 512, pack_bf16(A[8 * i] * SM_SCALE, A[8 * i + 1] * SM_SCALE), pack_bf16(A[8 * i + 2] * SM_SCALE, A[8 * i + 3] * SM_SCALE),
                       pack_bf16(A[8 * i + 4] * SM_SCALE, A[8 * i + 5] * SM_SCALE), pack_bf16(A[8 * i + 6] * SM_SCALE, A[8 * i + 7] * SM_SCALE));
        };
        auto get_queries = [&]() {
#pragma unroll
            for (int i = 0; i < 8; i++) lds128(qaddr + (i >> 2) * 8192 + (i & 3) * 512, Q[4 * i], Q[4 * i + 1], Q[4 * i + 2], Q[4 * i + 3]);
        };
        const uint32_t kdesc0 = (uint32_t)make_desc(sb, PAGE), vdesc0 = (uint32_t)make_desc(sb, 16);
        auto wait_block = [&](uint32_t word) { mbar_wait(sb + BAR_FULL + (word & 56), (word >> 6) & 1); };
        auto write_out = [&](auto early) {
            uint8_t* dst = ctx_dst(item == 5, 0);
            uint8_t* d[2] = {ptr_off(dst, chunk0), ptr_off(dst, chunk0 ^ 64)};
#pragma unroll
            for (int i = early.value ? 0 : WN; i < (early.value ? WN : 8); i++) {
                const float sc = scale[i & 1];
                uint32_t q[4];
#pragma unroll
                for (int k = 0; k < 4; k++) q[k] = pack_bf16(O[chunk_src(4 * i + k)] * sc, O[chunk_src(4 * i + k) + 1] * sc);
                if (early.value && i > 0) {
#pragma unroll
                    for (int k = 0; k < 4; k++) O[4 * (i - 1) + k] = __uint_as_float(q[k]);
                }
                stg_hint(d[(i >> 1) & 1] + (i >> 2) * PAGE + (i & 1) * 1024, q[0], q[1], q[2], q[3], item == 2 ? evict_first() : evict_normal());
            }
            if (!early.value) mark_done(1);
        };
        put_queries(O);
        bar_sync(2 + w, 256);
        if (!(ctl & CTL_HALF)) {
            wg_fence();
            issue_qk(S, Q, kdesc0);
            wg_commit();
            wg_fence();
            wg_commit();
            wg_commit();
            bar_arrive(3 - w, 256);
            wg_wait<2>();
            reg_fence(S);
        } else {
            float T[32];
            wg_fence();
            issue_qk_half(T, Q, kdesc0);
            wg_commit();
            wg_fence();
            wg_commit();
            wg_commit();
            bar_arrive(3 - w, 256);
            wg_wait<2>();
            reg_fence(T);
#pragma unroll
            for (int i = 0; i < 32; i++) S[i] = T[i];
        }
        for (;;) {
            const bool kready = mbar_try(sb + BAR_FULL + (nxt & 56), (nxt >> 6) & 1);
            if (ctl & (CTL_HALF | CTL_MASKHI | CTL_SHIFT)) {
                if (ctl & CTL_HALF) mask_half<0>(S, lim, v);
                if (ctl & CTL_MASKHI) mask_half<8>(S, lim, v);
                if (ctl & CTL_SHIFT) shift_rows(S, mc[0], mc[1]);
            }
            float early[4 * EARLY];
#pragma unroll
            for (int j = 0; j < EARLY; j++) {
#pragma unroll
                for (int i = 4 * j; i < 4 * j + 4; i++) early[i] = ex2(S[i]);
                sum[0] = (j ? sum[0] + early[4 * j] : early[4 * j]) + early[4 * j + 1];
                sum[1] = (j ? sum[1] + early[4 * j + 2] : early[4 * j + 2]) + early[4 * j + 3];
            }
            const uint32_t tie = __float_as_uint(sum[0]) & __float_as_uint(sum[1]) & (ctl & 0x80000000u);
            if (lane < 3) mbar_arrive_cluster(empty_rel + tie + (ctl & 56));
            wg_wait<1>();
#pragma unroll
            for (int j = 0; j < EARLY; j++) {
                asm volatile("" : "+r"(Pm[2 * j]), "+r"(Pm[2 * j + 1])::"memory");
                Pm[2 * j] = pack_bf16(early[4 * j], early[4 * j + 1]);
                Pm[2 * j + 1] = pack_bf16(early[4 * j + 2], early[4 * j + 3]);
            }
            exp_groups<EARLY, 8>(S, Pm, sum);
            const bool half = ctl & CTL_HALF;
            if (!half) {
                wg_wait<0>();
                reg_fence(O);
                if (lane < 3) mbar_arrive_cluster(empty_rel + ((ctl >> 16) & 56));
                exp_groups<8, 16>(S, Pm, sum);
            } else {
                asm volatile("wgmma.wait_group.sync.aligned 0;\n" ::: "memory");
                reg_fence(O);
                if (lane < 3) asm volatile("mbarrier.arrive.shared::cluster.b64 _, [%0];\n" ::"r"(empty_rel + ((ctl >> 16) & 56)) : "memory");
            }
            const bool over = !(sum[0] + sum[1] <= SUM_HI);
            const bool first = ctl & CTL_FIRST, suspect = over || (first && !(fminf(sum[0], sum[1]) >= SUM_LO));
            if (__any_sync(~0u, suspect || !kready) || (((ctl & CTL_SWITCH) | (nxt & (CTL_SWITCH | CTL_LAST | CTL_HALF))) != 0)) {
                if (!kready) wait_block(nxt);
                bool bad = __any_sync(~0u, suspect);
                if (bad) {
                    uint32_t b0 = __ballot_sync(~0u, sum[0] >= SUM_LO), b1 = __ballot_sync(~0u, sum[1] >= SUM_LO);
                    b0 |= b0 >> 1; b1 |= b1 >> 1;
                    b0 |= b0 >> 2; b1 |= b1 >> 2;
                    bad = __any_sync(~0u, over) || (first && (b0 & b1 & 0x11111111u) != 0x11111111u);
                }
                if (bad) {
                    float d0 = fmaxf(S[0], S[1]), d1 = fmaxf(S[2], S[3]);
#pragma unroll
                    for (int j = 1; j < 8; j++) {
                        d0 = fmaxf(d0, fmaxf(S[4 * j], S[4 * j + 1]));
                        d1 = fmaxf(d1, fmaxf(S[4 * j + 2], S[4 * j + 3]));
                    }
                    if (!half) {
#pragma unroll
                        for (int j = 8; j < 16; j++) {
                            d0 = fmaxf(d0, fmaxf(S[4 * j], S[4 * j + 1]));
                            d1 = fmaxf(d1, fmaxf(S[4 * j + 2], S[4 * j + 3]));
                        }
                    }
                    d0 = fmaxf(d0, __shfl_xor_sync(~0u, d0, 1));
                    d1 = fmaxf(d1, __shfl_xor_sync(~0u, d1, 1));
                    d0 = fmaxf(d0, __shfl_xor_sync(~0u, d0, 2));
                    d1 = fmaxf(d1, __shfl_xor_sync(~0u, d1, 2));
                    if (!first) {
                        d0 = fmaxf(d0, 0.f);
                        d1 = fmaxf(d1, 0.f);
                        const float a0 = ex2(-d0), a1 = ex2(-d1);
#pragma unroll
                        for (int j = 0; j < 16; j++) {
                            O[4 * j] *= a0; O[4 * j + 1] *= a0; O[4 * j + 2] *= a1; O[4 * j + 3] *= a1;
                        }
                        l[0] *= a0; l[1] *= a1;
                    }
                    mc[0] += d0; mc[1] += d1;
                    ctl_tab |= CTL_SHIFT;
                    nxt |= CTL_SHIFT;
                    shift_rows(S, d0, d1);
                    exp_groups<0, 8>(S, Pm, sum);
                    if (!half) exp_groups<8, 16>(S, Pm, sum);
                }
                if (ctl & CTL_SWITCH) write_out(std::true_type());
                if (nxt & CTL_LAST) break;
                if (nxt & CTL_SWITCH) {
                    get_queries();
                    nxt &= ~CTL_SHIFT;
                    ctl_tab &= ~CTL_SHIFT;
                }
                if (nxt & CTL_HALF) {
                    ctl = nxt;
                    float T[32];
                    bar_sync(2 + w, 256);
                    wg_fence();
                    issue_qk_half(T, Q, kdesc0 + (ctl & 0x3800));
                    wg_commit();
                    l[0] += sum[0]; l[1] += sum[1];
                    nxt = __shfl_sync(~0u, ctl_tab, ++t);
                    wait_block(ctl >> 16);
                    const uint32_t vdesc = vdesc0 + ((ctl >> 16) & 0x3800);
                    wg_fence();
                    issue_pv<0>(O, Pm, vdesc, ctl & CTL_PVACC);
                    wg_commit();
                    issue_pv<1>(O, Pm, vdesc, 1);
                    wg_commit();
                    bar_arrive(3 - w, 256);
                    wg_wait<2>();
                    reg_fence(T);
#pragma unroll
                    for (int i = 0; i < 32; i++) S[i] = T[i];
                    continue;
                }
            }
            ctl = nxt;
            bar_sync(2 + w, 256);
            wg_fence();
            issue_qk(S, Q, kdesc0 + (ctl & 0x3800));
            wg_commit();
            l[0] += sum[0]; l[1] += sum[1];
            nxt = __shfl_sync(~0u, ctl_tab, ++t);
            if (ctl & (CTL_SWITCH | CTL_WOUT)) {
                if (ctl & CTL_SWITCH) {
                    scale[0] = rcp_approx(quad_sum(l[0]));
                    scale[1] = rcp_approx(quad_sum(l[1]));
                    l[0] = l[1] = mc[0] = mc[1] = 0.f;
                    if (w == 1) { release((ctl >> 3) - 2); release((ctl >> 3) + 1); }
                } else {
                    write_out(std::false_type());
                }
            }
            wait_block(ctl >> 16);
            const uint32_t vdesc = vdesc0 + ((ctl >> 16) & 0x3800);
            if (!(ctl & CTL_PVHALF)) {
                wg_fence();
                issue_pv<0>(O, Pm, vdesc, ctl & CTL_PVACC);
                wg_commit();
                issue_pv<1>(O, Pm, vdesc, 1);
                wg_commit();
            } else {
                wg_fence();
                issue_pv<0>(O, Pm, vdesc, ctl & CTL_PVACC);
                wg_commit();
                wg_commit();
            }
            bar_arrive(3 - w, 256);
            wg_wait<2>();
            reg_fence(S);
        }
        g += 36;
        const uint32_t vdesc = vdesc0 + (nxt & 0x3800);
        if (nxt & CTL_PVHALF) {
            wg_fence();
            issue_pv<0>(O, Pm, vdesc, nxt & CTL_PVACC);
            wg_commit();
        } else {
            wg_fence();
            issue_pv<0>(O, Pm, vdesc, nxt & CTL_PVACC);
            issue_pv<1>(O, Pm, vdesc, 1);
            wg_commit();
        }
        l[0] += sum[0]; l[1] += sum[1];
        ctl_tab = (ctl_tab & ~(0x00780078u | CTL_SHIFT)) | ((ctl_tab + 0x00200020u) & 0x00780078u);
        const float i0 = rcp_approx(quad_sum(l[0])), i1 = rcp_approx(quad_sum(l[1]));
        const uint32_t tie = __float_as_uint(i0) & __float_as_uint(i1) & (nxt & 0x80000000u);
        if (lane + tie < (w ? 0 : 3)) mbar_arrive_cluster(empty_rel + ((g - 3) & 7) * 8);
        auto finish_attention = [&](uint32_t next) {
            reg_fence(O);
            if (w == 0) release(next - 2);
            release(next - 1);
#pragma unroll
            for (int i = 0; i < 32; i++) {
                const float sc = (i & 4) ? i1 : i0;
                pk[i] = pack_bf16(O[chunk_src(i)] * sc, O[chunk_src(i) + 1] * sc);
            }
            pend = ptr_off(ctx_dst(item == 5, 1), chunk0);
            PROF(3 + 2 * item, w);
            if (w == 0) PROF_GT(3 + 2 * item);
        };
        if (item != 5) {
            wg_wait<0>();
            finish_attention(g);
            prow = 0x400;
#pragma unroll
            for (int i = 32; i < 64; i++) pk[i] = Pm[i - 32];
            continue;
        }

        float acc[64];
        uint32_t slot = 0;
        auto issue_out = [&](int first_acc) {
            wait_full(g);
            const uint64_t da = make_desc(sb + slot + w * 8192, 16), db = make_desc(sb + slot + PAGE, 8192);
            wg_fence();
#pragma unroll
            for (int q = 0; q < 4; q++) wgmma_n128_ss(acc, da + 2 * q, db + 128 * q, q ? 1 : first_acc);
            wg_commit();
            g++;
            slot = slot == SM_REGION - 2 * PAGE ? 0 : slot + 2 * PAGE;
        };
        issue_out(0);
        wg_wait<1>();
        finish_attention(g - 1);
#pragma unroll 1
        for (int kb = 1; kb < 64 - PEEL; kb++) {
            issue_out(1);
            wg_wait<1>();
            release(g - 2);
            if (kb <= 8 && !(kb & 1)) {
                store_part4(pend, (kb >> 1) - 1, pk);
                if (kb == 8) mark_done(0);
            }
            if (kb >= 32 - PEEL && ((kb + PEEL) & 3) == 2 * w) {
                uint32_t u0, u1, u2, u3;
                const uint32_t a = stg + ((kb + PEEL) & 16) * 512 + ((kb + PEEL) & 12) * 128 + lane * 16;
                mbar_wait(sb + BAR_G + w * 8, 0);
                lds128(a, u0, u1, u2, u3);
                sts128(a, pack_bf16(silu_f(bf_lo(u0)), silu_f(bf_hi(u0))), pack_bf16(silu_f(bf_lo(u1)), silu_f(bf_hi(u1))),
                       pack_bf16(silu_f(bf_lo(u2)), silu_f(bf_hi(u2))), pack_bf16(silu_f(bf_lo(u3)), silu_f(bf_hi(u3))));
            }
        }
        const uint32_t goff = (out_rows(pair) * 256 + c * 128 + w * 64 + v * 16 + (lane >> 3)) * (DM * 2) +
                              out_cols(pair) * 128 + (((lane & 7) ^ (lane >> 3)) << 4);
        uint32_t xr[32], gr[32];
        {
            const uint8_t* src[2] = {ptr_off(x, goff), ptr_off(x, goff ^ 64)};
#pragma unroll
            for (int i = 0; i < 8; i++) {
                const uint4 t = ldg_hint(src[i & 1] + (i & 3) * (4 * DM * 2) + (i >> 2) * 128, evict_first());
                xr[4 * i] = t.x; xr[4 * i + 1] = t.y; xr[4 * i + 2] = t.z; xr[4 * i + 3] = t.w;
            }
        }
#pragma unroll 1
        for (int i = 0; i < PEEL; i++) {
            if (i == PEEL - STAG && w == 1) bar_sync(4, 256);
            issue_out(1);
            if (i == PEEL - 1 && w == 0) bar_arrive(4, 256);
            wg_wait<1>();
        }
        asm volatile("barrier.cluster.arrive.relaxed.aligned;" ::: "memory");
#pragma unroll
        for (int i = 0; i < 8; i++) lds128(stg + (i >> 2) * 8192 + (i & 3) * 512 + lane * 16, gr[4 * i], gr[4 * i + 1], gr[4 * i + 2], gr[4 * i + 3]);
        uint8_t* dst[2] = {ptr_off(out, goff), ptr_off(out, goff ^ 64)};
        __syncwarp();
        wg_wait<0>();
        reg_fence(acc);
        PROF(14, w);
        if (w == 0) PROF_GT(14);
#pragma unroll
        for (int s = 0; s < 8; s++)
            stmatrix_x4(slab_addr(stg, lane, s), pack_bf16(acc[8 * s], acc[8 * s + 1]), pack_bf16(acc[8 * s + 2], acc[8 * s + 3]),
                        pack_bf16(acc[8 * s + 4], acc[8 * s + 5]), pack_bf16(acc[8 * s + 6], acc[8 * s + 7]));
        __syncwarp();
        uint32_t o[32];
#pragma unroll
        for (int i = 0; i < 8; i++) lds128(stg + (i >> 2) * 8192 + (i & 3) * 512 + lane * 16, o[4 * i], o[4 * i + 1], o[4 * i + 2], o[4 * i + 3]);
#pragma unroll
        for (int i = 0; i < 8; i++) {
#pragma unroll
            for (int k = 0; k < 4; k++) xr[4 * i + k] = bf2_add(xr[4 * i + k], bf2_mul(o[4 * i + k], gr[4 * i + k]));
            __stcg(reinterpret_cast<uint4*>(dst[i & 1] + (i & 3) * (4 * DM * 2) + (i >> 2) * 128), make_uint4(xr[4 * i], xr[4 * i + 1], xr[4 * i + 2], xr[4 * i + 3]));
        }
        PROF(28, w);
        return;
    }
}

__global__ void __cluster_dims__(2, 1, 1) __launch_bounds__(384, 1)
fused_kernel(const __grid_constant__ CUtensorMap m_ckv, const __grid_constant__ CUtensorMap m_wuk,
             const __grid_constant__ CUtensorMap m_wuv, const __grid_constant__ CUtensorMap m_wq,
             const __grid_constant__ CUtensorMap m_wo, const __grid_constant__ CUtensorMap m_gate,
             const __grid_constant__ CUtensorMap m_up, const __grid_constant__ CUtensorMap m_down, const Params P) {
    extern __shared__ __align__(1024) uint8_t smem[];
    const uint32_t sb = __shfl_sync(~0u, smem_u32(smem), 0);
    const int tid = threadIdx.x;
    const int cl = blockIdx.x >> 1, c = blockIdx.x & 1;
    const int pair = cl >= 64 ? cl : cl < 4 ? cl * 16 + 15 : cl < 36 ? ((cl - 4) >> 3) * 16 + ((cl - 4) & 7)
                                                                    : ((cl - 36) / 7) * 16 + 8 + (cl - 36) % 7;
    const bool starter = tid == 256 && pair < NMAIN / 2;
    const CUtensorMap* m_wu = c ? &m_wuv : &m_wuk;
    if (tid == 256) {
        mbar_init(sb + BAR_FULL, 1);
        if (starter) {
            asm volatile("fence.mbarrier_init.release.cluster;" ::: "memory");
            mbar_expect_tx(sb + BAR_FULL, 3 * PAGE);
            tma_3d(sb, m_wu, 0, 0, kv_head(pair) * 2, sb + BAR_FULL);
            tma_3d(sb + PAGE, &m_ckv, 0, kv_tokens(pair) * 256, 0, sb + BAR_FULL);
            tma_3d(sb + 2 * PAGE, &m_ckv, 0, kv_tokens(pair) * 256 + 128, 0, sb + BAR_FULL);
        }
#pragma unroll
        for (int i = 1; i < NBAR; i++) mbar_init(sb + SM_BAR + i * 8, (i >> 3) == 1 ? 16 : i >= 25 ? 8 : 1);
        asm volatile("fence.mbarrier_init.release.cluster;" ::: "memory");
    }
    if (starter) {
#pragma unroll 1
        for (int kb = 1; kb < 4; kb++) mbar_expect_tx(sb + BAR_FULL + kb * 8, 3 * PAGE);
        tma_3d(sb + 3 * PAGE, m_wu, 0, 64, kv_head(pair) * 2, sb + BAR_FULL + 8);
    }
    PROF(18, (tid >> 7) & 1);
    __syncthreads();
    cluster_sync();
    PROF(22, (tid >> 7) & 1);
    PROF(19, (tid >> 7) & 1);
    const int warp = __shfl_sync(~0u, tid >> 5, 0), lane = tid & 31;
    auto dump_prof = [&]() {
    };
    if (pair >= NMAIN / 2) {
        if (warp < 8) ffn_cta(smem, sb, blockIdx.x - NMAIN, __ldcg(&g_sync.done) / NCTA, P.w_r);
        else if (tid == 256) ffn_producer(sb, blockIdx.x - NMAIN, &m_gate, &m_up, &m_down);
        __syncwarp();
        PROF(29, tid >> 7);
        cluster_sync();
        if (tid == 0) atomicAdd(&g_sync.done, 1u);
        if (warp < 8) dump_prof();
    } else if (warp < 8) {
        asm volatile("setmaxnreg.inc.sync.aligned.u32 232;");
        consumer(sb, pair, c, P.out, (const uint8_t*)P.x);
        PROF(29, tid >> 7);
        asm volatile("barrier.cluster.wait.aligned;" ::: "memory");
        dump_prof();
    } else {
        asm volatile("setmaxnreg.dec.sync.aligned.u32 40;");
        if (starter) {
#pragma unroll 1
            for (int kb = 1; kb < 4; kb++) {
                if (kb > 1) tma_3d(sb + kb * (3 * PAGE), m_wu, 0, kb * 64, kv_head(pair) * 2, sb + BAR_FULL + kb * 8);
                tma_3d_mc(sb + kb * (3 * PAGE) + (1 + c) * PAGE, &m_ckv, 0, kv_tokens(pair) * 256 + c * 128, kb, sb + BAR_FULL + kb * 8);
            }
        }
        if (warp == 10) {
            sync_helper(sb, lane, pair, c);
        } else if (warp & 1) {
            fetch_helper((warp & 2) ? P.w_uv : P.w_uk, sb, (warp >> 1) & 1, lane, pair, c);
        } else {
            producer(P, sb, pair, c, &m_ckv, m_wu, &m_wq, &m_wo);
        }
        bar_sync(6, 128);
        if (tid == 256) atomicAdd(&g_sync.done, 1u);
        cluster_sync();
    }
}

typedef CUresult (*EncodeFn)(CUtensorMap*, CUtensorMapDataType, cuuint32_t, void*, const cuuint64_t*, const cuuint64_t*,
                             const cuuint32_t*, const cuuint32_t*, CUtensorMapInterleave, CUtensorMapSwizzle,
                             CUtensorMapL2promotion, CUtensorMapFloatOOBfill);

void make_map_w(EncodeFn fn, CUtensorMap* m, const void* ptr, int rows, int cols, int blocks, int box_rows = 32) {
    cuuint64_t dims[3] = {64, (cuuint64_t)rows, (cuuint64_t)cols / 64};
    cuuint64_t strides[2] = {(cuuint64_t)cols * 2, 128};
    cuuint32_t box[3] = {64, (cuuint32_t)box_rows, (cuuint32_t)blocks};
    cuuint32_t es[3] = {1, 1, 1};
    fn(m, CU_TENSOR_MAP_DATA_TYPE_BFLOAT16, 3, const_cast<void*>(ptr), dims, strides, box, es, CU_TENSOR_MAP_INTERLEAVE_NONE,
       CU_TENSOR_MAP_SWIZZLE_128B, CU_TENSOR_MAP_L2_PROMOTION_L2_256B, CU_TENSOR_MAP_FLOAT_OOB_FILL_NONE);
}

}

extern "C" void kernel_launch(void* const* d_in, const int* in_sizes, int n_in, void* d_out, int out_size) {
    static EncodeFn fn = nullptr;
    if (!fn) {
        void* f = nullptr;
        cudaDriverEntryPointQueryResult qr;
        cudaGetDriverEntryPoint("cuTensorMapEncodeTiled", &f, cudaEnableDefault, &qr);
        fn = (EncodeFn)f;
        cudaFuncSetAttribute(fused_kernel, cudaFuncAttributeMaxDynamicSharedMemorySize, SMEM_BYTES);
    }
    CUtensorMap m_ckv, m_wuk, m_wuv, m_wq, m_wo, m_gate, m_up, m_down;
    make_map_w(fn, &m_gate, d_in[8], DM, FF, FS / 64, 16);
    make_map_w(fn, &m_up, d_in[9], DM, FF, FS / 64, 16);
    make_map_w(fn, &m_down, d_in[10], FF, DM, DM / 64, 16);
    make_map_w(fn, &m_ckv, d_in[1], SEQ, DC, 1, 128);
    make_map_w(fn, &m_wq, d_in[2], DM, NH * 128, 1, 64);
    make_map_w(fn, &m_wuk, d_in[3], DC, NH * 128, 2, 64);
    make_map_w(fn, &m_wuv, d_in[4], DC, NH * 128, 2, 64);
    make_map_w(fn, &m_wo, d_in[5], NH * 128, DM, 1, 64);
    Params P;
    P.x = (const __nv_bfloat16*)d_in[0];
    P.w_r = (const __nv_bfloat16*)d_in[7];
    P.c_kv = (const uint8_t*)d_in[1];
    P.w_uk = (const uint8_t*)d_in[3];
    P.w_uv = (const uint8_t*)d_in[4];
    P.out = (uint8_t*)d_out;
    fused_kernel<<<NCTA, 384, SMEM_BYTES>>>(m_ckv, m_wuk, m_wuv, m_wq, m_wo, m_gate, m_up, m_down, P);
}
```
